```python
import torch

def _softmax(x, axis=-1):
    return torch.softmax(x, dim=axis)

def _gelu(x):
    return torch.nn.functional.gelu(x, approximate='tanh')

def _silu(x):
    return torch.nn.functional.silu(x)

def _sigmoid(x):
    return torch.sigmoid(x)

def _layernorm(x, axis=-1, eps=1e-05):
    m = x.mean(dim=axis, keepdim=True)
    v = x.var(dim=axis, keepdim=True, unbiased=False)
    return (x - m) / torch.sqrt(v + eps)

def _scatter_add(tgt, idx, src, axis=0):
    return tgt.clone().index_add_(axis, idx, src)

def _segment_sum(src, seg, n):
    out = torch.zeros((n,) + src.shape[1:], dtype=src.dtype)
    return out.index_add_(0, seg, src)

def _pad(x, pw):
    flat = tuple((v for pair in reversed(pw) for v in pair))
    return torch.nn.functional.pad(x, flat)
kernel_name = 'adaLN_cond__sliding_block_cached__glu_gated_swiglu__decode'

def setup_inputs():

    _w = lambda a: (lambda t: t.to(torch.bfloat16) if t.is_floating_point() else t)(torch.as_tensor(a))

    def _A_setup():
        B, Sq, D = (2, 1, 512)
        Hq, Hkv, Sk, Dh = (32, 32, 16384, 128)
        assert Hq % Hkv == 0, (Hq, Hkv)
        return {'x': _w((lambda *s: torch.randn(*s, dtype=torch.bfloat16) * 0.05)(B, Sq, D)), 'k_cache': _w((lambda *s: torch.randn(*s, dtype=torch.bfloat16) * 3.2)(B, Hkv, Sk, Dh)), 'v_cache': _w((lambda *s: torch.randn(*s, dtype=torch.bfloat16) * 3.2)(B, Hkv, Sk, Dh)), 'wq': _w((lambda *s: torch.randn(*s, dtype=torch.bfloat16) * 3.2)(D, Hq * Dh) * D ** (-0.5)), 'wo': _w((lambda *s: torch.randn(*s, dtype=torch.bfloat16) * 3.2)(Hq * Dh, D) * (Hq * Dh) ** (-0.5))}
    _A_in = _A_setup()

    def _B_setup():
        B, S, D, F = (2, 1, 512, 1376)
        return {'x': _w((lambda *s: torch.randn(*s, dtype=torch.bfloat16) * 0.05)(B, S, D)), 'w1': _w((lambda *s: torch.randn(*s, dtype=torch.bfloat16) * 1.6)(D, F) * (2.0 / D) ** 0.5), 'w3': _w((lambda *s: torch.randn(*s, dtype=torch.bfloat16) * 1.6)(D, F) * (2.0 / D) ** 0.5), 'w2': _w((lambda *s: torch.randn(*s, dtype=torch.bfloat16) * 1.6)(F, D) * (2.0 / F) ** 0.5)}
    _B_in = _B_setup()
    return {'A_x': _A_in['x'], 'A_k_cache': _A_in['k_cache'], 'A_v_cache': _A_in['v_cache'], 'A_wq': _A_in['wq'], 'A_wo': _A_in['wo'], 'B_x': _B_in['x'], 'B_w1': _B_in['w1'], 'B_w3': _B_in['w3'], 'B_w2': _B_in['w2'], 'c': _w((lambda *s: torch.randn(*s, dtype=torch.bfloat16) * 0.2)(2, 512) * 8.0), 'w_mod': _w((lambda *s: torch.randn(*s, dtype=torch.bfloat16) * 0.2)(512, 6 * 512) * 512 ** (-0.5) * 8.0)}

def reference(A_x, A_k_cache, A_v_cache, A_wq, A_wo, B_x, B_w1, B_w3, B_w2, c, w_mod):

    def _A_ref(x, k_cache, v_cache, wq, wo):
        B, Sq, D = x.shape
        Hq, Dh = (32, 128)
        Hkv, Sk = (k_cache.shape[1], k_cache.shape[2])
        W = min(4096, max(256, Sk // 4))
        rep = Hq // Hkv
        q = (lambda x, *d: x.permute(*d))((x @ wq).reshape(B, Sq, Hq, Dh), 0, 2, 1, 3)
        k = (lambda x, n, axis: torch.repeat_interleave(x, n, dim=axis))(k_cache[:, :, Sk - W:, :], rep, axis=1)
        v = (lambda x, n, axis: torch.repeat_interleave(x, n, dim=axis))(v_cache[:, :, Sk - W:, :], rep, axis=1)
        scores = torch.einsum('bhqd,bhkd->bhqk', q, k) * Dh ** (-0.5)
        p = _softmax(scores, axis=-1)
        o = torch.einsum('bhqk,bhkd->bhqd', p, v)
        return (lambda x, *d: x.permute(*d))(o, 0, 2, 1, 3).reshape(B, Sq, Hq * Dh) @ wo

    def _B_ref(x, w1, w3, w2):
        gate = torch.einsum('bsd,df->bsf', x, w1)
        up = torch.einsum('bsd,df->bsf', x, w3)
        h = _silu(gate) * up
        out = torch.einsum('bsf,fd->bsd', h, w2)
        return out
    x = A_x
    mod = (_silu(c) @ w_mod).reshape(c.shape[0], 6, 1, -1)
    sa, ca, ga, sb, cb, gb = (mod[:, 0].clone(), mod[:, 1].clone(), mod[:, 2].clone(), mod[:, 3].clone(), mod[:, 4].clone(), mod[:, 5].clone())
    h = _layernorm(x, axis=-1) * (1 + ca) + sa
    x = x + ga * _A_ref(h, A_k_cache, A_v_cache, A_wq, A_wo)
    h = _layernorm(x, axis=-1) * (1 + cb) + sb
    x = x + gb * _B_ref(h, B_w1, B_w3, B_w2)
    return x
```

```cpp
#include <cuda_runtime.h>
#include <cuda.h>
#include <cuda_bf16.h>
#include <stdint.h>

namespace {

constexpr int D_ = 512, DH = 128, SK = 16384, WIN = 4096, FF = 1376, QD = 4096, MODW = 3072;
constexpr int NCTA = 128;
constexpr int TILE_BYTES = 16384;
constexpr int NT = 32;
constexpr int STAGES = 13;
constexpr int K_FIRST = 2;
constexpr int FIRST_N = 5;
constexpr int WO_AT = 20;
constexpr int WO_EARLY = 3;
constexpr int PACE = 656;
constexpr int LEAD_NS = 1350;
constexpr int GATE_X = 23;
constexpr int POLL_NS = 300;
constexpr int ALPHA16 = 4;
constexpr int GU_NS = 5075;
constexpr int W2_NS = 6270;
constexpr int GB_LEAD = 390;
constexpr int NQ = 4;
constexpr int PROBES = 6;
constexpr int PROBE_NS = 1000;
constexpr int HEAD_TID = 256;
constexpr int N_WMOD = 0, N_WQ = 2, N_K = 6, N_V = N_K + NT, N_WO = N_V + WO_AT, N_V2 = N_WO + WO_EARLY, N_WO2 = N_V + NT + WO_EARLY, N_FFN = N_V + NT + 4;
constexpr int N_GATE = N_V + GATE_X + WO_EARLY;
constexpr int THREADS = 320;
constexpr int N_MOD_CTA = 80;
#define SPIN_LIMIT_S "4194304"
constexpr unsigned SPIN_LIMIT = 1u << 22;

constexpr int SM_RING = 0;
constexpr int SM_P = STAGES * TILE_BYTES;
constexpr int SM_PART = SM_P + WIN * 2;
constexpr int SM_OP = SM_PART + 8192;
constexpr int SM_Q = SM_OP + 2048;
constexpr int SM_RED = SM_Q + 256;
constexpr int SM_ML = SM_RED + 128;
constexpr int SM_PROG = SM_ML + 16;
constexpr int SM_SIDE = SM_PROG + 16;
constexpr int SM_BAR = SM_SIDE + 16;
constexpr int BAR_FULL = SM_BAR, BAR_EMPTY = SM_BAR + 8 * STAGES, BAR_XQ = SM_BAR + 16 * STAGES,
              BAR_XML = BAR_XQ + 8, BAR_XP = BAR_XQ + 16, BAR_FFN = BAR_XQ + 24;
constexpr int BAR_W2 = BAR_FFN + 8 * NQ;
constexpr int SMEM_BYTES = BAR_W2 + 8;
static_assert(SMEM_BYTES <= 232448, "shared memory");
__host__ __device__ constexpr uint32_t slot_addr(int n) { return SM_RING + (n % STAGES) * TILE_BYTES; }
__host__ __device__ constexpr uint32_t full_bar(int n) { return BAR_FULL + 8 * (n % STAGES); }
__host__ __device__ constexpr uint32_t empty_bar(int n) { return BAR_EMPTY + 8 * (n % STAGES); }
__host__ __device__ constexpr uint32_t tile_phase(int n) { return (n / STAGES) & 1; }
static_assert((N_FFN + 4) % STAGES + 2 <= STAGES && N_FFN % STAGES + 4 <= STAGES, "w1/w3 tiles and w2 tiles occupy consecutive slots");
static_assert(GATE_X >= WO_AT && N_GATE - STAGES < N_V2 && N_FFN + 5 - 2 * STAGES < N_WO && N_FFN + 5 - STAGES < N_WO2,
              "barrier parities the helper warp waits on are unambiguous after the rendezvous; the last wo tiles are not replaced");
__host__ __device__ constexpr int fill_tile(int j) { return j < K_FIRST ? N_K + j : j < K_FIRST + N_K ? j - K_FIRST : j; }

struct Ptrs {
    const __nv_bfloat16 *kwin, *x, *c;
    __nv_bfloat16* out;
};
struct Params {
    CUtensorMap m_wmod, m_wq, m_v, m_wo, m_w1, m_w3, m_w2, m_gb;
};

__device__ unsigned g_epoch;
__device__ __align__(128) uint2 g_mod[2][5 * D_ / 2];
__device__ __align__(256) unsigned char g_s[131072];
__device__ __forceinline__ unsigned long long s_line(int blk, int i) {
    return (((unsigned long long)g_s + 65535) & ~65535ull) + blk * 4096 + (i >> 1) * 1024 + (i & 1) * 256;
}
__device__ __forceinline__ int e1_blk(int r, int w) { return 2 * w + (r ^ (w & 1)); }
constexpr int S_OUT = 512, S_PROG = 128;
__device__ __align__(128) unsigned g_clear;

typedef unsigned long long u64;
#define PIN64(v) asm volatile("" : "+l"(v))

__device__ __forceinline__ void mbar_init(uint32_t bar, uint32_t cnt) {
    asm volatile("mbarrier.init.shared::cta.b64 [%0], %1;" :: "r"(bar), "r"(cnt) : "memory");
}
__device__ __forceinline__ void mbar_expect_tx(uint32_t bar, uint32_t bytes) {
    asm volatile("mbarrier.arrive.expect_tx.shared::cta.b64 _, [%0], %1;" :: "r"(bar), "r"(bytes) : "memory");
}
__device__ __forceinline__ void mbar_arrive(uint32_t bar) {
    asm volatile("mbarrier.arrive.shared::cta.b64 _, [%0];" :: "r"(bar) : "memory");
}
__device__ __forceinline__ void mbar_arrive_n(uint32_t bar, uint32_t n) {
    asm volatile("mbarrier.arrive.shared::cta.b64 _, [%0], %1;" :: "r"(bar), "r"(n) : "memory");
}
__device__ __forceinline__ void mbar_wait(uint32_t bar, uint32_t parity) {
    asm volatile("{\n.reg .pred p;\n.reg .u32 n;\nmov.u32 n, 0;\nW0:\n"
                 "mbarrier.try_wait.parity.shared::cta.b64 p, [%0], %1;\n@p bra W1;\n"
                 "add.u32 n, n, 1;\nsetp.lt.u32 p, n, " SPIN_LIMIT_S ";\n@p bra W0;\nW1:\n}"
                 :: "r"(bar), "r"(parity) : "memory");
}
__device__ __forceinline__ void mbar_wait_cluster(uint32_t bar, uint32_t parity) {
    asm volatile("{\n.reg .pred p;\n.reg .u32 n;\nmov.u32 n, 0;\nW0:\n"
                 "mbarrier.try_wait.parity.acquire.cluster.shared::cta.b64 p, [%0], %1;\n@p bra W1;\n"
                 "add.u32 n, n, 1;\nsetp.lt.u32 p, n, " SPIN_LIMIT_S ";\n@p bra W0;\nW1:\n}"
                 :: "r"(bar), "r"(parity) : "memory");
}
__device__ __forceinline__ void bulk_load(uint32_t dst, const void* src, uint32_t bytes, uint32_t bar, uint64_t pol) {
    asm volatile("cp.async.bulk.shared::cluster.global.mbarrier::complete_tx::bytes.L2::cache_hint [%0], [%1], %2, [%3], %4;"
                 :: "r"(dst), "l"(src), "r"(bytes), "r"(bar), "l"(pol) : "memory");
}
__device__ __forceinline__ void tma2d(uint32_t dst, const CUtensorMap* m, int c0, int c1, uint32_t bar) {
    asm volatile("cp.async.bulk.tensor.2d.shared::cluster.global.mbarrier::complete_tx::bytes [%0], [%1, {%3, %4}], [%2];"
                 :: "r"(dst), "l"(m), "r"(bar), "r"(c0), "r"(c1) : "memory");
}
__device__ __forceinline__ void tma2d_hint(uint32_t dst, const CUtensorMap* m, int c0, int c1, uint32_t bar, uint64_t pol) {
    asm volatile("cp.async.bulk.tensor.2d.shared::cluster.global.mbarrier::complete_tx::bytes.L2::cache_hint [%0], [%1, {%3, %4}], [%2], %5;"
                 :: "r"(dst), "l"(m), "r"(bar), "r"(c0), "r"(c1), "l"(pol) : "memory");
}
__device__ __forceinline__ void tma3d(uint32_t dst, const CUtensorMap* m, int c0, int c1, int c2, uint32_t bar) {
    asm volatile("cp.async.bulk.tensor.3d.shared::cluster.global.mbarrier::complete_tx::bytes [%0], [%1, {%3, %4, %5}], [%2];"
                 :: "r"(dst), "l"(m), "r"(bar), "r"(c0), "r"(c1), "r"(c2) : "memory");
}
__device__ __forceinline__ void tma4d(uint32_t dst, const CUtensorMap* m, int c0, int c3, uint32_t bar) {
    asm volatile("cp.async.bulk.tensor.4d.shared::cluster.global.mbarrier::complete_tx::bytes [%0], [%1, {%3, %5, %5, %4}], [%2];"
                 :: "r"(dst), "l"(m), "r"(bar), "r"(c0), "r"(c3), "r"(0) : "memory");
}
__device__ __forceinline__ void tma5d(uint32_t dst, const CUtensorMap* m, int c3, uint32_t bar) {
    asm volatile("cp.async.bulk.tensor.5d.shared::cluster.global.mbarrier::complete_tx::bytes [%0], [%1, {%4, %4, %4, %3, %4}], [%2];"
                 :: "r"(dst), "l"(m), "r"(bar), "r"(c3), "r"(0) : "memory");
}
__device__ __forceinline__ uint32_t mapa(uint32_t addr, uint32_t rank) {
    uint32_t r;
    asm("mapa.shared::cluster.u32 %0, %1, %2;" : "=r"(r) : "r"(addr), "r"(rank));
    return r;
}
__device__ __forceinline__ void st_async_b32(uint32_t addr, uint32_t v, uint32_t bar) {
    asm volatile("st.async.weak.shared::cluster.mbarrier::complete_tx::bytes.b32 [%0], %1, [%2];" :: "r"(addr), "r"(v), "r"(bar) : "memory");
}
__device__ __forceinline__ void st_async_v2(uint32_t addr, float a, float b, uint32_t bar) {
    asm volatile("st.async.weak.shared::cluster.mbarrier::complete_tx::bytes.v2.f32 [%0], {%1, %2}, [%3];" :: "r"(addr), "f"(a), "f"(b), "r"(bar) : "memory");
}
__device__ __forceinline__ void st_async_v4(uint32_t addr, uint32_t a, uint32_t b, uint32_t c, uint32_t d, uint32_t bar) {
    asm volatile("st.async.weak.shared::cluster.mbarrier::complete_tx::bytes.v4.b32 [%0], {%1, %2, %3, %4}, [%5];"
                 :: "r"(addr), "r"(a), "r"(b), "r"(c), "r"(d), "r"(bar) : "memory");
}
template <int ID> __device__ __forceinline__ void bar_sync() { asm volatile("bar.sync %0, 288;" :: "n"(ID) : "memory"); }
template <int ID> __device__ __forceinline__ void bar_arrive() { asm volatile("bar.arrive %0, 288;" :: "n"(ID) : "memory"); }
__device__ __forceinline__ void cbar() { asm volatile("bar.sync 1, 256;" ::: "memory"); }

__device__ __forceinline__ uint4 ldg128(const void* p) {
    uint4 v;
    asm volatile("ld.global.nc.v4.u32 {%0,%1,%2,%3}, [%4];" : "=r"(v.x), "=r"(v.y), "=r"(v.z), "=r"(v.w) : "l"(p));
    return v;
}
__device__ __forceinline__ uint32_t ldg16(const void* p) {
    uint16_t v;
    asm volatile("ld.global.nc.u16 %0, [%1];" : "=h"(v) : "l"(p));
    return v;
}
__device__ __forceinline__ uint4 ld_strong128(unsigned long long p) {
    uint4 v;
    asm volatile("ld.relaxed.gpu.global.v4.b32 {%0,%1,%2,%3}, [%4];" : "=r"(v.x), "=r"(v.y), "=r"(v.z), "=r"(v.w) : "l"(p) : "memory");
    return v;
}
__device__ __forceinline__ uint2 ld_strong64(unsigned long long p) {
    uint2 v;
    asm volatile("ld.relaxed.gpu.global.v2.b32 {%0,%1}, [%2];" : "=r"(v.x), "=r"(v.y) : "l"(p) : "memory");
    return v;
}
__device__ __forceinline__ uint32_t ldg32(const void* p) {
    uint32_t v;
    asm volatile("ld.global.nc.u32 %0, [%1];" : "=r"(v) : "l"(p));
    return v;
}
struct Pkt2 { u64 a, b; };
__device__ __forceinline__ uint32_t lo32(u64 v) { return (uint32_t)v; }
__device__ __forceinline__ uint32_t hi32(u64 v) { return (uint32_t)(v >> 32); }
__device__ __forceinline__ Pkt2 ld_pkt2(const void* p) {
    Pkt2 r;
    asm volatile("ld.relaxed.gpu.global.v2.b64 {%0,%1}, [%2];" : "=l"(r.a), "=l"(r.b) : "l"(p) : "memory");
    return r;
}
__device__ __forceinline__ bool pkt_ok(const Pkt2& r, uint32_t tag) { return hi32(r.a) == tag && hi32(r.b) == tag; }
__device__ __forceinline__ void st_pkt(u64 p, uint32_t data, uint32_t tag) {
    asm volatile("{\n.reg .b64 v;\nmov.b64 v, {%1, %2};\nst.relaxed.gpu.global.b64 [%0], v;\n}" :: "l"(p), "r"(data), "r"(tag) : "memory");
}
__device__ __forceinline__ uint4 lds128(uint32_t a) {
    uint4 v;
    asm volatile("ld.shared.v4.u32 {%0,%1,%2,%3}, [%4];" : "=r"(v.x), "=r"(v.y), "=r"(v.z), "=r"(v.w) : "r"(a) : "memory");
    return v;
}
__device__ __forceinline__ float4 lds128f(uint32_t a) {
    float4 v;
    asm volatile("ld.shared.v4.f32 {%0,%1,%2,%3}, [%4];" : "=f"(v.x), "=f"(v.y), "=f"(v.z), "=f"(v.w) : "r"(a) : "memory");
    return v;
}
__device__ __forceinline__ uint2 lds64(uint32_t a) {
    uint2 v;
    asm volatile("ld.shared.v2.u32 {%0,%1}, [%2];" : "=r"(v.x), "=r"(v.y) : "r"(a) : "memory");
    return v;
}
__device__ __forceinline__ float2 lds64f(uint32_t a) {
    float2 v;
    asm volatile("ld.shared.v2.f32 {%0,%1}, [%2];" : "=f"(v.x), "=f"(v.y) : "r"(a) : "memory");
    return v;
}
__device__ __forceinline__ float lds32f(uint32_t a) {
    float v;
    asm volatile("ld.shared.f32 %0, [%1];" : "=f"(v) : "r"(a) : "memory");
    return v;
}
__device__ __forceinline__ void sts64f(uint32_t a, float x, float y) {
    asm volatile("st.shared.v2.f32 [%0], {%1,%2};" :: "r"(a), "f"(x), "f"(y) : "memory");
}
__device__ __forceinline__ void sts128f(uint32_t a, float x, float y, float z, float w) {
    asm volatile("st.shared.v4.f32 [%0], {%1,%2,%3,%4};" :: "r"(a), "f"(x), "f"(y), "f"(z), "f"(w) : "memory");
}
__device__ __forceinline__ void sts32f(uint32_t a, float x) {
    asm volatile("st.shared.f32 [%0], %1;" :: "r"(a), "f"(x) : "memory");
}
__device__ __forceinline__ void sts128(uint32_t a, uint32_t x, uint32_t y, uint32_t z, uint32_t w) {
    asm volatile("st.shared.v4.u32 [%0], {%1,%2,%3,%4};" :: "r"(a), "r"(x), "r"(y), "r"(z), "r"(w) : "memory");
}
__device__ __forceinline__ void settle(uint32_t tag, uint32_t a, uint32_t x, uint32_t y, uint32_t z, uint32_t w) {
    asm volatile("{\n.reg .pred p;\nsetp.eq.u32 p, %0, 0;\n@p st.shared.v4.u32 [%1], {%2,%3,%4,%5};\n}" :: "r"(tag), "r"(a), "r"(x), "r"(y), "r"(z), "r"(w) : "memory");
}
__device__ __forceinline__ void settle(uint32_t tag, uint32_t a, const float4& v) {
    settle(tag, a, __float_as_uint(v.x), __float_as_uint(v.y), __float_as_uint(v.z), __float_as_uint(v.w));
}
__device__ __forceinline__ void sts16(uint32_t a, uint32_t x) {
    asm volatile("st.shared.u16 [%0], %1;" :: "r"(a), "h"((uint16_t)x) : "memory");
}
__device__ __forceinline__ void ldsm4t(uint32_t a, uint32_t (&r)[4]) {
    asm volatile("ldmatrix.sync.aligned.m8n8.x4.trans.shared.b16 {%0,%1,%2,%3}, [%4];"
                 : "=r"(r[0]), "=r"(r[1]), "=r"(r[2]), "=r"(r[3]) : "r"(a) : "memory");
}
__device__ __forceinline__ void mma(float (&c)[4], uint32_t a0, uint32_t a1, uint32_t a2, uint32_t a3, uint32_t b0, uint32_t b1) {
    asm volatile("mma.sync.aligned.m16n8k16.row.col.f32.bf16.bf16.f32 {%0,%1,%2,%3}, {%4,%5,%6,%7}, {%8,%9}, {%0,%1,%2,%3};"
                 : "+f"(c[0]), "+f"(c[1]), "+f"(c[2]), "+f"(c[3]) : "r"(a0), "r"(a1), "r"(a2), "r"(a3), "r"(b0), "r"(b1));
}
__device__ __forceinline__ void mma4(float (&c)[4], const uint32_t (&a)[4], uint32_t b0, uint32_t b1) { mma(c, a[0], a[1], a[2], a[3], b0, b1); }
__device__ __forceinline__ float sel(uint32_t c, float a, float b) {
    float r;
    asm("{\n.reg .pred p;\nsetp.ne.u32 p, %3, 0;\nselp.f32 %0, %1, %2, p;\n}" : "=f"(r) : "f"(a), "f"(b), "r"(c));
    return r;
}
__device__ __forceinline__ float bf_lo(uint32_t v) { return __uint_as_float(v << 16); }
__device__ __forceinline__ float bf_hi(uint32_t v) { return __uint_as_float(v & 0xffff0000u); }
__device__ __forceinline__ uint32_t pack2(float lo, float hi) {
    uint32_t r;
    asm("cvt.rn.bf16x2.f32 %0, %1, %2;" : "=r"(r) : "f"(hi), "f"(lo));
    return r;
}
__device__ __forceinline__ float rbf(float x) { return __uint_as_float(pack2(0.f, x)); }
__device__ __forceinline__ uint32_t hadd2(uint32_t a, uint32_t b) { uint32_t r; asm("add.rn.bf16x2 %0, %1, %2;" : "=r"(r) : "r"(a), "r"(b)); return r; }
__device__ __forceinline__ uint32_t hsub2(uint32_t a, uint32_t b) { uint32_t r; asm("sub.rn.bf16x2 %0, %1, %2;" : "=r"(r) : "r"(a), "r"(b)); return r; }
__device__ __forceinline__ uint32_t hmul2(uint32_t a, uint32_t b) { uint32_t r; asm("mul.rn.bf16x2 %0, %1, %2;" : "=r"(r) : "r"(a), "r"(b)); return r; }
__device__ __forceinline__ uint32_t hfma2(uint32_t a, uint32_t b, uint32_t c) { uint32_t r; asm("fma.rn.bf16x2 %0, %1, %2, %3;" : "=r"(r) : "r"(a), "r"(b), "r"(c)); return r; }
__device__ __forceinline__ uint32_t selu(uint32_t c, uint32_t a, uint32_t b) { return __float_as_uint(sel(c, __uint_as_float(a), __uint_as_float(b))); }
constexpr uint32_t ONE2 = 0x3f803f80u;
__device__ __forceinline__ float silu_f(float x) {
    float e, r;
    asm("ex2.approx.ftz.f32 %0, %1;" : "=f"(e) : "f"(x * -1.4426950408889634f));
    asm("rcp.approx.ftz.f32 %0, %1;" : "=f"(r) : "f"(1.0f + e));
    return x * r;
}
__device__ __forceinline__ float rcp_sd(float m2) {
    float s, r;
    asm("sqrt.approx.ftz.f32 %0, %1;" : "=f"(s) : "f"(rbf(rbf(m2 * (1.0f / D_)) + 1e-5f)));
    asm("rcp.approx.ftz.f32 %0, %1;" : "=f"(r) : "f"(rbf(s)));
    return r;
}
__device__ __forceinline__ uint32_t ln_mod2(uint32_t x, uint32_t mean2, float rsd, uint32_t c1, uint32_t sh) {
    const uint32_t d = hsub2(x, mean2);
    return hadd2(hmul2(pack2(bf_lo(d) * rsd, bf_hi(d) * rsd), c1), sh);
}
__device__ __forceinline__ int pair_pos(int j) { return 2 * (j & 3) + (j >> 2); }

__global__ void __cluster_dims__(2, 1, 1) __launch_bounds__(THREADS, 1)
fused_decode_kernel(const __grid_constant__ Ptrs q_, const __grid_constant__ Params p) {
    extern __shared__ __align__(1024) unsigned char smem[];
    unsigned t_top;
    asm volatile("mov.u32 %0, %%globaltimer_lo;" : "=r"(t_top));
    const uint32_t sb = (uint32_t)__cvta_generic_to_shared(smem);
    const int tid = threadIdx.x, cta = blockIdx.x;
    const int rank = cta & 1;
    const int cl = cta >> 1, per = cl < 4 ? 1 : cl < 36 ? 8 : 7, d0 = cl < 4 ? cl : cl < 36 ? cl - 4 : cl - 36;
    const int up = d0 >= 2 * per, r0 = d0 - 2 * per * up, b = r0 >= per, h = (cl < 4 ? 0 : cl < 36 ? 2 : 18) + per * up + r0 - per * b, bh = 32 * b + h;

    uint32_t z0;
    asm("and.b32 %0, %1, 1024;" : "=r"(z0) : "r"(tid));
    const char* kw = *(const char* const*)((const char*)&q_.kwin + z0);
    const char* kp;
    auto set_kp = [&]() {
        asm volatile("{\n.reg .u32 lo, hi;\nmov.b64 {lo, hi}, %1;\nadd.cc.u32 lo, lo, %2;\naddc.u32 hi, hi, 0;\nmov.b64 %0, {lo, hi};\n}"
                     : "=l"(kp) : "l"(kw), "r"(bh * (SK * DH * 2) + rank * TILE_BYTES));
    };
    uint64_t pol;
    asm("createpolicy.fractional.L2::evict_first.b64 %0, 1.0;" : "=l"(pol));
    auto first_fill = [&](int j) {
        const int n = fill_tile(j);
        if (n >= N_K) {
            mbar_expect_tx(sb + full_bar(n), TILE_BYTES);
            bulk_load(sb + slot_addr(n), kp + (n - N_K) * 2 * TILE_BYTES, TILE_BYTES, sb + full_bar(n), pol);
        } else if (n >= N_WQ) {
            mbar_expect_tx(sb + full_bar(n), TILE_BYTES);
            tma2d(sb + slot_addr(n), &p.m_wq, h * DH + 64 * rank, 128 * (n - N_WQ), sb + full_bar(n));
        } else if (cta < N_MOD_CTA) {
            mbar_expect_tx(sb + full_bar(n), TILE_BYTES);
            tma2d(sb + slot_addr(n), &p.m_wmod, 32 * cta, 256 * n, sb + full_bar(n));
        } else {
            mbar_arrive(sb + full_bar(n));
        }
    };
    static_assert(K_FIRST >= 1, "head block starts with K tile 0");
    if (tid == HEAD_TID) {
        mbar_init(sb + full_bar(N_K), 1);
        set_kp();
        bulk_load(sb + slot_addr(N_K), kp, TILE_BYTES, sb + full_bar(N_K), pol);
        mbar_expect_tx(sb + full_bar(N_K), TILE_BYTES);
#pragma unroll
        for (int j = 1; j < FIRST_N; j++) mbar_init(sb + full_bar(fill_tile(j)), 1);
#pragma unroll
        for (int j = 1; j < FIRST_N; j++) first_fill(j);
        asm volatile("fence.mbarrier_init.release.cluster;" ::: "memory");
    }
    __syncwarp();

    const int role = cta / 3;
    const bool is_gu = cta == 3 * role, is_gb = cta == 3 * role + 1 && role < 32;
    if (tid >= 288) {
        const unsigned t_start = t_top;
        asm volatile("barrier.cluster.arrive.relaxed.aligned;" ::: "memory");
        unsigned tag;
        asm volatile("ld.relaxed.gpu.global.u32 %0, [%1];" : "=r"(tag) : "l"(&g_epoch) : "memory");
        tag += 1;
        if (cta == NCTA - 1) {
            for (int i = tid - 288; i < 64 * 8; i += 32) {
                uint4* q = reinterpret_cast<uint4*>(s_line(i >> 6, (i >> 3) & 7)) + (i & 7);
                const uint32_t v = (i & 48) == 48 ? ~0u : 0u;
                q[0] = make_uint4(v, v, v, v);
                q[S_OUT / 16] = make_uint4(0u, 0u, 0u, 0u);
            }
            for (int i = tid - 288; i < 64 * 8; i += 32) {
                uint4* q = reinterpret_cast<uint4*>(s_line(8 + (i >> 6), (i >> 3) & 7)) + (i & 7);
                q[0] = make_uint4(0u, 0u, 0u, 0u);
            }
            if (tid == 288) *reinterpret_cast<uint4*>(s_line(0, 0) + S_PROG) = make_uint4(0u, 0u, 0u, 0u);
            __syncwarp();
            asm volatile("fence.acq_rel.gpu;" ::: "memory");
            if (tid == 288) asm volatile("st.relaxed.gpu.global.u32 [%0], %1;" :: "l"(&g_clear), "r"(tag) : "memory");
        }
        asm volatile("barrier.cluster.wait.acquire.aligned;" ::: "memory");
        mbar_wait_cluster(sb + BAR_XQ, 0);
        for (uint32_t n = 0; n < SPIN_LIMIT; n++) {
            unsigned c;
            asm volatile("ld.relaxed.gpu.global.u32 %0, [%1];" : "=r"(c) : "l"(&g_clear) : "memory");
            if (c == tag) break;
        }
        asm volatile("fence.acq_rel.gpu;" ::: "memory");
        asm volatile("st.volatile.shared.u32 [%0], %1;" :: "r"(sb + SM_SIDE), "r"(0) : "memory");
        asm volatile("bar.sync 2, 288;" ::: "memory");
        if (tid == 288) {
            asm volatile("prefetch.tensormap [%0];" :: "l"(is_gu ? &p.m_w1 : &p.m_gb) : "memory");
            asm volatile("prefetch.tensormap [%0];" :: "l"(&p.m_w3) : "memory");
            asm volatile("prefetch.tensormap [%0];" :: "l"(&p.m_w2) : "memory");
            mbar_wait(sb + full_bar(N_GATE), tile_phase(N_GATE));
            unsigned now, c = 0;
            asm volatile("mov.u32 %0, %%globaltimer_lo;" : "=r"(now));
            const unsigned mine = (1u << 24) + min(now - t_start, 100000u);
            const u64 prog = s_line(0, 0) + S_PROG;
            asm volatile("red.relaxed.gpu.global.add.u32 [%0], %1;" :: "l"(prog), "r"(mine) : "memory");
            if (is_gu || is_gb) {
#pragma unroll
                for (int i = 0; i < 6; i++) mbar_wait(sb + empty_bar(N_FFN + i), tile_phase(N_FFN + i) ^ 1);
#pragma unroll
                for (int i = 0; i < NQ; i++) mbar_expect_tx(sb + BAR_FFN + 8 * i, is_gu ? 65536 / NQ : 16384);
                mbar_expect_tx(sb + BAR_W2, 32768);
                const int issue = (4 * N_GATE - 11 - 2 * WO_EARLY) * (PACE / 4) - LEAD_NS;
                unsigned due = 0, next = now, best[2] = {~0u, ~0u}, np = is_gu ? 0 : PROBES;
                const u64 pa = s_line(e1_blk(0, role & 7), role >> 3);
                asm volatile("st.volatile.shared.u32 [%0], %1;" :: "r"(sb + SM_PROG), "r"(mine) : "memory");
                for (uint32_t n = 0; n < 4096; n++) {
                    unsigned v;
                    asm volatile("ld.volatile.shared.u32 %0, [%1];" : "=r"(v) : "r"(sb + SM_PROG) : "memory");
                    if (v > c) {
                        c = v;
                        const int arr = (int)__fdividef((float)(c & 0xffffffu), (float)(c >> 24));
                        due = arr - ((arr - issue) * ALPHA16 >> 4) + (is_gu ? GU_NS : W2_NS - GB_LEAD);
                    }
                    asm volatile("mov.u32 %0, %%globaltimer_lo;" : "=r"(now));
                    if (now - t_start + PROBE_NS >= due) np = PROBES;
                    if ((c >= ((unsigned)NCTA << 24) && np == PROBES) || now - t_start >= due) break;
                    if ((int)(now - next) >= 0 && c < ((unsigned)NCTA << 24)) {
                        asm volatile("cp.async.cg.shared.global [%0], [%1], 16;" :: "r"(sb + SM_PROG), "l"(prog) : "memory");
                        next = now + POLL_NS;
                    }
                    if (np < PROBES) {
                        unsigned c0, c1 = 0;
                        asm volatile("mov.u32 %0, %%clock;" : "=r"(c0));
                        asm volatile("ld.relaxed.gpu.global.u32 %0, [%1];" : "=r"(v) : "l"(pa ^ ((np & 1) << 12)) : "memory");
                        asm volatile("{\n.reg .pred p;\nsetp.ne.u32 p, %1, 0xffffffff;\n@p mov.u32 %0, %%clock;\n}" : "+r"(c1) : "r"(v));
                        if (np & 1) best[1] = min(best[1], c1 - c0); else best[0] = min(best[0], c1 - c0);
                        np++;
                    }
                }
                asm volatile("st.volatile.shared.u32 [%0], %1;" :: "r"(sb + SM_SIDE), "r"(best[0] <= best[1] ? 0 : 4096) : "memory");
                for (uint32_t n = 0; n < 1024 && now - t_start < due; n++) asm volatile("mov.u32 %0, %%globaltimer_lo;" : "=r"(now));
                if (is_gu) {
#pragma unroll 1
                    for (int i = 0; i < 2 * NQ; i++) {
                        const int q = i >> 1, r0 = q * (512 / NQ);
                        tma4d(sb + slot_addr(N_FFN) + (r0 >> 8) * 2 * TILE_BYTES + (i & 1) * TILE_BYTES + (r0 & 255) * 64, (i & 1) ? &p.m_w3 : &p.m_w1, 32 * role, r0 / 16, sb + BAR_FFN + 8 * q);
                    }
                    for (uint32_t n = 0; n < 1024 && now - t_start < due + (W2_NS - GU_NS); n++) asm volatile("mov.u32 %0, %%globaltimer_lo;" : "=r"(now));
                    tma5d(sb + slot_addr(N_FFN + 4), &p.m_w2, 2 * role, sb + BAR_W2);
                } else {
                    tma2d(sb + slot_addr(N_FFN), &p.m_gb, 5 * D_ + 16 * role, 0, sb + BAR_FFN);
                    tma2d(sb + slot_addr(N_FFN) + 8192, &p.m_gb, 5 * D_ + 16 * role, 256, sb + BAR_FFN);
                }
                asm volatile("cp.async.wait_all;" ::: "memory");
            }
        }
        __syncwarp();
        if (is_gu) {
            const int lane = tid & 31;
            auto sum8 = [&](uint32_t a, int stride) {
                float4 u[8];
#pragma unroll
                for (int i = 0; i < 8; i++) u[i] = lds128f(a + i * stride);
                return make_float4(((u[0].x + u[1].x) + (u[2].x + u[3].x)) + ((u[4].x + u[5].x) + (u[6].x + u[7].x)),
                                   ((u[0].y + u[1].y) + (u[2].y + u[3].y)) + ((u[4].y + u[5].y) + (u[6].y + u[7].y)),
                                   ((u[0].z + u[1].z) + (u[2].z + u[3].z)) + ((u[4].z + u[5].z) + (u[6].z + u[7].z)),
                                   ((u[0].w + u[1].w) + (u[2].w + u[3].w)) + ((u[4].w + u[5].w) + (u[6].w + u[7].w)));
            };
            uint32_t h_st = sb + SM_Q + (((lane & 1) * 4 + ((lane >> 2) & 3)) * 4 + (lane & 2) + (lane >> 4)) * 4;
            bar_sync<3>();
            const float4 C = sum8(sb + SM_P + lane * 16, 1024), S = sum8(sb + SM_P + 512 + lane * 16, 1024);
            const uint32_t st_ld = sb + SM_RED + (lane & 1) * 64;
            settle(tag, sb + SM_OP, C); settle(tag, sb + SM_OP, S); settle(tag, sb + SM_OP, h_st, st_ld, 0, 0);
            bar_sync<4>();
            const float4 r0 = lds128f(st_ld), r1 = lds128f(st_ld + 16), r2 = lds128f(st_ld + 32), r3 = lds128f(st_ld + 48);
            const float4 Y = sum8(sb + SM_PART + lane * 16, 512);
            const float e1 = r0.z - r0.x, e2 = r1.x - r0.x, e3 = r1.z - r0.x, e4 = r2.x - r0.x, e5 = r2.z - r0.x, e6 = r3.x - r0.x, e7 = r3.z - r0.x;
            const float se = ((e1 + e2) + (e3 + e4)) + ((e5 + e6) + e7);
            const float ee = (fmaf(e1, e1, e2 * e2) + fmaf(e3, e3, e4 * e4)) + fmaf(e5, e5, fmaf(e6, e6, e7 * e7));
            const float sq = ((r0.y + r0.w) + (r1.y + r1.w)) + ((r2.y + r2.w) + (r3.y + r3.w));
            const float rsd = rcp_sd(fmaf(se * (-1.0f / D_), se, fmaf(ee, 1.0f / 64, sq))), mu = -rbf(fmaf(r0.x, 8.0f, se) * (1.0f / D_));
            const uint32_t gr = pack2(fmaf(rsd, fmaf(mu, C.x, Y.x), S.x), fmaf(rsd, fmaf(mu, C.z, Y.z), S.z));
            const uint32_t ur = pack2(fmaf(rsd, fmaf(mu, C.y, Y.y), S.y), fmaf(rsd, fmaf(mu, C.w, Y.w), S.w));
            const uint32_t hv = hmul2(pack2(silu_f(bf_lo(gr)), silu_f(bf_hi(gr))), ur);
            sts32f(h_st, __uint_as_float(hv));
            bar_arrive<5>();
            if (cta == 0 && lane == 0) g_epoch = tag;
        }
        return;
    }
    if (tid >= 256) {
        set_kp();
        const unsigned t_start = t_top;
        auto pace = [&](int q4) {
            const int due = q4 * (PACE / 4) - LEAD_NS;
            unsigned now, n = 0;
            do { asm volatile("mov.u32 %0, %%globaltimer_lo;" : "=r"(now)); } while ((int)(now - t_start) < due && ++n < 256);
        };
        if (tid == 256) {
#pragma unroll
            for (int j = FIRST_N; j < STAGES; j++) mbar_init(sb + full_bar(fill_tile(j)), 1);
#pragma unroll
            for (int s = 0; s < STAGES; s++) mbar_init(sb + BAR_EMPTY + 8 * s, 8);
            mbar_init(sb + BAR_XQ, 1); mbar_init(sb + BAR_XML, 1); mbar_init(sb + BAR_XP, 1);
#pragma unroll
            for (int i = 0; i < NQ + 1; i++) mbar_init(sb + BAR_FFN + 8 * i, 1);
            mbar_expect_tx(sb + BAR_XQ, 256); mbar_expect_tx(sb + BAR_XML, 8); mbar_expect_tx(sb + BAR_XP, WIN);
            asm volatile("fence.mbarrier_init.release.cluster;" ::: "memory");
            asm volatile("fence.proxy.async.shared::cta;" ::: "memory");
        }
        __syncwarp();
        asm volatile("barrier.cluster.arrive.relaxed.aligned;" ::: "memory");
        if (tid == 256) {
#pragma unroll
            for (int j = FIRST_N; j < STAGES; j++) {
                pace(j <= K_FIRST ? 4 * j : j <= K_FIRST + 2 ? 4 * K_FIRST + 5 * (j - K_FIRST) / 2 :
                     j <= K_FIRST + 6 ? 4 * K_FIRST + 5 + 2 * (j - K_FIRST - 2) : 4 * j - 11);
                first_fill(j);
            }
        }
        __syncwarp();
        asm volatile("barrier.cluster.wait.acquire.aligned;" ::: "memory");
        if (tid == 256) {
            asm volatile("prefetch.tensormap [%0];" :: "l"(&p.m_v) : "memory");
            asm volatile("prefetch.tensormap [%0];" :: "l"(&p.m_wo) : "memory");
            int s = 0, ph = 0;
#pragma unroll 1
            for (int n = STAGES; n < N_FFN; n++) {
                const uint32_t dst = sb + SM_RING + s * TILE_BYTES, bar = sb + BAR_FULL + 8 * s;
                mbar_wait(sb + BAR_EMPTY + 8 * s, ph);
                mbar_expect_tx(bar, TILE_BYTES);
                pace(n < N_WO ? 4 * n - 11 : n < N_V2 ? 2 * (N_WO + n) - 11 : n < N_WO2 ? 4 * n - 11 - 2 * WO_EARLY : 2 * (N_WO2 + n - WO_EARLY) - 11);
                if (n < N_V) bulk_load(dst, kp + (n - N_K) * 2 * TILE_BYTES, TILE_BYTES, bar, pol);
                else if (n >= N_WO2 || (n >= N_WO && n < N_V2)) tma3d(dst, &p.m_wo, 0, h * DH + 64 * rank + 16 * (n - (n < N_V2 ? N_WO : N_V + NT)), 0, bar);
                else tma2d_hint(dst, &p.m_v, 64 * rank, bh * SK + (SK - WIN) + 128 * (n - (n < N_WO ? N_V : N_V + WO_EARLY)), bar, pol);
                if (++s == STAGES) { s = 0; ph ^= 1; }
            }
        }
        return;
    }

    const unsigned t_c = t_top;
    const int lane = tid & 31, w = tid >> 5, g = lane >> 2, t = lane & 3;
    const int hgrp = 4 * w + (g & 3);
    const int vb = g >> 2;
    const uint32_t cv0 = ldg32(q_.c + vb * D_ + 16 * hgrp + 2 * t), cv1 = ldg32(q_.c + vb * D_ + 16 * hgrp + 8 + 2 * t);
    unsigned tag;
    asm volatile("ld.relaxed.gpu.global.u32 %0, [%1];" : "=r"(tag) : "l"(&g_epoch) : "memory");
    const uint4 xa = ldg128(q_.x + b * D_ + 16 * lane), xb = ldg128(q_.x + b * D_ + 16 * lane + 8);
    const uint32_t xh0 = ldg32(q_.x + b * D_ + 16 * hgrp + 2 * t), xh1 = ldg32(q_.x + b * D_ + 16 * hgrp + 8 + 2 * t);
    asm volatile("barrier.cluster.arrive.relaxed.aligned;" ::: "memory");
#pragma unroll 1
    for (uint32_t n = t_c; n < 2; n++) asm volatile("nanosleep.u32 1;" ::: "memory");
    const int grp = w >> 2, sub = w & 3;
    const int lrow = (lane & 7) + 8 * (lane >> 4);
    const int lch = (lane >> 3) & 1;
    const int ob = lane >> 4;
    const uint32_t t1 = t & 1, t2 = t & 2;
    const int gsrc = 16 * (g & 1) + t;
    const uint32_t sw128 = lrow * 128 + ((lch ^ (lrow & 7)) << 4);
    uint32_t A[16][4];

    const uint32_t sc0 = pack2(silu_f(bf_lo(cv0)), silu_f(bf_hi(cv0))), sc1 = pack2(silu_f(bf_lo(cv1)), silu_f(bf_hi(cv1)));
    tag += 1;
    asm volatile("barrier.cluster.wait.acquire.aligned;" ::: "memory");
    mbar_wait(sb + BAR_FULL + 8 * (N_WMOD + grp), 0);
    if (cta < N_MOD_CTA) {
        const uint32_t tb = sb + SM_RING + (N_WMOD + grp) * TILE_BYTES + (64 * sub + lrow) * 64;
#pragma unroll
        for (int i = 0; i < 8; i++)
            ldsm4t(tb + (i >> 1) * 1024 + (((2 * (i & 1) + lch) ^ ((lrow >> 1) & 3)) << 4), A[i]);
        float acc[2][4] = {{0.f, 0.f, 0.f, 0.f}, {0.f, 0.f, 0.f, 0.f}};
#pragma unroll
        for (int s = 0; s < 4; s++) {
            const uint32_t b0 = __shfl_sync(~0u, sc0, 4 * s + gsrc), b1 = __shfl_sync(~0u, sc1, 4 * s + gsrc);
            mma4(acc[0], A[2 * s], b0, b1);
            mma4(acc[1], A[2 * s + 1], b0, b1);
        }
        sts32f(sb + SM_P + (w * 64 + 8 * t + g) * 4, sel(t2, sel(t1, acc[1][2], acc[1][0]), sel(t1, acc[0][2], acc[0][0])));
        sts32f(sb + SM_P + (w * 64 + 32 + 8 * t + g) * 4, sel(t2, sel(t1, acc[1][3], acc[1][1]), sel(t1, acc[0][3], acc[0][1])));
        cbar();
        if (w == 0) {
            const bool adj = cta < 32;
            const uint32_t a0 = sb + SM_P + (adj ? 2 * lane : ob * 32 + (lane & 1) * 16 + ((lane >> 1) & 7)) * 4, a1 = a0 + (adj ? 4 : 32);
            float2 sum = make_float2(0.f, 0.f);
#pragma unroll
            for (int i = 0; i < 8; i++) { sum.x += lds32f(a0 + i * 256); sum.y += lds32f(a1 + i * 256); }
            st_pkt((u64)&g_mod[ob][16 * cta + (adj ? (lane & 8) + pair_pos(lane & 7) : lane & 15)], pack2(sum.x, sum.y), tag);
        }
    }
    __syncwarp();
    if (lane == 0) mbar_arrive_n(sb + BAR_EMPTY + 8 * (N_WMOD + grp), 2);

    {
        const uint2* mp = &g_mod[b][vb * 256 + 8 * hgrp + 2 * t];
        const uint32_t ms = sb + SM_PART + tid * 16;
        auto fetch_mod = [&](uint32_t k) {
            asm volatile("cp.async.cg.shared.global [%0], [%1], 16;\ncp.async.commit_group;" :: "r"(ms + k), "l"(mp) : "memory");
        };
        fetch_mod(0);
        float xs[16] = {bf_lo(xa.x), bf_hi(xa.x), bf_lo(xa.y), bf_hi(xa.y), bf_lo(xa.z), bf_hi(xa.z), bf_lo(xa.w), bf_hi(xa.w),
                        bf_lo(xb.x), bf_hi(xb.x), bf_lo(xb.y), bf_hi(xb.y), bf_lo(xb.z), bf_hi(xb.z), bf_lo(xb.w), bf_hi(xb.w)};
        float s = 0.f;
#pragma unroll
        for (int i = 0; i < 16; i++) s += xs[i];
#pragma unroll
        for (int m = 1; m < 32; m <<= 1) s += __shfl_xor_sync(~0u, s, m);
        const float mean = s * (1.0f / D_);
        float q = 0.f;
#pragma unroll
        for (int i = 0; i < 16; i++) q += (xs[i] - mean) * (xs[i] - mean);
#pragma unroll
        for (int m = 1; m < 32; m <<= 1) q += __shfl_xor_sync(~0u, q, m);
        const uint32_t mean2 = pack2(mean, mean);
        const float rsd = rcp_sd(q);

        mbar_wait(sb + BAR_FULL + 8 * (N_WQ + (w >> 1)), 0);
        const uint32_t tb = sb + SM_RING + (N_WQ + (w >> 1)) * TILE_BYTES + (w & 1) * 8192;
#pragma unroll
        for (int i = 0; i < 16; i++) ldsm4t(tb + (i >> 2) * 2048 + (sw128 ^ ((i & 3) * 32)), A[i]);
        __syncwarp();
        if (lane == 0) mbar_arrive_n(sb + BAR_EMPTY + 8 * (N_WQ + (w >> 1)), 4);

        Pkt2 m;
        for (uint32_t n = 0, k = 0; n < SPIN_LIMIT; n++) {
            fetch_mod(k ^ 4096);
            asm volatile("cp.async.wait_group 1;" ::: "memory");
            const uint4 u = lds128(ms + k);
            m.a = u.x | (u64)u.y << 32; m.b = u.z | (u64)u.w << 32;
            if (__all_sync(~0u, pkt_ok(m, tag))) break;
            k ^= 4096;
        }
        const uint32_t ca0 = __shfl_xor_sync(~0u, lo32(m.a), 16), ca1 = __shfl_xor_sync(~0u, lo32(m.b), 16);
        const uint32_t v0 = ln_mod2(xh0, mean2, rsd, hadd2(ONE2, ca0), lo32(m.a));
        const uint32_t v1 = ln_mod2(xh1, mean2, rsd, hadd2(ONE2, ca1), lo32(m.b));
        float acc[4][4];
#pragma unroll
        for (int i = 0; i < 4; i++) { acc[i][0] = acc[i][1] = acc[i][2] = acc[i][3] = 0.f; }
#pragma unroll
        for (int s4 = 0; s4 < 4; s4++) {
            const uint32_t b0 = __shfl_sync(~0u, v0, 4 * s4 + t), b1 = __shfl_sync(~0u, v1, 4 * s4 + t);
#pragma unroll
            for (int i = 0; i < 4; i++) mma4(acc[i], A[4 * s4 + i], b0, b1);
        }
        sts32f(sb + SM_OP + (w * 64 + 16 * t + g) * 4, sel(t2, sel(t1, acc[3][0], acc[2][0]), sel(t1, acc[1][0], acc[0][0])));
        sts32f(sb + SM_OP + (w * 64 + 16 * t + 8 + g) * 4, sel(t2, sel(t1, acc[3][2], acc[2][2]), sel(t1, acc[1][2], acc[0][2])));
        cbar();
        if (w == 0) {
            float2 sum = make_float2(0.f, 0.f);
#pragma unroll
            for (int i = 0; i < 8; i++) { const float2 u = lds64f(sb + SM_OP + (i * 64 + 2 * lane) * 4); sum.x += u.x; sum.y += u.y; }
            const uint32_t v = pack2(sum.x, sum.y), a = sb + SM_Q + rank * 128 + lane * 4;
            st_async_b32(mapa(a, rank ^ 1), v, mapa(sb + BAR_XQ, rank ^ 1));
            st_async_b32(mapa(a, rank), v, mapa(sb + BAR_XQ, rank));
        }
        mbar_wait_cluster(sb + BAR_XQ, 0);
    }

    Pkt2 mga, msb, mcb;
    uint32_t tx0, tx1;
    const uint2* tmp = &g_mod[ob][32 * w + 2 * (lane & 15)];
    {
        uint4 Q[4];
        uint32_t koff[4];
#pragma unroll
        for (int i = 0; i < 4; i++) {
            const int ch = t + 4 * (i ^ (g & 1));
            Q[i] = lds128(sb + SM_Q + ch * 16);
            koff[i] = (sub * 16 + g) * 256 + ch * 16;
        }
        float mx = -INFINITY;
        int stage = N_K + grp, phase = 0;
#pragma unroll 1
        for (int it = 0; it < NT / 2; it++) {
            const uint32_t tb = sb + SM_RING + stage * TILE_BYTES;
            mbar_wait(sb + BAR_FULL + 8 * stage, phase);
            uint4 Ka[4], Kb[4];
#pragma unroll
            for (int i = 0; i < 4; i++) { Ka[i] = lds128(tb + koff[i]); Kb[i] = lds128(tb + koff[i] + 2048); }
            float c0[4] = {0.f, 0.f, 0.f, 0.f}, c1[4] = {0.f, 0.f, 0.f, 0.f};
#pragma unroll
            for (int i = 0; i < 4; i++) {
                mma(c0, Ka[i].x, Kb[i].x, Ka[i].y, Kb[i].y, Q[i].x, Q[i].y);
                mma(c1, Ka[i].z, Kb[i].z, Ka[i].w, Kb[i].w, Q[i].z, Q[i].w);
            }
            __syncwarp();
            if (lane == 0) mbar_arrive_n(sb + BAR_EMPTY + 8 * stage, 2);
            const float lo = (g & 1) ? c0[1] + c1[1] : c0[0] + c1[0];
            const float hi = (g & 1) ? c0[3] + c1[3] : c0[2] + c1[2];
            const float sc = rbf(rbf(t1 ? hi : lo) * 0.08838834764831845f);
            mx = fmaxf(mx, sc);
            if (t < 2) sts16(sb + SM_P + ((2 * it + grp) * 128 + rank * 64 + sub * 16 + 4 * (g >> 1) + 2 * t + (g & 1)) * 2, __float_as_uint(sc) >> 16);
            stage += 2;
            if (stage >= STAGES) { stage -= STAGES; phase ^= 1; }
        }

        mga = ld_pkt2(tmp + 2 * 256); msb = ld_pkt2(tmp + 3 * 256); mcb = ld_pkt2(tmp + 4 * 256);
        const __nv_bfloat16* xp = q_.x + ob * D_ + 64 * w + 4 * (lane & 8) + (lane & 7);
        tx0 = ldg16(xp) | ldg16(xp + 8) << 16;
        tx1 = ldg16(xp + 16) | ldg16(xp + 24) << 16;

        asm volatile("cp.async.wait_all;" ::: "memory");

#pragma unroll
        for (int m = 1; m < 32; m <<= 1) mx = fmaxf(mx, __shfl_xor_sync(~0u, mx, m));
        if (lane == 0) sts32f(sb + SM_RED + w * 4, mx);
        cbar();
        {
            const float4 u = lds128f(sb + SM_RED), v = lds128f(sb + SM_RED + 16);
            mx = fmaxf(fmaxf(fmaxf(u.x, u.y), fmaxf(u.z, u.w)), fmaxf(fmaxf(v.x, v.y), fmaxf(v.z, v.w)));
        }
        const uint32_t pa = sb + SM_P + (tid >> 3) * 256 + rank * 128 + (tid & 7) * 16;
        const uint4 s0 = lds128(pa);
        const float sc[8] = {bf_lo(s0.x), bf_hi(s0.x), bf_lo(s0.y), bf_hi(s0.y), bf_lo(s0.z), bf_hi(s0.z), bf_lo(s0.w), bf_hi(s0.w)};
        float l = 0.f;
#pragma unroll
        for (int i = 0; i < 8; i++) l += __expf(sc[i] - mx);
#pragma unroll
        for (int m = 1; m < 32; m <<= 1) l += __shfl_xor_sync(~0u, l, m);
        if (lane == 0) sts32f(sb + SM_RED + 32 + w * 4, l);
        cbar();
        {
            const float4 u = lds128f(sb + SM_RED + 32), v = lds128f(sb + SM_RED + 48);
            l = ((u.x + u.y) + (u.z + u.w)) + ((v.x + v.y) + (v.z + v.w));
        }
        if (tid == 0) st_async_v2(mapa(sb + SM_ML, rank ^ 1), mx, l, mapa(sb + BAR_XML, rank ^ 1));
        mbar_wait_cluster(sb + BAR_XML, 0);
        const float2 o = lds64f(sb + SM_ML);
        const float m = fmaxf(mx, o.x);
        const float inv = __fdividef(1.0f, l * __expf(mx - m) + o.y * __expf(o.x - m));
        const uint32_t p0 = pack2(__expf(sc[0] - m) * inv, __expf(sc[1] - m) * inv), p1 = pack2(__expf(sc[2] - m) * inv, __expf(sc[3] - m) * inv);
        const uint32_t p2 = pack2(__expf(sc[4] - m) * inv, __expf(sc[5] - m) * inv), p3 = pack2(__expf(sc[6] - m) * inv, __expf(sc[7] - m) * inv);
        st_async_v4(mapa(pa, rank ^ 1), p0, p1, p2, p3, mapa(sb + BAR_XP, rank ^ 1));
        sts128(pa, p0, p1, p2, p3);
        cbar();
        mbar_wait_cluster(sb + BAR_XP, 0);
    }

    for (uint32_t n = 0; n < SPIN_LIMIT && !__all_sync(~0u, pkt_ok(mga, tag) && pkt_ok(msb, tag) && pkt_ok(mcb, tag)); n++) {
        mga = ld_pkt2(tmp + 2 * 256); msb = ld_pkt2(tmp + 3 * 256); mcb = ld_pkt2(tmp + 4 * 256);
    }
    const uint32_t ga0 = lo32(mga.a), ga1 = lo32(mga.b), sb0 = lo32(msb.a), sb1 = lo32(msb.b);
    const uint32_t cb0 = hadd2(ONE2, lo32(mcb.a)), cb1 = hadd2(ONE2, lo32(mcb.b));
    u64 red_p = s_line(e1_blk(1, w), 2 * b) + lane * 4, red2_p = s_line(e1_blk(1, w), 4 + b) + lane * 4;

    PIN64(red_p); PIN64(red2_p);
    float oa[4][4];
#pragma unroll
    for (int i = 0; i < 4; i++) { oa[i][0] = oa[i][1] = oa[i][2] = oa[i][3] = 0.f; }
    {
        int stage = N_V % STAGES, phase = tile_phase(N_V);
        auto v_tiles = [&](int v0, int v1) {
#pragma unroll 1
            for (int v = v0; v < v1; v++) {
                const uint32_t tb = sb + SM_RING + stage * TILE_BYTES + grp * 8192 + (sw128 ^ (sub * 32));
                uint2 P[4];
#pragma unroll
                for (int i = 0; i < 4; i++) P[i] = lds64(sb + SM_P + v * 256 + grp * 128 + i * 32 + t * 8);
                mbar_wait(sb + BAR_FULL + 8 * stage, phase);
                uint32_t a[4][4];
#pragma unroll
                for (int i = 0; i < 4; i++) ldsm4t(tb + i * 2048, a[i]);
#pragma unroll
                for (int i = 0; i < 4; i++) mma4(oa[i], a[i], P[i].x, P[i].y);
                __syncwarp();
                if (lane == 0) mbar_arrive(sb + BAR_EMPTY + 8 * stage);
                if (++stage == STAGES) { stage = 0; phase ^= 1; }
            }
        };
        v_tiles(0, WO_AT);
#pragma unroll
        for (int i = 0; i < 4 * WO_EARLY; i++) {
            if ((i & 3) == 0) mbar_wait(sb + full_bar(N_WO + (i >> 2)), tile_phase(N_WO + (i >> 2)));
            ldsm4t(sb + slot_addr(N_WO + (i >> 2)) + w * 2048 + (sw128 ^ ((i & 3) * 32)), A[i]);
        }
        asm volatile("bar.sync 2, 288;" ::: "memory");
        if (tid < WO_EARLY) mbar_arrive_n(sb + BAR_EMPTY + 8 * ((N_WO + tid) % STAGES), 8);
        stage = N_V2 % STAGES; phase = tile_phase(N_V2);
        v_tiles(WO_AT, NT);
    }

    if (t < 2) sts32f(sb + SM_OP + w * 64 + (g >> 1) * 16 + (g & 1) * 4 + t * 8,
                      sel(t1, (oa[0][2] + oa[1][2]) + (oa[2][2] + oa[3][2]), (oa[0][0] + oa[1][0]) + (oa[2][0] + oa[3][0])));
    cbar();

    {
        float acc[4][4];
#pragma unroll
        for (int i = 0; i < 4; i++) { acc[i][0] = acc[i][1] = acc[i][2] = acc[i][3] = 0.f; }
        const float2 u = lds64f(sb + SM_OP + (lane & 15) * 16 + vb * 8), v = lds64f(sb + SM_OP + 256 + (lane & 15) * 16 + vb * 8);
        const uint32_t o2 = pack2(u.x + v.x, u.y + v.y);
#pragma unroll
        for (int s4 = 0; s4 < 4; s4++) {
            const uint32_t b0 = __shfl_sync(~0u, o2, 4 * s4 + t), b1 = __shfl_sync(~0u, o2, 16 + 4 * s4 + t);
            if (s4 >= WO_EARLY) {
                mbar_wait(sb + full_bar(N_V + NT + s4), tile_phase(N_V + NT + s4));
                if (s4 == 3) { }
#pragma unroll
                for (int i = 0; i < 4; i++) ldsm4t(sb + slot_addr(N_V + NT + s4) + w * 2048 + (sw128 ^ (i * 32)), A[4 * s4 + i]);
            }
#pragma unroll
            for (int i = 0; i < 4; i++) mma4(acc[i], A[4 * s4 + i], b0, b1);
        }
        const float r0 = sel(t2, sel(t1, 1.0f, acc[1][0]), sel(t1, acc[0][2], acc[0][0]));
        const float r1 = sel(t2, sel(t1, 1.0f, acc[3][0]), sel(t1, acc[2][2], acc[2][0]));
        const float r2 = sel(t2, 1.0f, sel(t1, acc[3][2], acc[1][2]));
        asm volatile("red.relaxed.gpu.global.add.f32 [%0], %2;\nred.relaxed.gpu.global.add.f32 [%0 + 256], %3;\nred.relaxed.gpu.global.add.f32 [%1], %4;"
                     :: "l"(red_p), "l"(red2_p), "f"(r0), "f"(r1), "f"(r2) : "memory");
        asm volatile("red.relaxed.gpu.global.add.f32 [%0], %2;\nred.relaxed.gpu.global.add.f32 [%0 + 256], %3;\nred.relaxed.gpu.global.add.f32 [%1], %4;"
                     :: "l"(red_p ^ 4096), "l"(red2_p ^ 4096), "f"(r0), "f"(r1), "f"(r2) : "memory");
    }

    constexpr uint32_t CNT = 0x42800000u;
    if (is_gu) {
        uint32_t side;
        asm volatile("ld.volatile.shared.u32 %0, [%1];" : "=r"(side) : "r"(sb + SM_SIDE) : "memory");
        u64 acc_p = (s_line(e1_blk(0, w), lane >> 3) + (lane & 7) * 16) ^ side, acc2_p = (s_line(e1_blk(0, w), 4 + ob) + (lane & 7) * 16) ^ side;
        u64 out_p = s_line(w, lane >> 3) + S_OUT + (lane & 7) * 16, out2_p = s_line(w, 4 + ob) + S_OUT + (lane & 15) * 8;
        u64 gb_p = s_line(w, 6 + ob) + (lane & 15) * 8, y_p = (u64)(q_.out + t1 * D_ + 64 * w + 4 * t2 + g);
        PIN64(acc_p); PIN64(acc2_p); PIN64(out_p); PIN64(out2_p); PIN64(gb_p); PIN64(y_p);
        auto keep = [&](uint32_t x) { return __shfl_sync(~0u, x, lane); };
        const int src = keep(8 * (g & 2) + t), src1 = keep(src + 4), src2 = keep(src + 8), src3 = keep(src + 12);
        const uint32_t p_st = keep(sb + SM_PART + w * 512 + lane * 16), r_st = keep(sb + SM_RED + (vb * 8 + w) * 8);
        tx0 = keep(tx0); tx1 = keep(tx1);
        const uint32_t g1 = g & 1;
        uint32_t cp[8], cn[8];
        float acc[4][4];
#pragma unroll
        for (int i = 0; i < 8; i++) {
            cp[i] = __shfl_sync(~0u, (i & 1) ? cb1 : cb0, 4 * (i >> 1) + src);
            cn[i] = selu(g1, __shfl_sync(~0u, (i & 1) ? sb1 : sb0, 4 * (i >> 1) + src), cp[i]);
        }
        const int frow = (lane & 7) + (lane & 16);
        const uint32_t fa = sb + slot_addr(N_FFN) + grp * 2 * TILE_BYTES + (64 * sub + frow) * 64 + ((lch ^ ((frow >> 1) & 3)) << 4);
        mbar_wait(sb + BAR_FFN + 8 * (w * NQ >> 3), 0);
        uint4 u = ld_strong128(acc_p), v = ld_strong128(acc2_p);
#pragma unroll
        for (int i = 0; i < 16; i++) ldsm4t((fa ^ ((i & 1) * 32)) + (i >> 3) * 2048 + ((i >> 2) & 1) * 512 + ((i >> 1) & 1) * TILE_BYTES, A[i]);
#pragma unroll
        for (int i = 0; i < 4; i++) { acc[i][0] = acc[i][1] = acc[i][2] = acc[i][3] = 0.f; }
#pragma unroll
        for (int i = 0; i < 16; i++) mma4(acc[i & 3], A[i], cn[2 * (i >> 2)], cn[2 * (i >> 2) + 1]);
        sts128f(sb + SM_P + w * 1024 + lane * 16, sel(t2, acc[1][0], acc[0][0]), sel(t2, acc[3][0], acc[2][0]), sel(t2, acc[1][2], acc[0][2]), sel(t2, acc[3][2], acc[2][2]));
        sts128f(sb + SM_P + w * 1024 + 512 + lane * 16, sel(t2, acc[1][1], acc[0][1]), sel(t2, acc[3][1], acc[2][1]), sel(t2, acc[1][3], acc[0][3]), sel(t2, acc[3][3], acc[2][3]));
        bar_arrive<3>();
#pragma unroll
        for (int i = 0; i < 8; i++) cn[i] = selu(g1, cp[i] ^ 0x80008000u, 0u);
        settle(tag, sb + SM_OP, cn[0], cn[1], cn[2], cn[3]); settle(tag, sb + SM_OP, cn[4], cn[5], cn[6], cn[7]);
        for (uint32_t n = 0; !__all_sync(~0u, u.w == CNT && v.w == CNT) && n < SPIN_LIMIT; n++) { u = ld_strong128(acc_p); v = ld_strong128(acc2_p); }
        const uint32_t x0 = hadd2(tx0, hmul2(ga0, pack2(__uint_as_float(u.x), __uint_as_float(u.y))));
        const uint32_t x1 = hadd2(tx1, hmul2(ga1, pack2(__uint_as_float(u.z), __uint_as_float(selu(lane & 8, v.y, v.x)))));
        float c[4] = {0.f, 0.f, 0.f, 0.f};
        mma(c, x0, ONE2, x1, ONE2, x0, x1);
#pragma unroll
        for (int i = 0; i < 4; i++) { acc[i][0] = acc[i][1] = acc[i][2] = acc[i][3] = 0.f; }
        float q, s;
#pragma unroll
        for (int s4 = 0; s4 < 4; s4++) {
            const int from = s4 == 0 ? src : s4 == 1 ? src1 : s4 == 2 ? src2 : src3;
            uint32_t b0 = __shfl_sync(~0u, x0, from), b1 = __shfl_sync(~0u, x1, from);
            b0 = hfma2(b0, cp[2 * s4], hmul2(b0, cn[2 * s4]));
            b1 = hfma2(b1, cp[2 * s4 + 1], hmul2(b1, cn[2 * s4 + 1]));
#pragma unroll
            for (int i = 0; i < 4; i++) mma4(acc[i], A[4 * s4 + i], b0, b1);
            if (s4 == 0) { q = sel(g1, c[1], c[0]); s = c[2] + c[3]; q += __shfl_xor_sync(~0u, q, 4); s += __shfl_xor_sync(~0u, s, 9); }
            if (s4 == 1) q += __shfl_xor_sync(~0u, q, 9);
            if (s4 == 2) { if (lane == 0 || lane == 18) sts64f(r_st, s, fmaxf(fmaf(s * (-1.0f / 64), s, q), 0.f)); }
        }
        sts128f(p_st, sel(t2, acc[1][0] + acc[1][1], acc[0][0] + acc[0][1]), sel(t2, acc[3][0] + acc[3][1], acc[2][0] + acc[2][1]),
                sel(t2, acc[1][2] + acc[1][3], acc[0][2] + acc[0][3]), sel(t2, acc[3][2] + acc[3][3], acc[2][2] + acc[2][3]));
        bar_arrive<4>();
        uint32_t xo[2];
#pragma unroll
        for (int j = 0; j < 2; j++) {
            const uint32_t e0 = __shfl_sync(~0u, x0, 16 * t1 + 8 * j + g), e1 = __shfl_sync(~0u, x1, 16 * t1 + 8 * j + g);
            xo[j] = __byte_perm(e0, e1, t2 ? 0x7632 : 0x5410);
        }
        mbar_wait(sb + BAR_W2, 0);
#pragma unroll
        for (int i = 0; i < 8; i++) ldsm4t(sb + slot_addr(N_FFN + 4) + w * 4096 + (i >> 2) * 2048 + (sw128 ^ ((i & 3) * 32)), A[i]);
#pragma unroll
        for (int i = 0; i < 4; i++) { acc[i][0] = acc[i][1] = acc[i][2] = acc[i][3] = 0.f; }
        bar_sync<5>();
        const uint4 hv = lds128(sb + SM_Q + (g1 * 4 + t) * 16);
#pragma unroll
        for (int i = 0; i < 4; i++) mma4(acc[i], A[i], hv.x, hv.y);
#pragma unroll
        for (int i = 0; i < 4; i++) mma4(acc[i], A[4 + i], hv.z, hv.w);
        float r[4], o[6];
#pragma unroll
        for (int i = 0; i < 4; i++) r[i] = sel(t2, sel(t1, acc[i][3], acc[i][2]), sel(t1, acc[i][1], acc[i][0]));
        asm volatile("atom.relaxed.gpu.global.add.v4.f32 {%0, %1, %2, %3}, [%4], {%5, %6, %7, %8};"
                     : "=f"(o[0]), "=f"(o[1]), "=f"(o[2]), "=f"(o[4]) : "l"(out_p), "f"(r[0]), "f"(r[1]), "f"(r[2]), "f"(1.0f) : "memory");
        asm volatile("atom.relaxed.gpu.global.add.v2.f32 {%0, %1}, [%2], {%3, %4};"
                     : "=f"(o[3]), "=f"(o[5]) : "l"(out2_p), "f"(r[3]), "f"(1.0f) : "memory");
        uint2 gb = ld_strong64(gb_p);
        for (uint32_t n = 0; __any_sync(~0u, __vcmpeq2(gb.x, ~0u) | __vcmpeq2(gb.y, ~0u)) && n < SPIN_LIMIT; n++) gb = ld_strong64(gb_p);
        const uint32_t y0 = hadd2(xo[0], hmul2(gb.x, pack2(o[0] + r[0], o[1] + r[1]))), y1 = hadd2(xo[1], hmul2(gb.y, pack2(o[2] + r[2], o[3] + r[3])));
        asm volatile("{\n.reg .pred p, q;\n.reg .b16 a, b, c, d;\nsetp.eq.f32 p, %3, 0f42280000;\nsetp.eq.f32 q, %4, 0f42280000;\n"
                     "mov.b32 {a, b}, %1;\nmov.b32 {c, d}, %2;\n"
                     "@p st.global.u16 [%0], a;\n@p st.global.u16 [%0 + 32], b;\n@p st.global.u16 [%0 + 64], c;\n@q st.global.u16 [%0 + 96], d;\n}"
                     :: "l"(y_p), "r"(y0), "r"(y1), "f"(o[4]), "f"(o[5]) : "memory");
    } else if (is_gb) {
        const uint32_t fa = sb + slot_addr(N_FFN) + grp * 8192 + (64 * sub + lrow) * 32 + ((lch ^ ((lrow >> 2) & 1)) << 4);
        const int dl = (lane & 7) * 4 + ((lane >> 3) & 1) * 2 + ob;
        u64 gb_p = s_line(role >> 2, 6 + (dl >> 4)) + (dl & 15) * 8 + (role & 3) * 2;
        PIN64(gb_p);
        mbar_wait(sb + BAR_FFN, 0);
        float c[4] = {0.f, 0.f, 0.f, 0.f};
#pragma unroll
        for (int s4 = 0; s4 < 4; s4++) {
            ldsm4t(fa + s4 * 512, A[s4]);
            mma4(c, A[s4], __shfl_sync(~0u, sc0, 4 * s4 + gsrc), __shfl_sync(~0u, sc1, 4 * s4 + gsrc));
        }
        sts32f(sb + SM_PART + (w * 32 + t1 * 16 + (t >> 1) * 8 + g) * 4, sel(t2, sel(t1, c[3], c[2]), sel(t1, c[1], c[0])));
        cbar();
        if (w == 0) {
            float sum = 0.f;
#pragma unroll
            for (int i = 0; i < 8; i++) sum += lds32f(sb + SM_PART + i * 128 + lane * 4);
            asm volatile("st.relaxed.gpu.global.u16 [%0], %1;" :: "l"(gb_p), "h"((uint16_t)pack2(sum, 0.f)) : "memory");
        }
    }
}

typedef CUresult (*EncodeFn)(CUtensorMap*, CUtensorMapDataType, cuuint32_t, void*, const cuuint64_t*, const cuuint64_t*,
                             const cuuint32_t*, const cuuint32_t*, CUtensorMapInterleave, CUtensorMapSwizzle,
                             CUtensorMapL2promotion, CUtensorMapFloatOOBfill);

void make_map(EncodeFn enc, CUtensorMap* m, void* ptr, int cols, int rows, int box_cols, int box_rows, CUtensorMapSwizzle sw) {
    cuuint64_t gd[2] = {(cuuint64_t)cols, (cuuint64_t)rows}, gs[1] = {(cuuint64_t)cols * 2};
    cuuint32_t bd[2] = {(cuuint32_t)box_cols, (cuuint32_t)box_rows}, es[2] = {1, 1};
    enc(m, CU_TENSOR_MAP_DATA_TYPE_BFLOAT16, 2, ptr, gd, gs, bd, es, CU_TENSOR_MAP_INTERLEAVE_NONE, sw,
        CU_TENSOR_MAP_L2_PROMOTION_NONE, CU_TENSOR_MAP_FLOAT_OOB_FILL_NONE);
}

}

extern "C" void kernel_launch(void* const* d_in, const int* in_sizes, int n_in, void* d_out, int out_size) {
    (void)in_sizes; (void)n_in; (void)out_size;
    static EncodeFn enc = nullptr;
    if (!enc) {
        void* fn = nullptr;
        cudaDriverEntryPointQueryResult qr;
        cudaGetDriverEntryPoint("cuTensorMapEncodeTiled", &fn, cudaEnableDefault, &qr);
        enc = (EncodeFn)fn;
        cudaFuncSetAttribute(fused_decode_kernel, cudaFuncAttributeMaxDynamicSharedMemorySize, SMEM_BYTES);
    }
    Params p;
    Ptrs q;
    make_map(enc, &p.m_wmod, d_in[10], MODW, D_, 32, 256, CU_TENSOR_MAP_SWIZZLE_64B);
    make_map(enc, &p.m_wq, d_in[3], QD, D_, 64, 128, CU_TENSOR_MAP_SWIZZLE_128B);
    make_map(enc, &p.m_v, d_in[2], DH, 64 * SK, 64, 128, CU_TENSOR_MAP_SWIZZLE_128B);
    {
        cuuint64_t gd[3] = {64, QD, 8}, gs[2] = {D_ * 2, 128};
        cuuint32_t bd[3] = {64, 16, 8}, es[3] = {1, 1, 1};
        enc(&p.m_wo, CU_TENSOR_MAP_DATA_TYPE_BFLOAT16, 3, d_in[4], gd, gs, bd, es, CU_TENSOR_MAP_INTERLEAVE_NONE,
            CU_TENSOR_MAP_SWIZZLE_128B, CU_TENSOR_MAP_L2_PROMOTION_NONE, CU_TENSOR_MAP_FLOAT_OOB_FILL_NONE);
    }
    for (int i = 0; i < 2; i++) {
        cuuint64_t gd[4] = {FF, 2, 8, D_ / 16}, gs[3] = {8 * FF * 2, FF * 2, 16 * FF * 2};
        cuuint32_t bd[4] = {32, 2, 8, 32 / NQ}, es[4] = {1, 1, 1, 1};
        enc(i ? &p.m_w3 : &p.m_w1, CU_TENSOR_MAP_DATA_TYPE_BFLOAT16, 4, d_in[6 + i], gd, gs, bd, es, CU_TENSOR_MAP_INTERLEAVE_NONE,
            CU_TENSOR_MAP_SWIZZLE_64B, CU_TENSOR_MAP_L2_PROMOTION_NONE, CU_TENSOR_MAP_FLOAT_OOB_FILL_NONE);
    }
    {
        cuuint64_t gd[5] = {64, 2, 8, FF / 16, 8}, gs[4] = {8 * D_ * 2, D_ * 2, 16 * D_ * 2, 128};
        cuuint32_t bd[5] = {64, 2, 8, 2, 8}, es[5] = {1, 1, 1, 1, 1};
        enc(&p.m_w2, CU_TENSOR_MAP_DATA_TYPE_BFLOAT16, 5, d_in[8], gd, gs, bd, es, CU_TENSOR_MAP_INTERLEAVE_NONE,
            CU_TENSOR_MAP_SWIZZLE_128B, CU_TENSOR_MAP_L2_PROMOTION_NONE, CU_TENSOR_MAP_FLOAT_OOB_FILL_NONE);
    }
    make_map(enc, &p.m_gb, d_in[10], MODW, D_, 16, 256, CU_TENSOR_MAP_SWIZZLE_32B);
    q.x = (const __nv_bfloat16*)d_in[0];
    q.kwin = (const __nv_bfloat16*)d_in[1] + (size_t)(SK - WIN) * DH;
    q.c = (const __nv_bfloat16*)d_in[9];
    q.out = (__nv_bfloat16*)d_out;
    fused_decode_kernel<<<NCTA, THREADS, SMEM_BYTES, cudaStreamPerThread>>>(q, p);
}
```

```cpp
#include <cuda_runtime.h>
#include <cuda.h>
#include <cuda_bf16.h>
#include <stdint.h>

namespace {

constexpr int D_ = 512, DH = 128, SK = 16384, WIN = 4096, FF = 1376, QD = 4096, MODW = 3072;
constexpr int NCTA = 128;
constexpr int TILE_BYTES = 16384;
constexpr int NT = 32;
constexpr int STAGES = 13;
constexpr int K_FIRST = 2;
constexpr int FIRST_N = 5;
constexpr int WO_AT = 20;
constexpr int WO_EARLY = 3;
constexpr int PACE = 656;
constexpr int LEAD_NS = 1350;
constexpr int GATE_X = 23;
constexpr int POLL_NS = 300;
constexpr int ALPHA16 = 4;
constexpr int GU_NS = 5075;
constexpr int W2_NS = 6240;
constexpr int GB_LEAD = 390;
constexpr int NQ = 8;
constexpr int PROBES = 6;
constexpr int PROBE_NS = 1000;
constexpr int OPT = 0;
constexpr int EARLY_NS = 800;
constexpr int HEAD_TID = 256;
constexpr int N_WMOD = 0, N_WQ = 2, N_K = 6, N_V = N_K + NT, N_WO = N_V + WO_AT, N_V2 = N_WO + WO_EARLY, N_WO2 = N_V + NT + WO_EARLY, N_FFN = N_V + NT + 4;
constexpr int N_GATE = N_V + GATE_X + WO_EARLY;
constexpr int THREADS = 320;
constexpr int N_MOD_CTA = 80;
#define SPIN_LIMIT_S "4194304"
constexpr unsigned SPIN_LIMIT = 1u << 22;

constexpr int SM_RING = 0;
constexpr int SM_P = STAGES * TILE_BYTES;
constexpr int SM_PART = SM_P + WIN * 2;
constexpr int SM_OP = SM_PART + 8192;
constexpr int SM_Q = SM_OP + 2048;
constexpr int SM_RED = SM_Q + 256;
constexpr int SM_ML = SM_RED + 128;
constexpr int SM_PROG = SM_ML + 16;
constexpr int SM_SIDE = SM_PROG + 16;
constexpr int SM_BAR = SM_SIDE + 16;
constexpr int BAR_FULL = SM_BAR, BAR_EMPTY = SM_BAR + 8 * STAGES, BAR_XQ = SM_BAR + 16 * STAGES,
              BAR_XML = BAR_XQ + 8, BAR_XP = BAR_XQ + 16, BAR_FFN = BAR_XQ + 24;
constexpr int BAR_W2 = BAR_FFN + 8 * NQ;
constexpr int SMEM_BYTES = BAR_W2 + 8;
static_assert(SMEM_BYTES <= 232448, "shared memory");
__host__ __device__ constexpr uint32_t slot_addr(int n) { return SM_RING + (n % STAGES) * TILE_BYTES; }
__host__ __device__ constexpr uint32_t full_bar(int n) { return BAR_FULL + 8 * (n % STAGES); }
__host__ __device__ constexpr uint32_t empty_bar(int n) { return BAR_EMPTY + 8 * (n % STAGES); }
__host__ __device__ constexpr uint32_t tile_phase(int n) { return (n / STAGES) & 1; }
static_assert((N_FFN + 4) % STAGES + 2 <= STAGES && N_FFN % STAGES + 4 <= STAGES, "w1/w3 tiles and w2 tiles occupy consecutive slots");
static_assert(GATE_X >= WO_AT && N_GATE - STAGES < N_V2 && N_FFN + 5 - 2 * STAGES < N_WO && N_FFN + 5 - STAGES < N_WO2,
              "barrier parities the helper warp waits on are unambiguous after the rendezvous; the last wo tiles are not replaced");
__host__ __device__ constexpr int fill_tile(int j) { return j < K_FIRST ? N_K + j : j < K_FIRST + N_K ? j - K_FIRST : j; }

struct Ptrs {
    const __nv_bfloat16 *kwin, *x, *c;
    __nv_bfloat16* out;
};
struct Params {
    CUtensorMap m_wmod, m_wq, m_v, m_wo, m_w1, m_w3, m_w2, m_gb;
};

__device__ unsigned g_epoch;
__device__ __align__(128) uint2 g_mod[2][5 * D_ / 2];
__device__ __align__(256) unsigned char g_s[131072];
__device__ __forceinline__ unsigned long long s_line(int blk, int i) {
    return (((unsigned long long)g_s + 65535) & ~65535ull) + blk * 4096 + (i >> 1) * 1024 + (i & 1) * 256;
}
__device__ __forceinline__ int e1_blk(int r, int w) { return 2 * w + (r ^ (w & 1)); }
constexpr int S_OUT = 512, S_PROG = 128;
__device__ __align__(128) unsigned g_clear;

typedef unsigned long long u64;
__device__ __forceinline__ unsigned time_ns() {
    unsigned r;
    asm volatile("mov.u32 %0, %%globaltimer_lo;" : "=r"(r));
    return r;
}
__device__ __forceinline__ bool elect_one() {
    uint32_t r;
    asm volatile("{\n.reg .pred p;\nelect.sync _|p, 0xffffffff;\nselp.u32 %0, 1, 0, p;\n}" : "=r"(r));
    return r != 0;
}
#define PIN64(v) asm volatile("" : "+l"(v))

__device__ __forceinline__ void mbar_init(uint32_t bar, uint32_t cnt) {
    asm volatile("mbarrier.init.shared::cta.b64 [%0], %1;" :: "r"(bar), "r"(cnt) : "memory");
}
__device__ __forceinline__ void mbar_expect_tx(uint32_t bar, uint32_t bytes) {
    asm volatile("mbarrier.arrive.expect_tx.shared::cta.b64 _, [%0], %1;" :: "r"(bar), "r"(bytes) : "memory");
}
__device__ __forceinline__ void mbar_arrive(uint32_t bar) {
    asm volatile("mbarrier.arrive.shared::cta.b64 _, [%0];" :: "r"(bar) : "memory");
}
__device__ __forceinline__ void mbar_arrive_n(uint32_t bar, uint32_t n) {
    asm volatile("mbarrier.arrive.shared::cta.b64 _, [%0], %1;" :: "r"(bar), "r"(n) : "memory");
}
__device__ __forceinline__ void mbar_wait(uint32_t bar, uint32_t parity) {
    asm volatile("{\n.reg .pred p;\n.reg .u32 n;\nmov.u32 n, 0;\nW0:\n"
                 "mbarrier.try_wait.parity.shared::cta.b64 p, [%0], %1;\n@p bra W1;\n"
                 "add.u32 n, n, 1;\nsetp.lt.u32 p, n, " SPIN_LIMIT_S ";\n@p bra W0;\nW1:\n}"
                 :: "r"(bar), "r"(parity) : "memory");
}
__device__ __forceinline__ void mbar_wait_cluster(uint32_t bar, uint32_t parity) {
    asm volatile("{\n.reg .pred p;\n.reg .u32 n;\nmov.u32 n, 0;\nW0:\n"
                 "mbarrier.try_wait.parity.acquire.cluster.shared::cta.b64 p, [%0], %1;\n@p bra W1;\n"
                 "add.u32 n, n, 1;\nsetp.lt.u32 p, n, " SPIN_LIMIT_S ";\n@p bra W0;\nW1:\n}"
                 :: "r"(bar), "r"(parity) : "memory");
}
__device__ __forceinline__ void bulk_load(uint32_t dst, const void* src, uint32_t bytes, uint32_t bar, uint64_t pol) {
    asm volatile("cp.async.bulk.shared::cluster.global.mbarrier::complete_tx::bytes.L2::cache_hint [%0], [%1], %2, [%3], %4;"
                 :: "r"(dst), "l"(src), "r"(bytes), "r"(bar), "l"(pol) : "memory");
}
__device__ __forceinline__ void tma2d(uint32_t dst, const CUtensorMap* m, int c0, int c1, uint32_t bar) {
    asm volatile("cp.async.bulk.tensor.2d.shared::cluster.global.mbarrier::complete_tx::bytes [%0], [%1, {%3, %4}], [%2];"
                 :: "r"(dst), "l"(m), "r"(bar), "r"(c0), "r"(c1) : "memory");
}
__device__ __forceinline__ void tma2d_hint(uint32_t dst, const CUtensorMap* m, int c0, int c1, uint32_t bar, uint64_t pol) {
    asm volatile("cp.async.bulk.tensor.2d.shared::cluster.global.mbarrier::complete_tx::bytes.L2::cache_hint [%0], [%1, {%3, %4}], [%2], %5;"
                 :: "r"(dst), "l"(m), "r"(bar), "r"(c0), "r"(c1), "l"(pol) : "memory");
}
__device__ __forceinline__ void tma3d(uint32_t dst, const CUtensorMap* m, int c0, int c1, int c2, uint32_t bar) {
    asm volatile("cp.async.bulk.tensor.3d.shared::cluster.global.mbarrier::complete_tx::bytes [%0], [%1, {%3, %4, %5}], [%2];"
                 :: "r"(dst), "l"(m), "r"(bar), "r"(c0), "r"(c1), "r"(c2) : "memory");
}
__device__ __forceinline__ void tma4d(uint32_t dst, const CUtensorMap* m, int c0, int c3, uint32_t bar) {
    asm volatile("cp.async.bulk.tensor.4d.shared::cluster.global.mbarrier::complete_tx::bytes [%0], [%1, {%3, %5, %5, %4}], [%2];"
                 :: "r"(dst), "l"(m), "r"(bar), "r"(c0), "r"(c3), "r"(0) : "memory");
}
__device__ __forceinline__ void tma5d(uint32_t dst, const CUtensorMap* m, int c3, uint32_t bar) {
    asm volatile("cp.async.bulk.tensor.5d.shared::cluster.global.mbarrier::complete_tx::bytes [%0], [%1, {%4, %4, %4, %3, %4}], [%2];"
                 :: "r"(dst), "l"(m), "r"(bar), "r"(c3), "r"(0) : "memory");
}
__device__ __forceinline__ uint32_t mapa(uint32_t addr, uint32_t rank) {
    uint32_t r;
    asm("mapa.shared::cluster.u32 %0, %1, %2;" : "=r"(r) : "r"(addr), "r"(rank));
    return r;
}
__device__ __forceinline__ void st_async_b32(uint32_t addr, uint32_t v, uint32_t bar) {
    asm volatile("st.async.weak.shared::cluster.mbarrier::complete_tx::bytes.b32 [%0], %1, [%2];" :: "r"(addr), "r"(v), "r"(bar) : "memory");
}
__device__ __forceinline__ void st_async_v2(uint32_t addr, float a, float b, uint32_t bar) {
    asm volatile("st.async.weak.shared::cluster.mbarrier::complete_tx::bytes.v2.f32 [%0], {%1, %2}, [%3];" :: "r"(addr), "f"(a), "f"(b), "r"(bar) : "memory");
}
__device__ __forceinline__ void st_async_v4(uint32_t addr, uint32_t a, uint32_t b, uint32_t c, uint32_t d, uint32_t bar) {
    asm volatile("st.async.weak.shared::cluster.mbarrier::complete_tx::bytes.v4.b32 [%0], {%1, %2, %3, %4}, [%5];"
                 :: "r"(addr), "r"(a), "r"(b), "r"(c), "r"(d), "r"(bar) : "memory");
}
template <int ID> __device__ __forceinline__ void bar_sync() { asm volatile("bar.sync %0, 288;" :: "n"(ID) : "memory"); }
template <int ID> __device__ __forceinline__ void bar_arrive() { asm volatile("bar.arrive %0, 288;" :: "n"(ID) : "memory"); }
__device__ __forceinline__ void cbar() { asm volatile("bar.sync 1, 256;" ::: "memory"); }

__device__ __forceinline__ uint4 ldg128(const void* p) {
    uint4 v;
    asm volatile("ld.global.nc.v4.u32 {%0,%1,%2,%3}, [%4];" : "=r"(v.x), "=r"(v.y), "=r"(v.z), "=r"(v.w) : "l"(p));
    return v;
}
__device__ __forceinline__ uint32_t ldg16(const void* p) {
    uint16_t v;
    asm volatile("ld.global.nc.u16 %0, [%1];" : "=h"(v) : "l"(p));
    return v;
}
__device__ __forceinline__ uint4 ld_strong128(unsigned long long p) {
    uint4 v;
    asm volatile("ld.relaxed.gpu.global.v4.b32 {%0,%1,%2,%3}, [%4];" : "=r"(v.x), "=r"(v.y), "=r"(v.z), "=r"(v.w) : "l"(p) : "memory");
    return v;
}
__device__ __forceinline__ uint2 ld_strong64(unsigned long long p) {
    uint2 v;
    asm volatile("ld.relaxed.gpu.global.v2.b32 {%0,%1}, [%2];" : "=r"(v.x), "=r"(v.y) : "l"(p) : "memory");
    return v;
}
__device__ __forceinline__ uint32_t ldg32(const void* p) {
    uint32_t v;
    asm volatile("ld.global.nc.u32 %0, [%1];" : "=r"(v) : "l"(p));
    return v;
}
struct Pkt2 { u64 a, b; };
__device__ __forceinline__ uint32_t lo32(u64 v) { return (uint32_t)v; }
__device__ __forceinline__ uint32_t hi32(u64 v) { return (uint32_t)(v >> 32); }
__device__ __forceinline__ Pkt2 ld_pkt2(const void* p) {
    Pkt2 r;
    asm volatile("ld.relaxed.gpu.global.v2.b64 {%0,%1}, [%2];" : "=l"(r.a), "=l"(r.b) : "l"(p) : "memory");
    return r;
}
__device__ __forceinline__ bool pkt_ok(const Pkt2& r, uint32_t tag) { return hi32(r.a) == tag && hi32(r.b) == tag; }
__device__ __forceinline__ void st_pkt(u64 p, uint32_t data, uint32_t tag) {
    asm volatile("{\n.reg .b64 v;\nmov.b64 v, {%1, %2};\nst.relaxed.gpu.global.b64 [%0], v;\n}" :: "l"(p), "r"(data), "r"(tag) : "memory");
}
__device__ __forceinline__ uint4 lds128(uint32_t a) {
    uint4 v;
    asm volatile("ld.shared.v4.u32 {%0,%1,%2,%3}, [%4];" : "=r"(v.x), "=r"(v.y), "=r"(v.z), "=r"(v.w) : "r"(a) : "memory");
    return v;
}
__device__ __forceinline__ float4 lds128f(uint32_t a) {
    float4 v;
    asm volatile("ld.shared.v4.f32 {%0,%1,%2,%3}, [%4];" : "=f"(v.x), "=f"(v.y), "=f"(v.z), "=f"(v.w) : "r"(a) : "memory");
    return v;
}
__device__ __forceinline__ uint2 lds64(uint32_t a) {
    uint2 v;
    asm volatile("ld.shared.v2.u32 {%0,%1}, [%2];" : "=r"(v.x), "=r"(v.y) : "r"(a) : "memory");
    return v;
}
__device__ __forceinline__ float2 lds64f(uint32_t a) {
    float2 v;
    asm volatile("ld.shared.v2.f32 {%0,%1}, [%2];" : "=f"(v.x), "=f"(v.y) : "r"(a) : "memory");
    return v;
}
__device__ __forceinline__ float lds32f(uint32_t a) {
    float v;
    asm volatile("ld.shared.f32 %0, [%1];" : "=f"(v) : "r"(a) : "memory");
    return v;
}
__device__ __forceinline__ void sts64f(uint32_t a, float x, float y) {
    asm volatile("st.shared.v2.f32 [%0], {%1,%2};" :: "r"(a), "f"(x), "f"(y) : "memory");
}
__device__ __forceinline__ void sts128f(uint32_t a, float x, float y, float z, float w) {
    asm volatile("st.shared.v4.f32 [%0], {%1,%2,%3,%4};" :: "r"(a), "f"(x), "f"(y), "f"(z), "f"(w) : "memory");
}
__device__ __forceinline__ void sts32f(uint32_t a, float x) {
    asm volatile("st.shared.f32 [%0], %1;" :: "r"(a), "f"(x) : "memory");
}
__device__ __forceinline__ void sts128(uint32_t a, uint32_t x, uint32_t y, uint32_t z, uint32_t w) {
    asm volatile("st.shared.v4.u32 [%0], {%1,%2,%3,%4};" :: "r"(a), "r"(x), "r"(y), "r"(z), "r"(w) : "memory");
}
__device__ __forceinline__ void settle(uint32_t tag, uint32_t a, uint32_t x, uint32_t y, uint32_t z, uint32_t w) {
    asm volatile("{\n.reg .pred p;\nsetp.eq.u32 p, %0, 0;\n@p st.shared.v4.u32 [%1], {%2,%3,%4,%5};\n}" :: "r"(tag), "r"(a), "r"(x), "r"(y), "r"(z), "r"(w) : "memory");
}
__device__ __forceinline__ void settle(uint32_t tag, uint32_t a, const float4& v) {
    settle(tag, a, __float_as_uint(v.x), __float_as_uint(v.y), __float_as_uint(v.z), __float_as_uint(v.w));
}
__device__ __forceinline__ void cut(uint32_t tag) {
    asm volatile("{\n.reg .pred p;\nsetp.ne.u32 p, %0, 0;\n@p bra.uni C0;\nnanosleep.u32 1;\nC0:\n}" :: "r"(tag) : "memory");
}
__device__ __forceinline__ void sts16(uint32_t a, uint32_t x) {
    asm volatile("st.shared.u16 [%0], %1;" :: "r"(a), "h"((uint16_t)x) : "memory");
}
__device__ __forceinline__ void ldsm4t(uint32_t a, uint32_t (&r)[4]) {
    asm volatile("ldmatrix.sync.aligned.m8n8.x4.trans.shared.b16 {%0,%1,%2,%3}, [%4];"
                 : "=r"(r[0]), "=r"(r[1]), "=r"(r[2]), "=r"(r[3]) : "r"(a) : "memory");
}
__device__ __forceinline__ void mma(float (&c)[4], uint32_t a0, uint32_t a1, uint32_t a2, uint32_t a3, uint32_t b0, uint32_t b1) {
    asm volatile("mma.sync.aligned.m16n8k16.row.col.f32.bf16.bf16.f32 {%0,%1,%2,%3}, {%4,%5,%6,%7}, {%8,%9}, {%0,%1,%2,%3};"
                 : "+f"(c[0]), "+f"(c[1]), "+f"(c[2]), "+f"(c[3]) : "r"(a0), "r"(a1), "r"(a2), "r"(a3), "r"(b0), "r"(b1));
}
__device__ __forceinline__ void mma4(float (&c)[4], const uint32_t (&a)[4], uint32_t b0, uint32_t b1) { mma(c, a[0], a[1], a[2], a[3], b0, b1); }
__device__ __forceinline__ float sel(uint32_t c, float a, float b) {
    float r;
    asm("{\n.reg .pred p;\nsetp.ne.u32 p, %3, 0;\nselp.f32 %0, %1, %2, p;\n}" : "=f"(r) : "f"(a), "f"(b), "r"(c));
    return r;
}
__device__ __forceinline__ float bf_lo(uint32_t v) { return __uint_as_float(v << 16); }
__device__ __forceinline__ float bf_hi(uint32_t v) { return __uint_as_float(v & 0xffff0000u); }
__device__ __forceinline__ uint32_t pack2(float lo, float hi) {
    uint32_t r;
    asm("cvt.rn.bf16x2.f32 %0, %1, %2;" : "=r"(r) : "f"(hi), "f"(lo));
    return r;
}
__device__ __forceinline__ float rbf(float x) { return __uint_as_float(pack2(0.f, x)); }
__device__ __forceinline__ uint32_t hadd2(uint32_t a, uint32_t b) { uint32_t r; asm("add.rn.bf16x2 %0, %1, %2;" : "=r"(r) : "r"(a), "r"(b)); return r; }
__device__ __forceinline__ uint32_t hsub2(uint32_t a, uint32_t b) { uint32_t r; asm("sub.rn.bf16x2 %0, %1, %2;" : "=r"(r) : "r"(a), "r"(b)); return r; }
__device__ __forceinline__ uint32_t hmul2(uint32_t a, uint32_t b) { uint32_t r; asm("mul.rn.bf16x2 %0, %1, %2;" : "=r"(r) : "r"(a), "r"(b)); return r; }
__device__ __forceinline__ uint32_t hfma2(uint32_t a, uint32_t b, uint32_t c) { uint32_t r; asm("fma.rn.bf16x2 %0, %1, %2, %3;" : "=r"(r) : "r"(a), "r"(b), "r"(c)); return r; }
__device__ __forceinline__ uint32_t selu(uint32_t c, uint32_t a, uint32_t b) { return __float_as_uint(sel(c, __uint_as_float(a), __uint_as_float(b))); }
constexpr uint32_t ONE2 = 0x3f803f80u;
__device__ __forceinline__ float silu_f(float x) {
    float e, r;
    asm("ex2.approx.ftz.f32 %0, %1;" : "=f"(e) : "f"(x * -1.4426950408889634f));
    asm("rcp.approx.ftz.f32 %0, %1;" : "=f"(r) : "f"(1.0f + e));
    return x * r;
}
__device__ __forceinline__ float rcp_sd(float m2) {
    float s, r;
    asm("sqrt.approx.ftz.f32 %0, %1;" : "=f"(s) : "f"(rbf(rbf(m2 * (1.0f / D_)) + 1e-5f)));
    asm("rcp.approx.ftz.f32 %0, %1;" : "=f"(r) : "f"(rbf(s)));
    return r;
}
__device__ __forceinline__ uint32_t ln_mod2(uint32_t x, uint32_t mean2, float rsd, uint32_t c1, uint32_t sh) {
    const uint32_t d = hsub2(x, mean2);
    return hadd2(hmul2(pack2(bf_lo(d) * rsd, bf_hi(d) * rsd), c1), sh);
}
__device__ __forceinline__ int pair_pos(int j) { return 2 * (j & 3) + (j >> 2); }

__global__ void __cluster_dims__(2, 1, 1) __launch_bounds__(THREADS, 1)
fused_decode_kernel(const __grid_constant__ Ptrs q_, const __grid_constant__ Params p) {
    extern __shared__ __align__(1024) unsigned char smem[];
    unsigned t_top;
    asm volatile("mov.u32 %0, %%globaltimer_lo;" : "=r"(t_top));
    const int tid = threadIdx.x;
    uint32_t z0;
    asm("and.b32 %0, %1, 1024;" : "=r"(z0) : "r"(tid));
    const char* kw = *(const char* const*)((const char*)&q_.kwin + z0);
    const uint32_t sb = (uint32_t)__cvta_generic_to_shared(smem);
    auto place = [](int cl) { return cl < 4 ? 8 * cl + 39 : cl - 4 + max((cl * 37 - 36 * 37) >> 8, 0); };
    uint32_t z2;
    asm("and.b32 %0, %1, 2048;" : "=r"(z2) : "r"(tid));
    const int cv = blockIdx.x + z2, pw = place(cv >> 1);
    static_assert(SK * DH * 2 == 1 << 22 && TILE_BYTES == 1 << 14, "koff");
    const char* kp;
    auto set_kp = [&](uint32_t off) {
        asm volatile("{\n.reg .u32 lo, hi;\nmov.b64 {lo, hi}, %1;\nadd.cc.u32 lo, lo, %2;\naddc.u32 hi, hi, 0;\nmov.b64 %0, {lo, hi};\n}"
                     : "=l"(kp) : "l"(kw), "r"(off));
    };
    uint64_t pol;
    asm("createpolicy.fractional.L2::evict_first.b64 %0, 1.0;" : "=l"(pol));
    auto fill_k = [&](int n) {
        mbar_expect_tx(sb + full_bar(n), TILE_BYTES);
        bulk_load(sb + slot_addr(n), kp + (n - N_K) * 2 * TILE_BYTES, TILE_BYTES, sb + full_bar(n), pol);
    };
    static_assert(K_FIRST >= 1, "head block starts with K tile 0");
    if (tid + (sb >> 28) == HEAD_TID) {
        mbar_init(sb + full_bar(N_K), 1);
        set_kp(((pw & 7) << 22) | ((pw & 8) << 24) | ((pw & 48) << 21) | ((cv & 1) << 14));
        bulk_load(sb + slot_addr(N_K), kp, TILE_BYTES, sb + full_bar(N_K), pol);
        mbar_expect_tx(sb + full_bar(N_K), TILE_BYTES);
#pragma unroll
        for (int j = 1; j < K_FIRST; j++) { mbar_init(sb + full_bar(N_K + j), 1); fill_k(N_K + j); }
    }
    __syncwarp();
    const int cta = blockIdx.x, rank = cta & 1, pv = place(cta >> 1);
    const int b = (pv >> 3) & 1, h = (pv & 7) | ((pv >> 1) & 24), bh = 32 * b + h;
    auto first_fill = [&](int j) {
        const int n = fill_tile(j);
        if (n >= N_K) {
            fill_k(n);
        } else if (n >= N_WQ) {
            mbar_expect_tx(sb + full_bar(n), TILE_BYTES);
            tma2d(sb + slot_addr(n), &p.m_wq, h * DH + 64 * rank, 128 * (n - N_WQ), sb + full_bar(n));
        } else if (cta < N_MOD_CTA) {
            mbar_expect_tx(sb + full_bar(n), TILE_BYTES);
            tma2d(sb + slot_addr(n), &p.m_wmod, 32 * cta, 256 * n, sb + full_bar(n));
        } else {
            mbar_arrive(sb + full_bar(n));
        }
    };
    if ((tid >> 5) == HEAD_TID / 32 && elect_one()) {
#pragma unroll
        for (int j = K_FIRST; j < FIRST_N; j++) mbar_init(sb + full_bar(fill_tile(j)), 1);
#pragma unroll
        for (int j = K_FIRST; j < FIRST_N; j++) first_fill(j);
        asm volatile("fence.mbarrier_init.release.cluster;" ::: "memory");
    }
    __syncwarp();
    const int role = cta / 3;
    const bool is_gu = cta == 3 * role, is_gb = cta == 3 * role + 1 && role < 32;
    if (tid >= 288) {
        const unsigned t_start = t_top;
        asm volatile("barrier.cluster.arrive.relaxed.aligned;" ::: "memory");
        unsigned tag;
        asm volatile("ld.relaxed.gpu.global.u32 %0, [%1];" : "=r"(tag) : "l"(&g_epoch) : "memory");
        tag += 1;
        if (cta == NCTA - 1) {
#pragma unroll 2
            for (int i = tid - 288; i < 128 * 8; i += 32) {
                uint4* q = reinterpret_cast<uint4*>(s_line(i >> 6, (i >> 3) & 7)) + (i & 7);
                const uint32_t v = (i & 48) == 48 ? ~0u : 0u;
                q[0] = make_uint4(v, v, v, v);
                q[8] = q[32] = q[40] = make_uint4(0u, 0u, 0u, 0u);
            }
            __syncwarp();
            asm volatile("fence.acq_rel.gpu;" ::: "memory");
            if (tid == 288) asm volatile("st.relaxed.gpu.global.u32 [%0], %1;" :: "l"(&g_clear), "r"(tag) : "memory");
        }
        asm volatile("barrier.cluster.wait.acquire.aligned;" ::: "memory");
        mbar_wait_cluster(sb + BAR_XQ, 0);
        for (uint32_t n = 0; n < SPIN_LIMIT; n++) {
            unsigned c;
            asm volatile("ld.relaxed.gpu.global.u32 %0, [%1];" : "=r"(c) : "l"(&g_clear) : "memory");
            if (c == tag) break;
        }
        asm volatile("fence.acq_rel.gpu;" ::: "memory");
        asm volatile("st.volatile.shared.u32 [%0], %1;" :: "r"(sb + SM_SIDE), "r"(0) : "memory");
        asm volatile("bar.sync 2, 288;" ::: "memory");
        if (elect_one()) {
            asm volatile("prefetch.tensormap [%0];" :: "l"(is_gu ? &p.m_w1 : &p.m_gb) : "memory");
            asm volatile("prefetch.tensormap [%0];" :: "l"(&p.m_w3) : "memory");
            asm volatile("prefetch.tensormap [%0];" :: "l"(&p.m_w2) : "memory");
            const int issue = ((4 * N_GATE - 11 - 2 * WO_EARLY) * PACE >> 2) - LEAD_NS;
            unsigned now, c = 0, best[2] = {~0u, ~0u}, np = is_gu ? 0 : PROBES;
            auto probe = [&]() {
                const int k = np >> 1, i = (role >> 3) + 2 * k;
                const u64 a = (s_line(e1_blk(0, role & 7), i < 6 ? i : i - 6) + (k ? 512 * k - 384 : 0)) ^ ((np & 1) << 12);
                unsigned v, c0, c1 = 0;
                asm volatile("mov.u32 %0, %%clock;" : "=r"(c0));
                asm volatile("ld.relaxed.gpu.global.u32 %0, [%1];" : "=r"(v) : "l"(a) : "memory");
                asm volatile("{\n.reg .pred p;\nsetp.ne.u32 p, %1, 0xffffffff;\n@p mov.u32 %0, %%clock;\n}" : "+r"(c1) : "r"(v));
                if (np & 1) best[1] = min(best[1], c1 - c0); else best[0] = min(best[0], c1 - c0);
                np++;
                if (!(np & 1)) asm volatile("st.volatile.shared.u32 [%0], %1;" :: "r"(sb + SM_SIDE), "r"(best[0] <= best[1] ? 0 : 4096) : "memory");
            };
#pragma unroll 1
            while (np < PROBES) {
                now = time_ns();
                if ((int)(now - t_start) >= issue + EARLY_NS) break;
                probe();
            }
            mbar_wait(sb + full_bar(N_GATE), tile_phase(N_GATE));
            now = time_ns();
            const unsigned mine = (1u << 24) + min(now - t_start, 100000u);
            const u64 prog = s_line(0, 7) + S_PROG;
            asm volatile("red.relaxed.gpu.global.add.u32 [%0], %1;" :: "l"(prog), "r"(mine) : "memory");
            if (is_gu || is_gb) {
#pragma unroll
                for (int i = 0; i < 6; i++) mbar_wait(sb + empty_bar(N_FFN + i), tile_phase(N_FFN + i) ^ 1);
#pragma unroll
                for (int i = 0; i < NQ; i++) mbar_expect_tx(sb + BAR_FFN + 8 * i, is_gu ? 65536 / NQ : 8192);
                mbar_expect_tx(sb + BAR_W2, 32768);
                unsigned due = 0, next = now;
                constexpr unsigned full = (unsigned)NCTA << 24;
                asm volatile("st.volatile.shared.u32 [%0], %1;" :: "r"(sb + SM_PROG), "r"(mine) : "memory");
#pragma unroll 1
                for (uint32_t n = 0; n < 4096; n++) {
                    unsigned v;
                    asm volatile("ld.volatile.shared.u32 %0, [%1];" : "=r"(v) : "r"(sb + SM_PROG) : "memory");
                    if (v > c) {
                        c = v;
                        const int arr = (int)__fdividef((float)(c & 0xffffffu), (float)(c >> 24));
                        due = arr - ((arr - issue) * ALPHA16 >> 4) + (is_gb ? W2_NS - GB_LEAD : GU_NS);
                    }
                    now = time_ns();
                    if (now - t_start + PROBE_NS >= due) np = PROBES;
                    if ((c >= full && np == PROBES) || now - t_start >= due) break;
                    if ((int)(now - next) >= 0 && c < full) {
                        asm volatile("cp.async.cg.shared.global [%0], [%1], 16;" :: "r"(sb + SM_PROG), "l"(prog) : "memory");
                        next = now + POLL_NS;
                    }
                    if (np < PROBES) probe();
                }
#pragma unroll 1
                for (uint32_t n = 0; n < 1024 && now - t_start < due; n++) now = time_ns();
                if (is_gu) {
#pragma unroll
                    for (int i = 0; i < 2 * NQ; i++) {
                        const int q = i >> 1, r0 = q * (512 / NQ);
                        tma4d(sb + slot_addr(N_FFN) + (r0 >> 8) * 2 * TILE_BYTES + (i & 1) * TILE_BYTES + (r0 & 255) * 64, (i & 1) ? &p.m_w3 : &p.m_w1, 32 * role, r0 / 16, sb + BAR_FFN + 8 * q);
                    }
#pragma unroll 1
                    for (uint32_t n = 0; n < 1024 && now - t_start < due + (W2_NS - GU_NS); n++) now = time_ns();
                    tma5d(sb + slot_addr(N_FFN + 4), &p.m_w2, 2 * role, sb + BAR_W2);
                } else {
                    tma2d(sb + slot_addr(N_FFN), &p.m_gb, 5 * D_ + 16 * role, 0, sb + BAR_FFN);
                    tma2d(sb + slot_addr(N_FFN) + 8192, &p.m_gb, 5 * D_ + 16 * role, 256, sb + BAR_FFN + 8);
                }
                asm volatile("cp.async.wait_all;" ::: "memory");
            }
        }
        __syncwarp();
        if (is_gu) {
            const int lane = tid & 31;
            auto sum8 = [&](uint32_t a, int stride) {
                float4 u[8];
#pragma unroll
                for (int i = 0; i < 8; i++) u[i] = lds128f(a + i * stride);
                return make_float4(((u[0].x + u[1].x) + (u[2].x + u[3].x)) + ((u[4].x + u[5].x) + (u[6].x + u[7].x)),
                                   ((u[0].y + u[1].y) + (u[2].y + u[3].y)) + ((u[4].y + u[5].y) + (u[6].y + u[7].y)),
                                   ((u[0].z + u[1].z) + (u[2].z + u[3].z)) + ((u[4].z + u[5].z) + (u[6].z + u[7].z)),
                                   ((u[0].w + u[1].w) + (u[2].w + u[3].w)) + ((u[4].w + u[5].w) + (u[6].w + u[7].w)));
            };
            uint32_t h_st = sb + SM_Q + (((lane & 1) * 4 + ((lane >> 2) & 3)) * 4 + (lane & 2) + (lane >> 4)) * 4;
            bar_sync<3>();
            const float4 C = sum8(sb + SM_P + lane * 16, 1024), S = sum8(sb + SM_P + 512 + lane * 16, 1024);
            const uint32_t st_ld = sb + SM_RED + (lane & 1) * 64;
            settle(tag, sb + SM_OP, C); settle(tag, sb + SM_OP, S); settle(tag, sb + SM_OP, h_st, st_ld, 0, 0);
            if (OPT & 1) bar_sync<6>(); else bar_sync<4>();
            const float4 r0 = lds128f(st_ld), r1 = lds128f(st_ld + 16), r2 = lds128f(st_ld + 32), r3 = lds128f(st_ld + 48);
            float4 Y;
            if (!(OPT & 1)) Y = sum8(sb + SM_PART + lane * 16, 512);
            const float e1 = r0.z - r0.x, e2 = r1.x - r0.x, e3 = r1.z - r0.x, e4 = r2.x - r0.x, e5 = r2.z - r0.x, e6 = r3.x - r0.x, e7 = r3.z - r0.x;
            const float se = ((e1 + e2) + (e3 + e4)) + ((e5 + e6) + e7);
            const float ee = (fmaf(e1, e1, e2 * e2) + fmaf(e3, e3, e4 * e4)) + fmaf(e5, e5, fmaf(e6, e6, e7 * e7));
            const float sq = ((r0.y + r0.w) + (r1.y + r1.w)) + ((r2.y + r2.w) + (r3.y + r3.w));
            const float rsd = rcp_sd(fmaf(se * (-1.0f / D_), se, fmaf(ee, 1.0f / 64, sq))), mu = -rbf(fmaf(r0.x, 8.0f, se) * (1.0f / D_));
            if (OPT & 1) {
                settle(tag, sb + SM_OP, __float_as_uint(rsd), __float_as_uint(mu), 0, 0);
                bar_sync<4>();
                Y = sum8(sb + SM_PART + lane * 16, 512);
            }
            const uint32_t gr = pack2(fmaf(rsd, fmaf(mu, C.x, Y.x), S.x), fmaf(rsd, fmaf(mu, C.z, Y.z), S.z));
            const uint32_t ur = pack2(fmaf(rsd, fmaf(mu, C.y, Y.y), S.y), fmaf(rsd, fmaf(mu, C.w, Y.w), S.w));
            const uint32_t hv = hmul2(pack2(silu_f(bf_lo(gr)), silu_f(bf_hi(gr))), ur);
            sts32f(h_st, __uint_as_float(hv));
            bar_arrive<5>();
            if (cta == 0 && lane == 0) g_epoch = tag;
        }
        return;
    }
    if (tid >= 256) {
        set_kp(bh * (SK * DH * 2) + rank * TILE_BYTES);
        const unsigned t_start = t_top;
        auto pace = [&](int q4) {
            const int due = (q4 * PACE >> 2) - LEAD_NS;
            unsigned now, n = 0;
            do { now = time_ns(); } while ((int)(now - t_start) < due && ++n < 256);
        };
        if (tid == 256) {
#pragma unroll
            for (int j = FIRST_N; j < STAGES; j++) mbar_init(sb + full_bar(fill_tile(j)), 1);
#pragma unroll
            for (int s = 0; s < STAGES; s++) mbar_init(sb + BAR_EMPTY + 8 * s, 8);
            mbar_init(sb + BAR_XQ, 1); mbar_init(sb + BAR_XML, 1); mbar_init(sb + BAR_XP, 1);
#pragma unroll
            for (int i = 0; i < NQ + 1; i++) mbar_init(sb + BAR_FFN + 8 * i, 1);
            mbar_expect_tx(sb + BAR_XQ, 256); mbar_expect_tx(sb + BAR_XML, 8); mbar_expect_tx(sb + BAR_XP, WIN);
            asm volatile("fence.mbarrier_init.release.cluster;" ::: "memory");
            asm volatile("fence.proxy.async.shared::cta;" ::: "memory");
        }
        __syncwarp();
        asm volatile("barrier.cluster.arrive.relaxed.aligned;" ::: "memory");
        if (elect_one()) {
#pragma unroll
            for (int j = FIRST_N; j < STAGES; j++) {
                pace(j <= K_FIRST ? 4 * j : j <= K_FIRST + 2 ? 4 * K_FIRST + 5 * (j - K_FIRST) / 2 :
                     j <= K_FIRST + 6 ? 4 * K_FIRST + 5 + 2 * (j - K_FIRST - 2) : 4 * j - 11);
                first_fill(j);
            }
        }
        __syncwarp();
        asm volatile("barrier.cluster.wait.acquire.aligned;" ::: "memory");
        if (elect_one()) {
            asm volatile("prefetch.tensormap [%0];" :: "l"(&p.m_v) : "memory");
            asm volatile("prefetch.tensormap [%0];" :: "l"(&p.m_wo) : "memory");
            int s = 0, ph = 0;
#pragma unroll 1
            for (int n = STAGES; n < N_FFN; n++) {
                const uint32_t dst = sb + SM_RING + s * TILE_BYTES, bar = sb + BAR_FULL + 8 * s;
                mbar_wait(sb + BAR_EMPTY + 8 * s, ph);
                mbar_expect_tx(bar, TILE_BYTES);
                pace(n < N_WO ? 4 * n - 11 : n < N_V2 ? 2 * (N_WO + n) - 11 : n < N_WO2 ? 4 * n - 11 - 2 * WO_EARLY : 2 * (N_WO2 + n - WO_EARLY) - 11);
                if (n < N_V) bulk_load(dst, kp + (n - N_K) * 2 * TILE_BYTES, TILE_BYTES, bar, pol);
                else if (n >= N_WO2 || (n >= N_WO && n < N_V2)) tma3d(dst, &p.m_wo, 0, h * DH + 64 * rank + 16 * (n - (n < N_V2 ? N_WO : N_V + NT)), 0, bar);
                else tma2d_hint(dst, &p.m_v, 64 * rank, bh * SK + (SK - WIN) + 128 * (n - (n < N_WO ? N_V : N_V + WO_EARLY)), bar, pol);
                if (++s == STAGES) { s = 0; ph ^= 1; }
            }
        }
        return;
    }

    const unsigned t_c = t_top;
    const int lane = tid & 31, w = tid >> 5, g = lane >> 2, t = lane & 3;
    const int hgrp = 4 * w + (g & 3);
    const int vb = g >> 2;
    const uint32_t cv0 = ldg32(q_.c + vb * D_ + 16 * hgrp + 2 * t), cv1 = ldg32(q_.c + vb * D_ + 16 * hgrp + 8 + 2 * t);
    unsigned tag;
    asm volatile("ld.relaxed.gpu.global.u32 %0, [%1];" : "=r"(tag) : "l"(&g_epoch) : "memory");
    const uint4 xa = ldg128(q_.x + b * D_ + 16 * lane), xb = ldg128(q_.x + b * D_ + 16 * lane + 8);
    const uint32_t xh0 = ldg32(q_.x + b * D_ + 16 * hgrp + 2 * t), xh1 = ldg32(q_.x + b * D_ + 16 * hgrp + 8 + 2 * t);
    asm volatile("barrier.cluster.arrive.relaxed.aligned;" ::: "memory");
#pragma unroll 1
    for (uint32_t n = t_c; n < 2; n++) asm volatile("nanosleep.u32 1;" ::: "memory");
    const int grp = w >> 2, sub = w & 3;
    const int lrow = (lane & 7) + 8 * (lane >> 4);
    const int lch = (lane >> 3) & 1;
    const int ob = lane >> 4;
    const uint32_t t1 = t & 1, t2 = t & 2;
    const int gsrc = 16 * (g & 1) + t;
    const uint32_t sw128 = lrow * 128 + ((lch ^ (lrow & 7)) << 4);
    uint32_t A[16][4];

    const uint32_t sc0 = pack2(silu_f(bf_lo(cv0)), silu_f(bf_hi(cv0))), sc1 = pack2(silu_f(bf_lo(cv1)), silu_f(bf_hi(cv1)));
    tag += 1;
    asm volatile("barrier.cluster.wait.acquire.aligned;" ::: "memory");
    mbar_wait(sb + BAR_FULL + 8 * (N_WMOD + grp), 0);
    if (cta < N_MOD_CTA) {
        const uint32_t tb = sb + SM_RING + (N_WMOD + grp) * TILE_BYTES + (64 * sub + lrow) * 64;
#pragma unroll
        for (int i = 0; i < 8; i++)
            ldsm4t(tb + (i >> 1) * 1024 + (((2 * (i & 1) + lch) ^ ((lrow >> 1) & 3)) << 4), A[i]);
        float acc[2][4] = {{0.f, 0.f, 0.f, 0.f}, {0.f, 0.f, 0.f, 0.f}};
#pragma unroll
        for (int s = 0; s < 4; s++) {
            const uint32_t b0 = __shfl_sync(~0u, sc0, 4 * s + gsrc), b1 = __shfl_sync(~0u, sc1, 4 * s + gsrc);
            mma4(acc[0], A[2 * s], b0, b1);
            mma4(acc[1], A[2 * s + 1], b0, b1);
        }
        sts32f(sb + SM_P + (w * 64 + 8 * t + g) * 4, sel(t2, sel(t1, acc[1][2], acc[1][0]), sel(t1, acc[0][2], acc[0][0])));
        sts32f(sb + SM_P + (w * 64 + 32 + 8 * t + g) * 4, sel(t2, sel(t1, acc[1][3], acc[1][1]), sel(t1, acc[0][3], acc[0][1])));
        cbar();
        if (w == 0) {
            const bool adj = cta < 32;
            const uint32_t a0 = sb + SM_P + (adj ? 2 * lane : ob * 32 + (lane & 1) * 16 + ((lane >> 1) & 7)) * 4, a1 = a0 + (adj ? 4 : 32);
            float2 sum = make_float2(0.f, 0.f);
#pragma unroll
            for (int i = 0; i < 8; i++) { sum.x += lds32f(a0 + i * 256); sum.y += lds32f(a1 + i * 256); }
            st_pkt((u64)&g_mod[ob][16 * cta + (adj ? (lane & 8) + pair_pos(lane & 7) : lane & 15)], pack2(sum.x, sum.y), tag);
        }
    }
    __syncwarp();
    if (lane == 0) mbar_arrive_n(sb + BAR_EMPTY + 8 * (N_WMOD + grp), 2);

    {
        const uint2* mp = &g_mod[b][vb * 256 + 8 * hgrp + 2 * t];
        const uint32_t ms = sb + SM_PART + tid * 16;
        auto fetch_mod = [&](uint32_t k) {
            asm volatile("cp.async.cg.shared.global [%0], [%1], 16;\ncp.async.commit_group;" :: "r"(ms + k), "l"(mp) : "memory");
        };
        fetch_mod(0);
        float xs[16] = {bf_lo(xa.x), bf_hi(xa.x), bf_lo(xa.y), bf_hi(xa.y), bf_lo(xa.z), bf_hi(xa.z), bf_lo(xa.w), bf_hi(xa.w),
                        bf_lo(xb.x), bf_hi(xb.x), bf_lo(xb.y), bf_hi(xb.y), bf_lo(xb.z), bf_hi(xb.z), bf_lo(xb.w), bf_hi(xb.w)};
        float s = 0.f;
#pragma unroll
        for (int i = 0; i < 16; i++) s += xs[i];
#pragma unroll
        for (int m = 1; m < 32; m <<= 1) s += __shfl_xor_sync(~0u, s, m);
        const float mean = s * (1.0f / D_);
        float q = 0.f;
#pragma unroll
        for (int i = 0; i < 16; i++) q += (xs[i] - mean) * (xs[i] - mean);
#pragma unroll
        for (int m = 1; m < 32; m <<= 1) q += __shfl_xor_sync(~0u, q, m);
        const uint32_t mean2 = pack2(mean, mean);
        const float rsd = rcp_sd(q);

        mbar_wait(sb + BAR_FULL + 8 * (N_WQ + (w >> 1)), 0);
        const uint32_t tb = sb + SM_RING + (N_WQ + (w >> 1)) * TILE_BYTES + (w & 1) * 8192;
#pragma unroll
        for (int i = 0; i < 16; i++) ldsm4t(tb + (i >> 2) * 2048 + (sw128 ^ ((i & 3) * 32)), A[i]);
        __syncwarp();
        if (lane == 0) mbar_arrive_n(sb + BAR_EMPTY + 8 * (N_WQ + (w >> 1)), 4);

        Pkt2 m;
        for (uint32_t n = 0, k = 0; n < SPIN_LIMIT; n++) {
            fetch_mod(k ^ 4096);
            asm volatile("cp.async.wait_group 1;" ::: "memory");
            const uint4 u = lds128(ms + k);
            m.a = u.x | (u64)u.y << 32; m.b = u.z | (u64)u.w << 32;
            if (__all_sync(~0u, pkt_ok(m, tag))) break;
            k ^= 4096;
        }
        const uint32_t ca0 = __shfl_xor_sync(~0u, lo32(m.a), 16), ca1 = __shfl_xor_sync(~0u, lo32(m.b), 16);
        const uint32_t v0 = ln_mod2(xh0, mean2, rsd, hadd2(ONE2, ca0), lo32(m.a));
        const uint32_t v1 = ln_mod2(xh1, mean2, rsd, hadd2(ONE2, ca1), lo32(m.b));
        float acc[4][4];
#pragma unroll
        for (int i = 0; i < 4; i++) { acc[i][0] = acc[i][1] = acc[i][2] = acc[i][3] = 0.f; }
#pragma unroll
        for (int s4 = 0; s4 < 4; s4++) {
            const uint32_t b0 = __shfl_sync(~0u, v0, 4 * s4 + t), b1 = __shfl_sync(~0u, v1, 4 * s4 + t);
#pragma unroll
            for (int i = 0; i < 4; i++) mma4(acc[i], A[4 * s4 + i], b0, b1);
        }
        sts32f(sb + SM_OP + (w * 64 + 16 * t + g) * 4, sel(t2, sel(t1, acc[3][0], acc[2][0]), sel(t1, acc[1][0], acc[0][0])));
        sts32f(sb + SM_OP + (w * 64 + 16 * t + 8 + g) * 4, sel(t2, sel(t1, acc[3][2], acc[2][2]), sel(t1, acc[1][2], acc[0][2])));
        cbar();
        if (w == 0) {
            float2 sum = make_float2(0.f, 0.f);
#pragma unroll
            for (int i = 0; i < 8; i++) { const float2 u = lds64f(sb + SM_OP + (i * 64 + 2 * lane) * 4); sum.x += u.x; sum.y += u.y; }
            const uint32_t v = pack2(sum.x, sum.y), a = sb + SM_Q + rank * 128 + lane * 4;
            st_async_b32(mapa(a, rank ^ 1), v, mapa(sb + BAR_XQ, rank ^ 1));
            st_async_b32(mapa(a, rank), v, mapa(sb + BAR_XQ, rank));
        }
        mbar_wait_cluster(sb + BAR_XQ, 0);
    }

    Pkt2 mga, msb, mcb;
    uint32_t tx0, tx1;
    const uint2* tmp = &g_mod[ob][32 * w + 2 * (lane & 15)];
    {
        uint4 Q[4];
        uint32_t koff[4];
#pragma unroll
        for (int i = 0; i < 4; i++) {
            const int ch = t + 4 * (i ^ (g & 1));
            Q[i] = lds128(sb + SM_Q + ch * 16);
            koff[i] = (sub * 16 + g) * 256 + ch * 16;
        }
        float mx = -INFINITY;
        int stage = N_K + grp, phase = 0;
#pragma unroll 1
        for (int it = 0; it < NT / 2; it++) {
            const uint32_t tb = sb + SM_RING + stage * TILE_BYTES;
            mbar_wait(sb + BAR_FULL + 8 * stage, phase);
            uint4 Ka[4], Kb[4];
#pragma unroll
            for (int i = 0; i < 4; i++) { Ka[i] = lds128(tb + koff[i]); Kb[i] = lds128(tb + koff[i] + 2048); }
            float c0[4] = {0.f, 0.f, 0.f, 0.f}, c1[4] = {0.f, 0.f, 0.f, 0.f};
#pragma unroll
            for (int i = 0; i < 4; i++) {
                mma(c0, Ka[i].x, Kb[i].x, Ka[i].y, Kb[i].y, Q[i].x, Q[i].y);
                mma(c1, Ka[i].z, Kb[i].z, Ka[i].w, Kb[i].w, Q[i].z, Q[i].w);
            }
            __syncwarp();
            if (lane == 0) mbar_arrive_n(sb + BAR_EMPTY + 8 * stage, 2);
            const float lo = (g & 1) ? c0[1] + c1[1] : c0[0] + c1[0];
            const float hi = (g & 1) ? c0[3] + c1[3] : c0[2] + c1[2];
            const float sc = rbf(rbf(t1 ? hi : lo) * 0.08838834764831845f);
            mx = fmaxf(mx, sc);
            if (t < 2) sts16(sb + SM_P + ((2 * it + grp) * 128 + rank * 64 + sub * 16 + 4 * (g >> 1) + 2 * t + (g & 1)) * 2, __float_as_uint(sc) >> 16);
            stage += 2;
            if (stage >= STAGES) { stage -= STAGES; phase ^= 1; }
        }

        mga = ld_pkt2(tmp + 2 * 256); msb = ld_pkt2(tmp + 3 * 256); mcb = ld_pkt2(tmp + 4 * 256);
        const __nv_bfloat16* xp = q_.x + ob * D_ + 64 * w + 4 * (lane & 8) + (lane & 7);
        tx0 = ldg16(xp) | ldg16(xp + 8) << 16;
        tx1 = ldg16(xp + 16) | ldg16(xp + 24) << 16;

        asm volatile("cp.async.wait_all;" ::: "memory");

#pragma unroll
        for (int m = 1; m < 32; m <<= 1) mx = fmaxf(mx, __shfl_xor_sync(~0u, mx, m));
        if (lane == 0) sts32f(sb + SM_RED + w * 4, mx);
        cbar();
        {
            const float4 u = lds128f(sb + SM_RED), v = lds128f(sb + SM_RED + 16);
            mx = fmaxf(fmaxf(fmaxf(u.x, u.y), fmaxf(u.z, u.w)), fmaxf(fmaxf(v.x, v.y), fmaxf(v.z, v.w)));
        }
        const uint32_t pa = sb + SM_P + (tid >> 3) * 256 + rank * 128 + (tid & 7) * 16;
        const uint4 s0 = lds128(pa);
        const float sc[8] = {bf_lo(s0.x), bf_hi(s0.x), bf_lo(s0.y), bf_hi(s0.y), bf_lo(s0.z), bf_hi(s0.z), bf_lo(s0.w), bf_hi(s0.w)};
        float l = 0.f;
#pragma unroll
        for (int i = 0; i < 8; i++) l += __expf(sc[i] - mx);
#pragma unroll
        for (int m = 1; m < 32; m <<= 1) l += __shfl_xor_sync(~0u, l, m);
        if (lane == 0) sts32f(sb + SM_RED + 32 + w * 4, l);
        cbar();
        {
            const float4 u = lds128f(sb + SM_RED + 32), v = lds128f(sb + SM_RED + 48);
            l = ((u.x + u.y) + (u.z + u.w)) + ((v.x + v.y) + (v.z + v.w));
        }
        if (tid == 0) st_async_v2(mapa(sb + SM_ML, rank ^ 1), mx, l, mapa(sb + BAR_XML, rank ^ 1));
        mbar_wait_cluster(sb + BAR_XML, 0);
        const float2 o = lds64f(sb + SM_ML);
        const float m = fmaxf(mx, o.x);
        const float inv = __fdividef(1.0f, l * __expf(mx - m) + o.y * __expf(o.x - m));
        const uint32_t p0 = pack2(__expf(sc[0] - m) * inv, __expf(sc[1] - m) * inv), p1 = pack2(__expf(sc[2] - m) * inv, __expf(sc[3] - m) * inv);
        const uint32_t p2 = pack2(__expf(sc[4] - m) * inv, __expf(sc[5] - m) * inv), p3 = pack2(__expf(sc[6] - m) * inv, __expf(sc[7] - m) * inv);
        st_async_v4(mapa(pa, rank ^ 1), p0, p1, p2, p3, mapa(sb + BAR_XP, rank ^ 1));
        sts128(pa, p0, p1, p2, p3);
        cbar();
        mbar_wait_cluster(sb + BAR_XP, 0);
    }

    for (uint32_t n = 0; n < SPIN_LIMIT && !__all_sync(~0u, pkt_ok(mga, tag) && pkt_ok(msb, tag) && pkt_ok(mcb, tag)); n++) {
        mga = ld_pkt2(tmp + 2 * 256); msb = ld_pkt2(tmp + 3 * 256); mcb = ld_pkt2(tmp + 4 * 256);
    }
    const uint32_t ga0 = lo32(mga.a), ga1 = lo32(mga.b), sb0 = lo32(msb.a), sb1 = lo32(msb.b);
    const uint32_t cb0 = hadd2(ONE2, lo32(mcb.a)), cb1 = hadd2(ONE2, lo32(mcb.b));
    u64 red_p = s_line(e1_blk(1, w), 2 * b) + lane * 4, red2_p = s_line(e1_blk(1, w), 4 + b) + lane * 4;

    PIN64(red_p); PIN64(red2_p);
    float oa[4][4];
#pragma unroll
    for (int i = 0; i < 4; i++) { oa[i][0] = oa[i][1] = oa[i][2] = oa[i][3] = 0.f; }
    {
        int stage = N_V % STAGES, phase = tile_phase(N_V);
        auto v_tiles = [&](int v0, int v1) {
#pragma unroll 1
            for (int v = v0; v < v1; v++) {
                const uint32_t tb = sb + SM_RING + stage * TILE_BYTES + grp * 8192 + (sw128 ^ (sub * 32));
                uint2 P[4];
#pragma unroll
                for (int i = 0; i < 4; i++) P[i] = lds64(sb + SM_P + v * 256 + grp * 128 + i * 32 + t * 8);
                mbar_wait(sb + BAR_FULL + 8 * stage, phase);
                uint32_t a[4][4];
#pragma unroll
                for (int i = 0; i < 4; i++) ldsm4t(tb + i * 2048, a[i]);
#pragma unroll
                for (int i = 0; i < 4; i++) mma4(oa[i], a[i], P[i].x, P[i].y);
                __syncwarp();
                if (lane == 0) mbar_arrive(sb + BAR_EMPTY + 8 * stage);
                if (++stage == STAGES) { stage = 0; phase ^= 1; }
            }
        };
        v_tiles(0, WO_AT);
#pragma unroll
        for (int i = 0; i < 4 * WO_EARLY; i++) {
            if ((i & 3) == 0) mbar_wait(sb + full_bar(N_WO + (i >> 2)), tile_phase(N_WO + (i >> 2)));
            ldsm4t(sb + slot_addr(N_WO + (i >> 2)) + w * 2048 + (sw128 ^ ((i & 3) * 32)), A[i]);
        }
        asm volatile("bar.sync 2, 288;" ::: "memory");
        if (tid < WO_EARLY) mbar_arrive_n(sb + BAR_EMPTY + 8 * ((N_WO + tid) % STAGES), 8);
        stage = N_V2 % STAGES; phase = tile_phase(N_V2);
        v_tiles(WO_AT, NT);
    }

    if (t < 2) sts32f(sb + SM_OP + w * 64 + (g >> 1) * 16 + (g & 1) * 4 + t * 8,
                      sel(t1, (oa[0][2] + oa[1][2]) + (oa[2][2] + oa[3][2]), (oa[0][0] + oa[1][0]) + (oa[2][0] + oa[3][0])));
    cbar();

    {
        float acc[4][4];
#pragma unroll
        for (int i = 0; i < 4; i++) { acc[i][0] = acc[i][1] = acc[i][2] = acc[i][3] = 0.f; }
        const float2 u = lds64f(sb + SM_OP + (lane & 15) * 16 + vb * 8), v = lds64f(sb + SM_OP + 256 + (lane & 15) * 16 + vb * 8);
        const uint32_t o2 = pack2(u.x + v.x, u.y + v.y);
#pragma unroll
        for (int s4 = 0; s4 < 4; s4++) {
            const uint32_t b0 = __shfl_sync(~0u, o2, 4 * s4 + t), b1 = __shfl_sync(~0u, o2, 16 + 4 * s4 + t);
            if (s4 >= WO_EARLY) {
                mbar_wait(sb + full_bar(N_V + NT + s4), tile_phase(N_V + NT + s4));
                if (s4 == 3) { }
#pragma unroll
                for (int i = 0; i < 4; i++) ldsm4t(sb + slot_addr(N_V + NT + s4) + w * 2048 + (sw128 ^ (i * 32)), A[4 * s4 + i]);
            }
#pragma unroll
            for (int i = 0; i < 4; i++) mma4(acc[i], A[4 * s4 + i], b0, b1);
        }
        const float r0 = sel(t2, sel(t1, 1.0f, acc[1][0]), sel(t1, acc[0][2], acc[0][0]));
        const float r1 = sel(t2, sel(t1, 1.0f, acc[3][0]), sel(t1, acc[2][2], acc[2][0]));
        const float r2 = sel(t2, 1.0f, sel(t1, acc[3][2], acc[1][2]));
        asm volatile("red.relaxed.gpu.global.add.f32 [%0], %2;\nred.relaxed.gpu.global.add.f32 [%0 + 256], %3;\nred.relaxed.gpu.global.add.f32 [%1], %4;"
                     :: "l"(red_p), "l"(red2_p), "f"(r0), "f"(r1), "f"(r2) : "memory");
        asm volatile("red.relaxed.gpu.global.add.f32 [%0], %2;\nred.relaxed.gpu.global.add.f32 [%0 + 256], %3;\nred.relaxed.gpu.global.add.f32 [%1], %4;"
                     :: "l"(red_p ^ 4096), "l"(red2_p ^ 4096), "f"(r0), "f"(r1), "f"(r2) : "memory");
    }

    constexpr uint32_t CNT = 0x42800000u;
    if (is_gu) {
        uint32_t side;
        asm volatile("ld.volatile.shared.u32 %0, [%1];" : "=r"(side) : "r"(sb + SM_SIDE) : "memory");
        u64 acc_p = (s_line(e1_blk(0, w), lane >> 3) + (lane & 7) * 16) ^ side, acc2_p = (s_line(e1_blk(0, w), 4 + ob) + (lane & 7) * 16) ^ side;
        const int eb = e1_blk(w >> 2, w & 3);
        const uint32_t near = (w >> 2) * 4096 == side;
        u64 out_p = s_line(eb, lane >> 3) + S_OUT + (lane & 7) * 16, out2_p = s_line(eb, 4 + ob) + S_OUT + (lane & 15) * 8;
        u64 gb_p = (s_line(e1_blk(0, w), 6 + ob) + (lane & 15) * 8) ^ side, y_p = (u64)(q_.out + t1 * D_ + 64 * w + 4 * t2 + g);
        PIN64(acc_p); PIN64(acc2_p); PIN64(out_p); PIN64(out2_p); PIN64(gb_p); PIN64(y_p);
        auto keep = [&](uint32_t x) { return __shfl_sync(~0u, x, lane); };
        const int src = keep(8 * (g & 2) + t), src1 = keep(src + 4), src2 = keep(src + 8), src3 = keep(src + 12);
        const uint32_t p_st = keep(sb + SM_PART + w * 512 + lane * 16), r_st = keep(sb + SM_RED + (vb * 8 + w) * 8);
        tx0 = keep(tx0); tx1 = keep(tx1);
        const uint32_t g1 = g & 1;
        uint32_t cp[8], cn[8];
        float acc[4][4];
#pragma unroll
        for (int i = 0; i < 8; i++) {
            cp[i] = __shfl_sync(~0u, (i & 1) ? cb1 : cb0, 4 * (i >> 1) + src);
            cn[i] = selu(g1, __shfl_sync(~0u, (i & 1) ? sb1 : sb0, 4 * (i >> 1) + src), cp[i]);
        }
        const int frow = (lane & 7) + (lane & 16);
        const uint32_t fa = sb + slot_addr(N_FFN) + grp * 2 * TILE_BYTES + (64 * sub + frow) * 64 + ((lch ^ ((frow >> 1) & 3)) << 4);
        mbar_wait(sb + BAR_FFN + 8 * (w * NQ >> 3), 0);
        uint4 u = ld_strong128(acc_p), v = ld_strong128(acc2_p);
#pragma unroll
        for (int i = 0; i < 16; i++) ldsm4t((fa ^ ((i & 1) * 32)) + (i >> 3) * 2048 + ((i >> 2) & 1) * 512 + ((i >> 1) & 1) * TILE_BYTES, A[i]);
#pragma unroll
        for (int i = 0; i < 4; i++) { acc[i][0] = acc[i][1] = acc[i][2] = acc[i][3] = 0.f; }
#pragma unroll
        for (int i = 0; i < 16; i++) mma4(acc[i & 3], A[i], cn[2 * (i >> 2)], cn[2 * (i >> 2) + 1]);
        sts128f(sb + SM_P + w * 1024 + lane * 16, sel(t2, acc[1][0], acc[0][0]), sel(t2, acc[3][0], acc[2][0]), sel(t2, acc[1][2], acc[0][2]), sel(t2, acc[3][2], acc[2][2]));
        sts128f(sb + SM_P + w * 1024 + 512 + lane * 16, sel(t2, acc[1][1], acc[0][1]), sel(t2, acc[3][1], acc[2][1]), sel(t2, acc[1][3], acc[0][3]), sel(t2, acc[3][3], acc[2][3]));
        bar_arrive<3>();
#pragma unroll
        for (int i = 0; i < 8; i++) cn[i] = selu(g1, cp[i] ^ 0x80008000u, 0u);
        settle(tag, sb + SM_OP, cn[0], cn[1], cn[2], cn[3]); settle(tag, sb + SM_OP, cn[4], cn[5], cn[6], cn[7]);
        for (uint32_t n = 0; !__all_sync(~0u, u.w == CNT && v.w == CNT) && n < SPIN_LIMIT; n++) { u = ld_strong128(acc_p); v = ld_strong128(acc2_p); }
        const uint32_t x0 = hadd2(tx0, hmul2(ga0, pack2(__uint_as_float(u.x), __uint_as_float(u.y))));
        const uint32_t x1 = hadd2(tx1, hmul2(ga1, pack2(__uint_as_float(u.z), __uint_as_float(selu(lane & 8, v.y, v.x)))));
        float c[4] = {0.f, 0.f, 0.f, 0.f};
        mma(c, x0, ONE2, x1, ONE2, x0, x1);
#pragma unroll
        for (int i = 0; i < 4; i++) { acc[i][0] = acc[i][1] = acc[i][2] = acc[i][3] = 0.f; }
        float q, s;
#pragma unroll
        for (int s4 = 0; s4 < 4; s4++) {
            const int from = s4 == 0 ? src : s4 == 1 ? src1 : s4 == 2 ? src2 : src3;
            uint32_t b0 = __shfl_sync(~0u, x0, from), b1 = __shfl_sync(~0u, x1, from);
            b0 = hfma2(b0, cp[2 * s4], hmul2(b0, cn[2 * s4]));
            b1 = hfma2(b1, cp[2 * s4 + 1], hmul2(b1, cn[2 * s4 + 1]));
#pragma unroll
            for (int i = 0; i < 4; i++) mma4(acc[i], A[4 * s4 + i], b0, b1);
            if (s4 == 0) { q = sel(g1, c[1], c[0]); s = c[2] + c[3]; q += __shfl_xor_sync(~0u, q, 4); s += __shfl_xor_sync(~0u, s, 9); }
            if (s4 == 1) q += __shfl_xor_sync(~0u, q, 9);
            if (s4 == ((OPT & 1) ? 1 : 2)) {
                if (lane == 0 || lane == 18) sts64f(r_st, s, fmaxf(fmaf(s * (-1.0f / 64), s, q), 0.f));
                if (OPT & 1) { bar_arrive<6>(); cut(tag); }
            }
        }
        sts128f(p_st, sel(t2, acc[1][0] + acc[1][1], acc[0][0] + acc[0][1]), sel(t2, acc[3][0] + acc[3][1], acc[2][0] + acc[2][1]),
                sel(t2, acc[1][2] + acc[1][3], acc[0][2] + acc[0][3]), sel(t2, acc[3][2] + acc[3][3], acc[2][2] + acc[2][3]));
        bar_arrive<4>();
        uint32_t xo[2];
#pragma unroll
        for (int j = 0; j < 2; j++) {
            const uint32_t e0 = __shfl_sync(~0u, x0, 16 * t1 + 8 * j + g), e1 = __shfl_sync(~0u, x1, 16 * t1 + 8 * j + g);
            xo[j] = __byte_perm(e0, e1, t2 ? 0x7632 : 0x5410);
        }
        mbar_wait(sb + BAR_W2, 0);
#pragma unroll
        for (int i = 0; i < 8; i++) ldsm4t(sb + slot_addr(N_FFN + 4) + w * 4096 + (i >> 2) * 2048 + (sw128 ^ ((i & 3) * 32)), A[i]);
#pragma unroll
        for (int i = 0; i < 4; i++) { acc[i][0] = acc[i][1] = acc[i][2] = acc[i][3] = 0.f; }
        bar_sync<5>();
        asm volatile("{\n.reg .pred p;\nsetp.ne.u32 p, %0, 0;\n@p bar.sync 7, 256;\n}" :: "r"(near) : "memory");
        const uint4 hv = lds128(sb + SM_Q + ((g & 2) * 2 + t) * 16);
#pragma unroll
        for (int i = 0; i < 4; i++) mma4(acc[i], A[i], hv.x, hv.y);
#pragma unroll
        for (int i = 0; i < 4; i++) mma4(acc[i], A[4 + i], hv.z, hv.w);
        float r[4], o[6];
#pragma unroll
        for (int i = 0; i < 4; i++) r[i] = sel(t2, acc[i][2], acc[i][0]);
        asm volatile("atom.relaxed.gpu.global.add.v4.f32 {%0, %1, %2, %3}, [%4], {%5, %6, %7, %8};"
                     : "=f"(o[0]), "=f"(o[1]), "=f"(o[2]), "=f"(o[4]) : "l"(out_p), "f"(r[0]), "f"(r[1]), "f"(r[2]), "f"(1.0f) : "memory");
        asm volatile("atom.relaxed.gpu.global.add.v2.f32 {%0, %1}, [%2], {%3, %4};"
                     : "=f"(o[3]), "=f"(o[5]) : "l"(out2_p), "f"(r[3]), "f"(1.0f) : "memory");
        asm volatile("{\n.reg .pred p;\nsetp.eq.u32 p, %0, 0;\n@p bar.arrive 7, 256;\n}" :: "r"(near) : "memory");
        uint2 gb = ld_strong64(gb_p);
        const uint32_t f0 = pack2(o[0] + r[0], o[1] + r[1]), f1 = pack2(o[2] + r[2], o[3] + r[3]);
#pragma unroll 1
        for (uint32_t n = 0; n < SPIN_LIMIT; n++) {
            const uint32_t y0 = hadd2(xo[0], hmul2(gb.x, f0)), y1 = hadd2(xo[1], hmul2(gb.y, f1));
            uint32_t late;
            asm volatile("{\n.reg .pred p, q, m;\n.reg .b16 a, b, c, d;\n"
                         "mov.b32 {a, b}, %6;\nmov.b32 {c, d}, %7;\nsetp.ne.b16 m, a, 0xffff;\nsetp.ne.and.b16 m, b, 0xffff, m;\nsetp.ne.and.b16 m, c, 0xffff, m;\nsetp.ne.and.b16 m, d, 0xffff, m;\n"
                         "setp.eq.and.f32 p, %4, 0f42280000, m;\nsetp.eq.and.f32 q, %5, 0f42280000, m;\n"
                         "mov.b32 {a, b}, %2;\nmov.b32 {c, d}, %3;\n"
                         "@p st.global.u16 [%1], a;\n@p st.global.u16 [%1 + 32], b;\n@p st.global.u16 [%1 + 64], c;\n@q st.global.u16 [%1 + 96], d;\n"
                         "vote.sync.all.pred m, m, 0xffffffff;\nselp.u32 %0, 0, 1, m;\n}"
                         : "=r"(late) : "l"(y_p), "r"(y0), "r"(y1), "f"(o[4]), "f"(o[5]), "r"(gb.x), "r"(gb.y) : "memory");
            if (!late) break;
            gb = ld_strong64(gb_p);
        }
    } else if (is_gb) {
        const uint32_t fa = sb + slot_addr(N_FFN) + grp * 8192 + (64 * sub + lrow) * 32 + ((lch ^ ((lrow >> 2) & 1)) << 4);
        const int dl = (lane & 7) * 4 + ((lane >> 3) & 1) * 2 + ob;
        u64 gb_p = s_line(2 * (role >> 2), 6 + (dl >> 4)) + (dl & 15) * 8 + (role & 3) * 2;
        PIN64(gb_p);
        uint32_t bs[8];
#pragma unroll
        for (int i = 0; i < 8; i++) bs[i] = __shfl_sync(~0u, (i & 1) ? sc1 : sc0, 4 * (i >> 1) + 16 * ((g >> 1) & 1) + t);
        const uint32_t c_st = sb + SM_PART + (w * 32 + t1 * 16 + (t >> 1) * 8 + g) * 4;
        settle(tag, sb + SM_OP, bs[0], bs[1], bs[2], bs[3]); settle(tag, sb + SM_OP, bs[4], bs[5], bs[6], bs[7]); settle(tag, sb + SM_OP, c_st, fa, 0, 0);
        mbar_wait(sb + BAR_FFN + 8 * grp, 0);
        float c[4][4];
#pragma unroll
        for (int s4 = 0; s4 < 4; s4++) ldsm4t(fa + s4 * 512, A[s4]);
#pragma unroll
        for (int s4 = 0; s4 < 4; s4++) { c[s4][0] = c[s4][1] = c[s4][2] = c[s4][3] = 0.f; mma4(c[s4], A[s4], bs[2 * s4], bs[2 * s4 + 1]); }
        sts32f(c_st, sel(t2, (c[0][2] + c[1][2]) + (c[2][2] + c[3][2]), (c[0][0] + c[1][0]) + (c[2][0] + c[3][0])));
        cbar();
        if (w == 0) {
            float u[8];
#pragma unroll
            for (int i = 0; i < 8; i++) u[i] = lds32f(sb + SM_PART + i * 128 + lane * 4);
            const uint16_t v = (uint16_t)pack2(((u[0] + u[1]) + (u[2] + u[3])) + ((u[4] + u[5]) + (u[6] + u[7])), 0.f);
            asm volatile("st.relaxed.gpu.global.u16 [%0], %1;\nst.relaxed.gpu.global.u16 [%0 + 4096], %1;" :: "l"(gb_p), "h"(v) : "memory");
        }
    }
}

typedef CUresult (*EncodeFn)(CUtensorMap*, CUtensorMapDataType, cuuint32_t, void*, const cuuint64_t*, const cuuint64_t*,
                             const cuuint32_t*, const cuuint32_t*, CUtensorMapInterleave, CUtensorMapSwizzle,
                             CUtensorMapL2promotion, CUtensorMapFloatOOBfill);

void make_map(EncodeFn enc, CUtensorMap* m, void* ptr, int cols, int rows, int box_cols, int box_rows, CUtensorMapSwizzle sw) {
    cuuint64_t gd[2] = {(cuuint64_t)cols, (cuuint64_t)rows}, gs[1] = {(cuuint64_t)cols * 2};
    cuuint32_t bd[2] = {(cuuint32_t)box_cols, (cuuint32_t)box_rows}, es[2] = {1, 1};
    enc(m, CU_TENSOR_MAP_DATA_TYPE_BFLOAT16, 2, ptr, gd, gs, bd, es, CU_TENSOR_MAP_INTERLEAVE_NONE, sw,
        CU_TENSOR_MAP_L2_PROMOTION_NONE, CU_TENSOR_MAP_FLOAT_OOB_FILL_NONE);
}

}

extern "C" void kernel_launch(void* const* d_in, const int* in_sizes, int n_in, void* d_out, int out_size) {
    (void)in_sizes; (void)n_in; (void)out_size;
    static EncodeFn enc = nullptr;
    if (!enc) {
        void* fn = nullptr;
        cudaDriverEntryPointQueryResult qr;
        cudaGetDriverEntryPoint("cuTensorMapEncodeTiled", &fn, cudaEnableDefault, &qr);
        enc = (EncodeFn)fn;
        cudaFuncSetAttribute(fused_decode_kernel, cudaFuncAttributeMaxDynamicSharedMemorySize, SMEM_BYTES);
    }
    Params p;
    Ptrs q;
    make_map(enc, &p.m_wmod, d_in[10], MODW, D_, 32, 256, CU_TENSOR_MAP_SWIZZLE_64B);
    make_map(enc, &p.m_wq, d_in[3], QD, D_, 64, 128, CU_TENSOR_MAP_SWIZZLE_128B);
    make_map(enc, &p.m_v, d_in[2], DH, 64 * SK, 64, 128, CU_TENSOR_MAP_SWIZZLE_128B);
    {
        cuuint64_t gd[3] = {64, QD, 8}, gs[2] = {D_ * 2, 128};
        cuuint32_t bd[3] = {64, 16, 8}, es[3] = {1, 1, 1};
        enc(&p.m_wo, CU_TENSOR_MAP_DATA_TYPE_BFLOAT16, 3, d_in[4], gd, gs, bd, es, CU_TENSOR_MAP_INTERLEAVE_NONE,
            CU_TENSOR_MAP_SWIZZLE_128B, CU_TENSOR_MAP_L2_PROMOTION_NONE, CU_TENSOR_MAP_FLOAT_OOB_FILL_NONE);
    }
    for (int i = 0; i < 2; i++) {
        cuuint64_t gd[4] = {FF, 2, 8, D_ / 16}, gs[3] = {8 * FF * 2, FF * 2, 16 * FF * 2};
        cuuint32_t bd[4] = {32, 2, 8, 32 / NQ}, es[4] = {1, 1, 1, 1};
        enc(i ? &p.m_w3 : &p.m_w1, CU_TENSOR_MAP_DATA_TYPE_BFLOAT16, 4, d_in[6 + i], gd, gs, bd, es, CU_TENSOR_MAP_INTERLEAVE_NONE,
            CU_TENSOR_MAP_SWIZZLE_64B, CU_TENSOR_MAP_L2_PROMOTION_NONE, CU_TENSOR_MAP_FLOAT_OOB_FILL_NONE);
    }
    {
        cuuint64_t gd[5] = {64, 2, 8, FF / 16, 8}, gs[4] = {8 * D_ * 2, D_ * 2, 16 * D_ * 2, 128};
        cuuint32_t bd[5] = {64, 2, 8, 2, 8}, es[5] = {1, 1, 1, 1, 1};
        enc(&p.m_w2, CU_TENSOR_MAP_DATA_TYPE_BFLOAT16, 5, d_in[8], gd, gs, bd, es, CU_TENSOR_MAP_INTERLEAVE_NONE,
            CU_TENSOR_MAP_SWIZZLE_128B, CU_TENSOR_MAP_L2_PROMOTION_NONE, CU_TENSOR_MAP_FLOAT_OOB_FILL_NONE);
    }
    make_map(enc, &p.m_gb, d_in[10], MODW, D_, 16, 256, CU_TENSOR_MAP_SWIZZLE_32B);
    q.x = (const __nv_bfloat16*)d_in[0];
    q.kwin = (const __nv_bfloat16*)d_in[1] + (size_t)(SK - WIN) * DH;
    q.c = (const __nv_bfloat16*)d_in[9];
    q.out = (__nv_bfloat16*)d_out;
    fused_decode_kernel<<<NCTA, THREADS, SMEM_BYTES, cudaStreamPerThread>>>(q, p);
}
```

```cpp
#include <cuda_runtime.h>
#include <cuda.h>
#include <cuda_bf16.h>
#include <stdint.h>

namespace {

constexpr int D_ = 512, DH = 128, SK = 16384, WIN = 4096, FF = 1376, QD = 4096, MODW = 3072;
constexpr int NCTA = 128;
constexpr int TILE_BYTES = 16384;
constexpr int NT = 32;
constexpr int STAGES = 13;
constexpr int K_FIRST = 2;
constexpr int FIRST_N = 5;
constexpr int WO_AT = 20;
constexpr int WO_EARLY = 3;
constexpr int PACE = 656;
constexpr int LEAD_NS = 1350;
constexpr int GATE_X = 23;
constexpr int POLL_NS = 300;
constexpr int ALPHA16 = 4;
constexpr int GU_NS = 5075;
constexpr int W2_NS = 6240;
constexpr int GB_LEAD = 390;
constexpr int NQ = 8;
constexpr int PROBES = 6;
constexpr int PROBE_NS = 1000;
constexpr int EARLY_NS = 800;
constexpr int NW = 4;
constexpr int HEAD_TID = 256;
constexpr int N_WMOD = 0, N_WQ = 2, N_K = 6, N_V = N_K + NT, N_WO = N_V + WO_AT, N_V2 = N_WO + WO_EARLY, N_WO2 = N_V + NT + WO_EARLY, N_FFN = N_V + NT + 4;
constexpr int N_GATE = N_V + GATE_X + WO_EARLY;
constexpr int THREADS = 320;
constexpr int N_MOD_CTA = 80;
#define SPIN_LIMIT_S "4194304"
constexpr unsigned SPIN_LIMIT = 1u << 22;

constexpr int SM_RING = 0;
constexpr int SM_P = STAGES * TILE_BYTES;
constexpr int SM_PART = SM_P + WIN * 2;
constexpr int SM_OP = SM_PART + 8192;
constexpr int SM_Q = SM_OP + 2048;
constexpr int SM_RED = SM_Q + 256;
constexpr int SM_ML = SM_RED + 128;
constexpr int SM_PROG = SM_ML + 16;
constexpr int SM_SIDE = SM_PROG + 16;
constexpr int SM_BAR = SM_SIDE + 16;
constexpr int BAR_FULL = SM_BAR, BAR_EMPTY = SM_BAR + 8 * STAGES, BAR_XQ = SM_BAR + 16 * STAGES,
              BAR_XML = BAR_XQ + 8, BAR_XP = BAR_XQ + 16, BAR_FFN = BAR_XQ + 24;
constexpr int BAR_W2 = BAR_FFN + 8 * NQ;
constexpr int SMEM_BYTES = BAR_W2 + 8 * NW;
static_assert(SMEM_BYTES <= 232448, "shared memory");
__host__ __device__ constexpr uint32_t slot_addr(int n) { return SM_RING + (n % STAGES) * TILE_BYTES; }
__host__ __device__ constexpr uint32_t full_bar(int n) { return BAR_FULL + 8 * (n % STAGES); }
__host__ __device__ constexpr uint32_t empty_bar(int n) { return BAR_EMPTY + 8 * (n % STAGES); }
__host__ __device__ constexpr uint32_t tile_phase(int n) { return (n / STAGES) & 1; }
static_assert((N_FFN + 4) % STAGES + 2 <= STAGES && N_FFN % STAGES + 4 <= STAGES, "w1/w3 tiles and w2 tiles occupy consecutive slots");
static_assert(GATE_X >= WO_AT && N_GATE - STAGES < N_V2 && N_FFN + 5 - 2 * STAGES < N_WO && N_FFN + 5 - STAGES < N_WO2,
              "barrier parities the helper warp waits on are unambiguous after the rendezvous; the last wo tiles are not replaced");
__host__ __device__ constexpr int fill_tile(int j) { return j < K_FIRST ? N_K + j : j < K_FIRST + N_K ? j - K_FIRST : j; }

struct Ptrs {
    const __nv_bfloat16 *kwin, *x, *c;
    __nv_bfloat16* out;
};
struct Params {
    CUtensorMap m_wmod, m_wq, m_v, m_wo, m_w1, m_w3, m_w2, m_gb;
};

__device__ unsigned g_epoch;
__device__ __align__(128) uint2 g_mod[2][5 * D_ / 2];
__device__ __align__(256) unsigned char g_s[131072];
__device__ __forceinline__ unsigned long long s_line(int blk, int i) {
    return (((unsigned long long)g_s + 65535) & ~65535ull) + blk * 4096 + (i >> 1) * 1024 + (i & 1) * 256;
}
__device__ __forceinline__ int e1_blk(int r, int w) { return 2 * w + (r ^ (w & 1)); }
constexpr int S_OUT = 512, S_PROG = 128;
__device__ __align__(128) unsigned g_clear;

typedef unsigned long long u64;
__device__ __forceinline__ unsigned time_ns() {
    unsigned r;
    asm volatile("mov.u32 %0, %%globaltimer_lo;" : "=r"(r));
    return r;
}
__device__ __forceinline__ bool elect_one() {
    uint32_t r;
    asm volatile("{\n.reg .pred p;\nelect.sync _|p, 0xffffffff;\nselp.u32 %0, 1, 0, p;\n}" : "=r"(r));
    return r != 0;
}
#define PIN64(v) asm volatile("" : "+l"(v))

__device__ __forceinline__ void mbar_init(uint32_t bar, uint32_t cnt) {
    asm volatile("mbarrier.init.shared::cta.b64 [%0], %1;" :: "r"(bar), "r"(cnt) : "memory");
}
__device__ __forceinline__ void mbar_expect_tx(uint32_t bar, uint32_t bytes) {
    asm volatile("mbarrier.arrive.expect_tx.shared::cta.b64 _, [%0], %1;" :: "r"(bar), "r"(bytes) : "memory");
}
__device__ __forceinline__ void mbar_arrive(uint32_t bar) {
    asm volatile("mbarrier.arrive.shared::cta.b64 _, [%0];" :: "r"(bar) : "memory");
}
__device__ __forceinline__ void mbar_arrive_n(uint32_t bar, uint32_t n) {
    asm volatile("mbarrier.arrive.shared::cta.b64 _, [%0], %1;" :: "r"(bar), "r"(n) : "memory");
}
__device__ __forceinline__ void mbar_wait(uint32_t bar, uint32_t parity) {
    asm volatile("{\n.reg .pred p;\n.reg .u32 n;\nmov.u32 n, 0;\nW0:\n"
                 "mbarrier.try_wait.parity.shared::cta.b64 p, [%0], %1;\n@p bra W1;\n"
                 "add.u32 n, n, 1;\nsetp.lt.u32 p, n, " SPIN_LIMIT_S ";\n@p bra W0;\nW1:\n}"
                 :: "r"(bar), "r"(parity) : "memory");
}
__device__ __forceinline__ void mbar_wait_cluster(uint32_t bar, uint32_t parity) {
    asm volatile("{\n.reg .pred p;\n.reg .u32 n;\nmov.u32 n, 0;\nW0:\n"
                 "mbarrier.try_wait.parity.acquire.cluster.shared::cta.b64 p, [%0], %1;\n@p bra W1;\n"
                 "add.u32 n, n, 1;\nsetp.lt.u32 p, n, " SPIN_LIMIT_S ";\n@p bra W0;\nW1:\n}"
                 :: "r"(bar), "r"(parity) : "memory");
}
__device__ __forceinline__ void bulk_load(uint32_t dst, const void* src, uint32_t bytes, uint32_t bar, uint64_t pol) {
    asm volatile("cp.async.bulk.shared::cluster.global.mbarrier::complete_tx::bytes.L2::cache_hint [%0], [%1], %2, [%3], %4;"
                 :: "r"(dst), "l"(src), "r"(bytes), "r"(bar), "l"(pol) : "memory");
}
__device__ __forceinline__ void tma2d(uint32_t dst, const CUtensorMap* m, int c0, int c1, uint32_t bar) {
    asm volatile("cp.async.bulk.tensor.2d.shared::cluster.global.mbarrier::complete_tx::bytes [%0], [%1, {%3, %4}], [%2];"
                 :: "r"(dst), "l"(m), "r"(bar), "r"(c0), "r"(c1) : "memory");
}
__device__ __forceinline__ void tma2d_hint(uint32_t dst, const CUtensorMap* m, int c0, int c1, uint32_t bar, uint64_t pol) {
    asm volatile("cp.async.bulk.tensor.2d.shared::cluster.global.mbarrier::complete_tx::bytes.L2::cache_hint [%0], [%1, {%3, %4}], [%2], %5;"
                 :: "r"(dst), "l"(m), "r"(bar), "r"(c0), "r"(c1), "l"(pol) : "memory");
}
__device__ __forceinline__ void tma3d(uint32_t dst, const CUtensorMap* m, int c0, int c1, int c2, uint32_t bar) {
    asm volatile("cp.async.bulk.tensor.3d.shared::cluster.global.mbarrier::complete_tx::bytes [%0], [%1, {%3, %4, %5}], [%2];"
                 :: "r"(dst), "l"(m), "r"(bar), "r"(c0), "r"(c1), "r"(c2) : "memory");
}
__device__ __forceinline__ void tma4d(uint32_t dst, const CUtensorMap* m, int c0, int c3, uint32_t bar) {
    asm volatile("cp.async.bulk.tensor.4d.shared::cluster.global.mbarrier::complete_tx::bytes [%0], [%1, {%3, %5, %5, %4}], [%2];"
                 :: "r"(dst), "l"(m), "r"(bar), "r"(c0), "r"(c3), "r"(0) : "memory");
}
__device__ __forceinline__ void tma5d(uint32_t dst, const CUtensorMap* m, int c3, int c4, uint32_t bar) {
    asm volatile("cp.async.bulk.tensor.5d.shared::cluster.global.mbarrier::complete_tx::bytes [%0], [%1, {%5, %5, %5, %3, %4}], [%2];"
                 :: "r"(dst), "l"(m), "r"(bar), "r"(c3), "r"(c4), "r"(0) : "memory");
}
__device__ __forceinline__ uint32_t mapa(uint32_t addr, uint32_t rank) {
    uint32_t r;
    asm("mapa.shared::cluster.u32 %0, %1, %2;" : "=r"(r) : "r"(addr), "r"(rank));
    return r;
}
__device__ __forceinline__ void st_async_b32(uint32_t addr, uint32_t v, uint32_t bar) {
    asm volatile("st.async.weak.shared::cluster.mbarrier::complete_tx::bytes.b32 [%0], %1, [%2];" :: "r"(addr), "r"(v), "r"(bar) : "memory");
}
__device__ __forceinline__ void st_async_v2(uint32_t addr, float a, float b, uint32_t bar) {
    asm volatile("st.async.weak.shared::cluster.mbarrier::complete_tx::bytes.v2.f32 [%0], {%1, %2}, [%3];" :: "r"(addr), "f"(a), "f"(b), "r"(bar) : "memory");
}
__device__ __forceinline__ void st_async_v4(uint32_t addr, uint32_t a, uint32_t b, uint32_t c, uint32_t d, uint32_t bar) {
    asm volatile("st.async.weak.shared::cluster.mbarrier::complete_tx::bytes.v4.b32 [%0], {%1, %2, %3, %4}, [%5];"
                 :: "r"(addr), "r"(a), "r"(b), "r"(c), "r"(d), "r"(bar) : "memory");
}
template <int ID> __device__ __forceinline__ void bar_sync() { asm volatile("bar.sync %0, 288;" :: "n"(ID) : "memory"); }
template <int ID> __device__ __forceinline__ void bar_arrive() { asm volatile("bar.arrive %0, 288;" :: "n"(ID) : "memory"); }
__device__ __forceinline__ void cbar() { asm volatile("bar.sync 1, 256;" ::: "memory"); }

__device__ __forceinline__ uint4 ldg128(const void* p) {
    uint4 v;
    asm volatile("ld.global.nc.v4.u32 {%0,%1,%2,%3}, [%4];" : "=r"(v.x), "=r"(v.y), "=r"(v.z), "=r"(v.w) : "l"(p));
    return v;
}
__device__ __forceinline__ uint32_t ldg16(const void* p) {
    uint16_t v;
    asm volatile("ld.global.nc.u16 %0, [%1];" : "=h"(v) : "l"(p));
    return v;
}
__device__ __forceinline__ uint4 ld_strong128(unsigned long long p) {
    uint4 v;
    asm volatile("ld.relaxed.gpu.global.v4.b32 {%0,%1,%2,%3}, [%4];" : "=r"(v.x), "=r"(v.y), "=r"(v.z), "=r"(v.w) : "l"(p) : "memory");
    return v;
}
__device__ __forceinline__ uint2 ld_strong64(unsigned long long p) {
    uint2 v;
    asm volatile("ld.relaxed.gpu.global.v2.b32 {%0,%1}, [%2];" : "=r"(v.x), "=r"(v.y) : "l"(p) : "memory");
    return v;
}
__device__ __forceinline__ uint32_t ldg32(const void* p) {
    uint32_t v;
    asm volatile("ld.global.nc.u32 %0, [%1];" : "=r"(v) : "l"(p));
    return v;
}
struct Pkt2 { u64 a, b; };
__device__ __forceinline__ uint32_t lo32(u64 v) { return (uint32_t)v; }
__device__ __forceinline__ uint32_t hi32(u64 v) { return (uint32_t)(v >> 32); }
__device__ __forceinline__ Pkt2 ld_pkt2(const void* p) {
    Pkt2 r;
    asm volatile("ld.relaxed.gpu.global.v2.b64 {%0,%1}, [%2];" : "=l"(r.a), "=l"(r.b) : "l"(p) : "memory");
    return r;
}
__device__ __forceinline__ bool pkt_ok(const Pkt2& r, uint32_t tag) { return hi32(r.a) == tag && hi32(r.b) == tag; }
__device__ __forceinline__ void st_pkt(u64 p, uint32_t data, uint32_t tag) {
    asm volatile("{\n.reg .b64 v;\nmov.b64 v, {%1, %2};\nst.relaxed.gpu.global.b64 [%0], v;\n}" :: "l"(p), "r"(data), "r"(tag) : "memory");
}
__device__ __forceinline__ uint4 lds128(uint32_t a) {
    uint4 v;
    asm volatile("ld.shared.v4.u32 {%0,%1,%2,%3}, [%4];" : "=r"(v.x), "=r"(v.y), "=r"(v.z), "=r"(v.w) : "r"(a) : "memory");
    return v;
}
__device__ __forceinline__ float4 lds128f(uint32_t a) {
    float4 v;
    asm volatile("ld.shared.v4.f32 {%0,%1,%2,%3}, [%4];" : "=f"(v.x), "=f"(v.y), "=f"(v.z), "=f"(v.w) : "r"(a) : "memory");
    return v;
}
__device__ __forceinline__ uint2 lds64(uint32_t a) {
    uint2 v;
    asm volatile("ld.shared.v2.u32 {%0,%1}, [%2];" : "=r"(v.x), "=r"(v.y) : "r"(a) : "memory");
    return v;
}
__device__ __forceinline__ float2 lds64f(uint32_t a) {
    float2 v;
    asm volatile("ld.shared.v2.f32 {%0,%1}, [%2];" : "=f"(v.x), "=f"(v.y) : "r"(a) : "memory");
    return v;
}
__device__ __forceinline__ float lds32f(uint32_t a) {
    float v;
    asm volatile("ld.shared.f32 %0, [%1];" : "=f"(v) : "r"(a) : "memory");
    return v;
}
__device__ __forceinline__ void sts64f(uint32_t a, float x, float y) {
    asm volatile("st.shared.v2.f32 [%0], {%1,%2};" :: "r"(a), "f"(x), "f"(y) : "memory");
}
__device__ __forceinline__ void sts128f(uint32_t a, float x, float y, float z, float w) {
    asm volatile("st.shared.v4.f32 [%0], {%1,%2,%3,%4};" :: "r"(a), "f"(x), "f"(y), "f"(z), "f"(w) : "memory");
}
__device__ __forceinline__ void sts32f(uint32_t a, float x) {
    asm volatile("st.shared.f32 [%0], %1;" :: "r"(a), "f"(x) : "memory");
}
__device__ __forceinline__ void sts128(uint32_t a, uint32_t x, uint32_t y, uint32_t z, uint32_t w) {
    asm volatile("st.shared.v4.u32 [%0], {%1,%2,%3,%4};" :: "r"(a), "r"(x), "r"(y), "r"(z), "r"(w) : "memory");
}
__device__ __forceinline__ void settle(uint32_t tag, uint32_t a, uint32_t x, uint32_t y, uint32_t z, uint32_t w) {
    asm volatile("{\n.reg .pred p;\nsetp.eq.u32 p, %0, 0;\n@p st.shared.v4.u32 [%1], {%2,%3,%4,%5};\n}" :: "r"(tag), "r"(a), "r"(x), "r"(y), "r"(z), "r"(w) : "memory");
}
__device__ __forceinline__ void settle(uint32_t tag, uint32_t a, const float4& v) {
    settle(tag, a, __float_as_uint(v.x), __float_as_uint(v.y), __float_as_uint(v.z), __float_as_uint(v.w));
}
__device__ __forceinline__ void sts16(uint32_t a, uint32_t x) {
    asm volatile("st.shared.u16 [%0], %1;" :: "r"(a), "h"((uint16_t)x) : "memory");
}
__device__ __forceinline__ void ldsm4t(uint32_t a, uint32_t (&r)[4]) {
    asm volatile("ldmatrix.sync.aligned.m8n8.x4.trans.shared.b16 {%0,%1,%2,%3}, [%4];"
                 : "=r"(r[0]), "=r"(r[1]), "=r"(r[2]), "=r"(r[3]) : "r"(a) : "memory");
}
__device__ __forceinline__ void mma(float (&c)[4], uint32_t a0, uint32_t a1, uint32_t a2, uint32_t a3, uint32_t b0, uint32_t b1) {
    asm volatile("mma.sync.aligned.m16n8k16.row.col.f32.bf16.bf16.f32 {%0,%1,%2,%3}, {%4,%5,%6,%7}, {%8,%9}, {%0,%1,%2,%3};"
                 : "+f"(c[0]), "+f"(c[1]), "+f"(c[2]), "+f"(c[3]) : "r"(a0), "r"(a1), "r"(a2), "r"(a3), "r"(b0), "r"(b1));
}
__device__ __forceinline__ void mma4(float (&c)[4], const uint32_t (&a)[4], uint32_t b0, uint32_t b1) { mma(c, a[0], a[1], a[2], a[3], b0, b1); }
__device__ __forceinline__ float sel(uint32_t c, float a, float b) {
    float r;
    asm("{\n.reg .pred p;\nsetp.ne.u32 p, %3, 0;\nselp.f32 %0, %1, %2, p;\n}" : "=f"(r) : "f"(a), "f"(b), "r"(c));
    return r;
}
__device__ __forceinline__ float bf_lo(uint32_t v) { return __uint_as_float(v << 16); }
__device__ __forceinline__ float bf_hi(uint32_t v) { return __uint_as_float(v & 0xffff0000u); }
__device__ __forceinline__ uint32_t pack2(float lo, float hi) {
    uint32_t r;
    asm("cvt.rn.bf16x2.f32 %0, %1, %2;" : "=r"(r) : "f"(hi), "f"(lo));
    return r;
}
__device__ __forceinline__ float rbf(float x) { return __uint_as_float(pack2(0.f, x)); }
__device__ __forceinline__ uint32_t hadd2(uint32_t a, uint32_t b) { uint32_t r; asm("add.rn.bf16x2 %0, %1, %2;" : "=r"(r) : "r"(a), "r"(b)); return r; }
__device__ __forceinline__ uint32_t hsub2(uint32_t a, uint32_t b) { uint32_t r; asm("sub.rn.bf16x2 %0, %1, %2;" : "=r"(r) : "r"(a), "r"(b)); return r; }
__device__ __forceinline__ uint32_t hmul2(uint32_t a, uint32_t b) { uint32_t r; asm("mul.rn.bf16x2 %0, %1, %2;" : "=r"(r) : "r"(a), "r"(b)); return r; }
__device__ __forceinline__ uint32_t hfma2(uint32_t a, uint32_t b, uint32_t c) { uint32_t r; asm("fma.rn.bf16x2 %0, %1, %2, %3;" : "=r"(r) : "r"(a), "r"(b), "r"(c)); return r; }
__device__ __forceinline__ uint32_t selu(uint32_t c, uint32_t a, uint32_t b) { return __float_as_uint(sel(c, __uint_as_float(a), __uint_as_float(b))); }
constexpr uint32_t ONE2 = 0x3f803f80u;
__device__ __forceinline__ float silu_f(float x) {
    float e, r;
    asm("ex2.approx.ftz.f32 %0, %1;" : "=f"(e) : "f"(x * -1.4426950408889634f));
    asm("rcp.approx.ftz.f32 %0, %1;" : "=f"(r) : "f"(1.0f + e));
    return x * r;
}
__device__ __forceinline__ float rcp_sd(float m2) {
    float s, r;
    asm("sqrt.approx.ftz.f32 %0, %1;" : "=f"(s) : "f"(rbf(rbf(m2 * (1.0f / D_)) + 1e-5f)));
    asm("rcp.approx.ftz.f32 %0, %1;" : "=f"(r) : "f"(rbf(s)));
    return r;
}
__device__ __forceinline__ uint32_t ln_mod2(uint32_t x, uint32_t mean2, float rsd, uint32_t c1, uint32_t sh) {
    const uint32_t d = hsub2(x, mean2);
    return hadd2(hmul2(pack2(bf_lo(d) * rsd, bf_hi(d) * rsd), c1), sh);
}
__device__ __forceinline__ int pair_pos(int j) { return 2 * (j & 3) + (j >> 2); }

__global__ void __cluster_dims__(2, 1, 1) __launch_bounds__(THREADS, 1)
fused_decode_kernel(const __grid_constant__ Ptrs q_, const __grid_constant__ Params p) {
    extern __shared__ __align__(1024) unsigned char smem[];
    unsigned t_top;
    asm volatile("mov.u32 %0, %%globaltimer_lo;" : "=r"(t_top));
    const int tid = threadIdx.x;
    uint32_t z0;
    asm("and.b32 %0, %1, 1024;" : "=r"(z0) : "r"(tid));
    const char* kw = *(const char* const*)((const char*)&q_.kwin + z0);
    const uint32_t sb = (uint32_t)__cvta_generic_to_shared(smem);
    auto place = [](int cl) { return cl < 4 ? 8 * cl + 39 : cl - 4 + max((cl * 37 - 36 * 37) >> 8, 0); };
    uint32_t z2;
    asm("and.b32 %0, %1, 2048;" : "=r"(z2) : "r"(tid));
    const int cv = blockIdx.x + z2, pw = place(cv >> 1);
    static_assert(SK * DH * 2 == 1 << 22 && TILE_BYTES == 1 << 14, "koff");
    const char* kp;
    auto set_kp = [&](uint32_t off) {
        asm volatile("{\n.reg .u32 lo, hi;\nmov.b64 {lo, hi}, %1;\nadd.cc.u32 lo, lo, %2;\naddc.u32 hi, hi, 0;\nmov.b64 %0, {lo, hi};\n}"
                     : "=l"(kp) : "l"(kw), "r"(off));
    };
    uint64_t pol;
    asm("createpolicy.fractional.L2::evict_first.b64 %0, 1.0;" : "=l"(pol));
    auto fill_k = [&](int n) {
        mbar_expect_tx(sb + full_bar(n), TILE_BYTES);
        bulk_load(sb + slot_addr(n), kp + (n - N_K) * 2 * TILE_BYTES, TILE_BYTES, sb + full_bar(n), pol);
    };
    static_assert(K_FIRST >= 1, "head block starts with K tile 0");
    if (tid + (sb >> 28) == HEAD_TID) {
        mbar_init(sb + full_bar(N_K), 1);
        set_kp(((pw & 7) << 22) | ((pw & 8) << 24) | ((pw & 48) << 21) | ((cv & 1) << 14));
        bulk_load(sb + slot_addr(N_K), kp, TILE_BYTES, sb + full_bar(N_K), pol);
        mbar_expect_tx(sb + full_bar(N_K), TILE_BYTES);
#pragma unroll
        for (int j = 1; j < K_FIRST; j++) { mbar_init(sb + full_bar(N_K + j), 1); fill_k(N_K + j); }
    }
    __syncwarp();
    const int cta = blockIdx.x, rank = cta & 1, pv = place(cta >> 1);
    const int b = (pv >> 3) & 1, h = (pv & 7) | ((pv >> 1) & 24), bh = 32 * b + h;
    auto first_fill = [&](int j) {
        const int n = fill_tile(j);
        if (n >= N_K) {
            fill_k(n);
        } else if (n >= N_WQ) {
            mbar_expect_tx(sb + full_bar(n), TILE_BYTES);
            tma2d(sb + slot_addr(n), &p.m_wq, h * DH + 64 * rank, 128 * (n - N_WQ), sb + full_bar(n));
        } else if (cta < N_MOD_CTA) {
            mbar_expect_tx(sb + full_bar(n), TILE_BYTES);
            tma2d(sb + slot_addr(n), &p.m_wmod, 32 * cta, 256 * n, sb + full_bar(n));
        } else {
            mbar_arrive(sb + full_bar(n));
        }
    };
    if (tid == HEAD_TID) {
#pragma unroll
        for (int j = K_FIRST; j < FIRST_N; j++) mbar_init(sb + full_bar(fill_tile(j)), 1);
#pragma unroll
        for (int j = K_FIRST; j < FIRST_N; j++) first_fill(j);
        asm volatile("fence.mbarrier_init.release.cluster;" ::: "memory");
    }
    __syncwarp();
    const int role = cta / 3;
    const bool is_gu = cta == 3 * role, is_gb = cta == 3 * role + 1 && role < 32;
    if (tid >= 288) {
        const unsigned t_start = t_top;
        asm volatile("barrier.cluster.arrive.relaxed.aligned;" ::: "memory");
        unsigned tag;
        asm volatile("ld.relaxed.gpu.global.u32 %0, [%1];" : "=r"(tag) : "l"(&g_epoch) : "memory");
        tag += 1;
        if (cta == NCTA - 1) {
#pragma unroll 2
            for (int i = tid - 288; i < 128 * 8; i += 32) {
                uint4* q = reinterpret_cast<uint4*>(s_line(i >> 6, (i >> 3) & 7)) + (i & 7);
                const uint32_t v = (i & 48) == 48 ? ~0u : 0u;
                q[0] = make_uint4(v, v, v, v);
                q[8] = q[32] = q[40] = make_uint4(0u, 0u, 0u, 0u);
            }
            __syncwarp();
            asm volatile("fence.acq_rel.gpu;" ::: "memory");
            if (tid == 288) asm volatile("st.relaxed.gpu.global.u32 [%0], %1;" :: "l"(&g_clear), "r"(tag) : "memory");
        }
        asm volatile("barrier.cluster.wait.acquire.aligned;" ::: "memory");
        mbar_wait_cluster(sb + BAR_XQ, 0);
        for (uint32_t n = 0; n < SPIN_LIMIT; n++) {
            unsigned c;
            asm volatile("ld.relaxed.gpu.global.u32 %0, [%1];" : "=r"(c) : "l"(&g_clear) : "memory");
            if (c == tag) break;
        }
        asm volatile("fence.acq_rel.gpu;" ::: "memory");
        asm volatile("st.volatile.shared.u32 [%0], %1;" :: "r"(sb + SM_SIDE), "r"(0) : "memory");
        asm volatile("bar.sync 2, 288;" ::: "memory");
        if (elect_one()) {
            asm volatile("prefetch.tensormap [%0];" :: "l"(is_gu ? &p.m_w1 : &p.m_gb) : "memory");
            asm volatile("prefetch.tensormap [%0];" :: "l"(&p.m_w3) : "memory");
            asm volatile("prefetch.tensormap [%0];" :: "l"(&p.m_w2) : "memory");
            const int issue = ((4 * N_GATE - 11 - 2 * WO_EARLY) * PACE >> 2) - LEAD_NS;
            unsigned now, c = 0, best[2] = {~0u, ~0u}, np = is_gu ? 0 : PROBES;
            auto probe = [&]() {
                const int k = np >> 1, i = (role >> 3) + 2 * k;
                const u64 a = (s_line(e1_blk(0, role & 7), i < 6 ? i : i - 6) + (k ? 512 * k - 384 : 0)) ^ ((np & 1) << 12);
                unsigned v, c0, c1 = 0;
                asm volatile("mov.u32 %0, %%clock;" : "=r"(c0));
                asm volatile("ld.relaxed.gpu.global.u32 %0, [%1];" : "=r"(v) : "l"(a) : "memory");
                asm volatile("{\n.reg .pred p;\nsetp.ne.u32 p, %1, 0xffffffff;\n@p mov.u32 %0, %%clock;\n}" : "+r"(c1) : "r"(v));
                if (np & 1) best[1] = min(best[1], c1 - c0); else best[0] = min(best[0], c1 - c0);
                np++;
                if (!(np & 1)) asm volatile("st.volatile.shared.u32 [%0], %1;" :: "r"(sb + SM_SIDE), "r"(best[0] <= best[1] ? 0 : 4096) : "memory");
            };
#pragma unroll 1
            while (np < PROBES) {
                now = time_ns();
                if ((int)(now - t_start) >= issue + EARLY_NS) break;
                probe();
            }
            mbar_wait(sb + full_bar(N_GATE), tile_phase(N_GATE));
            now = time_ns();
            const unsigned mine = (1u << 24) + min(now - t_start, 100000u);
            const u64 prog = s_line(0, 7) + S_PROG;
            asm volatile("red.relaxed.gpu.global.add.u32 [%0], %1;" :: "l"(prog), "r"(mine) : "memory");
            if (is_gu || is_gb) {
#pragma unroll
                for (int i = 0; i < 6; i++) mbar_wait(sb + empty_bar(N_FFN + i), tile_phase(N_FFN + i) ^ 1);
#pragma unroll
                for (int i = 0; i < NQ; i++) mbar_expect_tx(sb + BAR_FFN + 8 * i, is_gu ? 65536 / NQ : 8192);
#pragma unroll
                for (int i = 0; i < NW; i++) mbar_expect_tx(sb + BAR_W2 + 8 * i, 32768 / NW);
                unsigned due = 0, next = now;
                constexpr unsigned full = (unsigned)NCTA << 24;
                asm volatile("st.volatile.shared.u32 [%0], %1;" :: "r"(sb + SM_PROG), "r"(mine) : "memory");
#pragma unroll 1
                for (uint32_t n = 0; n < 4096; n++) {
                    unsigned v;
                    asm volatile("ld.volatile.shared.u32 %0, [%1];" : "=r"(v) : "r"(sb + SM_PROG) : "memory");
                    if (v > c) {
                        c = v;
                        const int arr = (int)__fdividef((float)(c & 0xffffffu), (float)(c >> 24));
                        due = arr - ((arr - issue) * ALPHA16 >> 4) + (is_gb ? W2_NS - GB_LEAD : GU_NS);
                    }
                    now = time_ns();
                    if (now - t_start + PROBE_NS >= due) np = PROBES;
                    if ((c >= full && np == PROBES) || now - t_start >= due) break;
                    if ((int)(now - next) >= 0 && c < full) {
                        asm volatile("cp.async.cg.shared.global [%0], [%1], 16;" :: "r"(sb + SM_PROG), "l"(prog) : "memory");
                        next = now + POLL_NS;
                    }
                    if (np < PROBES) probe();
                }
#pragma unroll 1
                for (uint32_t n = 0; n < 1024 && now - t_start < due; n++) now = time_ns();
                if (is_gu) {
#pragma unroll
                    for (int i = 0; i < 2 * NQ; i++) {
                        const int q = i >> 1, r0 = q * (512 / NQ);
                        tma4d(sb + slot_addr(N_FFN) + (r0 >> 8) * 2 * TILE_BYTES + (i & 1) * TILE_BYTES + (r0 & 255) * 64, (i & 1) ? &p.m_w3 : &p.m_w1, 32 * role, r0 / 16, sb + BAR_FFN + 8 * q);
                    }
#pragma unroll 1
                    for (uint32_t n = 0; n < 1024 && now - t_start < due + (W2_NS - GU_NS); n++) now = time_ns();
                    const int f = best[0] <= best[1] ? NW / 2 : 0;
#pragma unroll
                    for (int i = 0; i < NW; i++) tma5d(sb + slot_addr(N_FFN + 4) + (i ^ f) * (32768 / NW), &p.m_w2, 2 * role, (i ^ f) * (8 / NW), sb + BAR_W2 + 8 * (i ^ f));
                } else {
                    tma2d(sb + slot_addr(N_FFN), &p.m_gb, 5 * D_ + 16 * role, 0, sb + BAR_FFN);
                    tma2d(sb + slot_addr(N_FFN) + 8192, &p.m_gb, 5 * D_ + 16 * role, 256, sb + BAR_FFN + 8);
                }
                asm volatile("cp.async.wait_all;" ::: "memory");
            }
        }
        __syncwarp();
        if (is_gu) {
            const int lane = tid & 31;
            auto sum8 = [&](uint32_t a, int stride) {
                float4 u[8];
#pragma unroll
                for (int i = 0; i < 8; i++) u[i] = lds128f(a + i * stride);
                return make_float4(((u[0].x + u[1].x) + (u[2].x + u[3].x)) + ((u[4].x + u[5].x) + (u[6].x + u[7].x)),
                                   ((u[0].y + u[1].y) + (u[2].y + u[3].y)) + ((u[4].y + u[5].y) + (u[6].y + u[7].y)),
                                   ((u[0].z + u[1].z) + (u[2].z + u[3].z)) + ((u[4].z + u[5].z) + (u[6].z + u[7].z)),
                                   ((u[0].w + u[1].w) + (u[2].w + u[3].w)) + ((u[4].w + u[5].w) + (u[6].w + u[7].w)));
            };
            uint32_t h_st = sb + SM_Q + (((lane & 1) * 4 + ((lane >> 2) & 3)) * 4 + (lane & 2) + (lane >> 4)) * 4;
            bar_sync<3>();
            const float4 C = sum8(sb + SM_P + lane * 16, 1024), S = sum8(sb + SM_P + 512 + lane * 16, 1024);
            const uint32_t st_ld = sb + SM_RED + (lane & 1) * 64;
            settle(tag, sb + SM_OP, C); settle(tag, sb + SM_OP, S); settle(tag, sb + SM_OP, h_st, st_ld, 0, 0);
            bar_sync<4>();
            const float4 r0 = lds128f(st_ld), r1 = lds128f(st_ld + 16), r2 = lds128f(st_ld + 32), r3 = lds128f(st_ld + 48);
            const float4 Y = sum8(sb + SM_PART + lane * 16, 512);
            const float e1 = r0.z - r0.x, e2 = r1.x - r0.x, e3 = r1.z - r0.x, e4 = r2.x - r0.x, e5 = r2.z - r0.x, e6 = r3.x - r0.x, e7 = r3.z - r0.x;
            const float se = ((e1 + e2) + (e3 + e4)) + ((e5 + e6) + e7);
            const float ee = (fmaf(e1, e1, e2 * e2) + fmaf(e3, e3, e4 * e4)) + fmaf(e5, e5, fmaf(e6, e6, e7 * e7));
            const float sq = ((r0.y + r0.w) + (r1.y + r1.w)) + ((r2.y + r2.w) + (r3.y + r3.w));
            const float rsd = rcp_sd(fmaf(se * (-1.0f / D_), se, fmaf(ee, 1.0f / 64, sq))), mu = -rbf(fmaf(r0.x, 8.0f, se) * (1.0f / D_));
            const uint32_t gr = pack2(fmaf(rsd, fmaf(mu, C.x, Y.x), S.x), fmaf(rsd, fmaf(mu, C.z, Y.z), S.z));
            const uint32_t ur = pack2(fmaf(rsd, fmaf(mu, C.y, Y.y), S.y), fmaf(rsd, fmaf(mu, C.w, Y.w), S.w));
            const uint32_t hv = hmul2(pack2(silu_f(bf_lo(gr)), silu_f(bf_hi(gr))), ur);
            sts32f(h_st, __uint_as_float(hv));
            bar_arrive<5>();
            if (cta == 0 && lane == 0) g_epoch = tag;
        }
        return;
    }
    if (tid >= 256) {
        set_kp(bh * (SK * DH * 2) + rank * TILE_BYTES);
        const unsigned t_start = t_top;
        auto pace = [&](int q4) {
            const int due = (q4 * PACE >> 2) - LEAD_NS;
            unsigned now, n = 0;
            do { now = time_ns(); } while ((int)(now - t_start) < due && ++n < 256);
        };
        if (tid == 256) {
#pragma unroll
            for (int j = FIRST_N; j < STAGES; j++) mbar_init(sb + full_bar(fill_tile(j)), 1);
#pragma unroll
            for (int s = 0; s < STAGES; s++) mbar_init(sb + BAR_EMPTY + 8 * s, 8);
            mbar_init(sb + BAR_XQ, 1); mbar_init(sb + BAR_XML, 1); mbar_init(sb + BAR_XP, 1);
#pragma unroll
            for (int i = 0; i < NQ + NW; i++) mbar_init(sb + BAR_FFN + 8 * i, 1);
            mbar_expect_tx(sb + BAR_XQ, 256); mbar_expect_tx(sb + BAR_XML, 8); mbar_expect_tx(sb + BAR_XP, WIN);
            asm volatile("fence.mbarrier_init.release.cluster;" ::: "memory");
            asm volatile("fence.proxy.async.shared::cta;" ::: "memory");
        }
        __syncwarp();
        asm volatile("barrier.cluster.arrive.relaxed.aligned;" ::: "memory");
        if (elect_one()) {
#pragma unroll
            for (int j = FIRST_N; j < STAGES; j++) {
                pace(j <= K_FIRST ? 4 * j : j <= K_FIRST + 2 ? 4 * K_FIRST + 5 * (j - K_FIRST) / 2 :
                     j <= K_FIRST + 6 ? 4 * K_FIRST + 5 + 2 * (j - K_FIRST - 2) : 4 * j - 11);
                first_fill(j);
            }
        }
        __syncwarp();
        asm volatile("barrier.cluster.wait.acquire.aligned;" ::: "memory");
        if (elect_one()) {
            asm volatile("prefetch.tensormap [%0];" :: "l"(&p.m_v) : "memory");
            asm volatile("prefetch.tensormap [%0];" :: "l"(&p.m_wo) : "memory");
            int s = 0, ph = 0;
#pragma unroll 1
            for (int n = STAGES; n < N_FFN; n++) {
                const uint32_t dst = sb + SM_RING + s * TILE_BYTES, bar = sb + BAR_FULL + 8 * s;
                mbar_wait(sb + BAR_EMPTY + 8 * s, ph);
                mbar_expect_tx(bar, TILE_BYTES);
                pace(n < N_WO ? 4 * n - 11 : n < N_V2 ? 2 * (N_WO + n) - 11 : n < N_WO2 ? 4 * n - 11 - 2 * WO_EARLY : 2 * (N_WO2 + n - WO_EARLY) - 11);
                if (n < N_V) bulk_load(dst, kp + (n - N_K) * 2 * TILE_BYTES, TILE_BYTES, bar, pol);
                else if (n >= N_WO2 || (n >= N_WO && n < N_V2)) tma3d(dst, &p.m_wo, 0, h * DH + 64 * rank + 16 * (n - (n < N_V2 ? N_WO : N_V + NT)), 0, bar);
                else tma2d_hint(dst, &p.m_v, 64 * rank, bh * SK + (SK - WIN) + 128 * (n - (n < N_WO ? N_V : N_V + WO_EARLY)), bar, pol);
                if (++s == STAGES) { s = 0; ph ^= 1; }
            }
        }
        return;
    }

    const unsigned t_c = t_top;
    const int lane = tid & 31, w = tid >> 5, g = lane >> 2, t = lane & 3;
    const int hgrp = 4 * w + (g & 3);
    const int vb = g >> 2;
    const uint32_t cv0 = ldg32(q_.c + vb * D_ + 16 * hgrp + 2 * t), cv1 = ldg32(q_.c + vb * D_ + 16 * hgrp + 8 + 2 * t);
    unsigned tag;
    asm volatile("ld.relaxed.gpu.global.u32 %0, [%1];" : "=r"(tag) : "l"(&g_epoch) : "memory");
    const uint4 xa = ldg128(q_.x + b * D_ + 16 * lane), xb = ldg128(q_.x + b * D_ + 16 * lane + 8);
    const uint32_t xh0 = ldg32(q_.x + b * D_ + 16 * hgrp + 2 * t), xh1 = ldg32(q_.x + b * D_ + 16 * hgrp + 8 + 2 * t);
    asm volatile("barrier.cluster.arrive.relaxed.aligned;" ::: "memory");
#pragma unroll 1
    for (uint32_t n = t_c; n < 2; n++) asm volatile("nanosleep.u32 1;" ::: "memory");
    const int grp = w >> 2, sub = w & 3;
    const int lrow = (lane & 7) + 8 * (lane >> 4);
    const int lch = (lane >> 3) & 1;
    const int ob = lane >> 4;
    const uint32_t t1 = t & 1, t2 = t & 2;
    const int gsrc = 16 * (g & 1) + t;
    const uint32_t sw128 = lrow * 128 + ((lch ^ (lrow & 7)) << 4);
    uint32_t A[16][4];

    const uint32_t sc0 = pack2(silu_f(bf_lo(cv0)), silu_f(bf_hi(cv0))), sc1 = pack2(silu_f(bf_lo(cv1)), silu_f(bf_hi(cv1)));
    tag += 1;
    asm volatile("barrier.cluster.wait.acquire.aligned;" ::: "memory");
    mbar_wait(sb + BAR_FULL + 8 * (N_WMOD + grp), 0);
    if (cta < N_MOD_CTA) {
        const uint32_t tb = sb + SM_RING + (N_WMOD + grp) * TILE_BYTES + (64 * sub + lrow) * 64;
#pragma unroll
        for (int i = 0; i < 8; i++)
            ldsm4t(tb + (i >> 1) * 1024 + (((2 * (i & 1) + lch) ^ ((lrow >> 1) & 3)) << 4), A[i]);
        float acc[2][4] = {{0.f, 0.f, 0.f, 0.f}, {0.f, 0.f, 0.f, 0.f}};
#pragma unroll
        for (int s = 0; s < 4; s++) {
            const uint32_t b0 = __shfl_sync(~0u, sc0, 4 * s + gsrc), b1 = __shfl_sync(~0u, sc1, 4 * s + gsrc);
            mma4(acc[0], A[2 * s], b0, b1);
            mma4(acc[1], A[2 * s + 1], b0, b1);
        }
        sts32f(sb + SM_P + (w * 64 + 8 * t + g) * 4, sel(t2, sel(t1, acc[1][2], acc[1][0]), sel(t1, acc[0][2], acc[0][0])));
        sts32f(sb + SM_P + (w * 64 + 32 + 8 * t + g) * 4, sel(t2, sel(t1, acc[1][3], acc[1][1]), sel(t1, acc[0][3], acc[0][1])));
        cbar();
        if (w == 0) {
            const bool adj = cta < 32;
            const uint32_t a0 = sb + SM_P + (adj ? 2 * lane : ob * 32 + (lane & 1) * 16 + ((lane >> 1) & 7)) * 4, a1 = a0 + (adj ? 4 : 32);
            float2 sum = make_float2(0.f, 0.f);
#pragma unroll
            for (int i = 0; i < 8; i++) { sum.x += lds32f(a0 + i * 256); sum.y += lds32f(a1 + i * 256); }
            st_pkt((u64)&g_mod[ob][16 * cta + (adj ? (lane & 8) + pair_pos(lane & 7) : lane & 15)], pack2(sum.x, sum.y), tag);
        }
    }
    __syncwarp();
    if (lane == 0) mbar_arrive_n(sb + BAR_EMPTY + 8 * (N_WMOD + grp), 2);

    {
        const uint2* mp = &g_mod[b][vb * 256 + 8 * hgrp + 2 * t];
        const uint32_t ms = sb + SM_PART + tid * 16;
        auto fetch_mod = [&](uint32_t k) {
            asm volatile("cp.async.cg.shared.global [%0], [%1], 16;\ncp.async.commit_group;" :: "r"(ms + k), "l"(mp) : "memory");
        };
        fetch_mod(0);
        float xs[16] = {bf_lo(xa.x), bf_hi(xa.x), bf_lo(xa.y), bf_hi(xa.y), bf_lo(xa.z), bf_hi(xa.z), bf_lo(xa.w), bf_hi(xa.w),
                        bf_lo(xb.x), bf_hi(xb.x), bf_lo(xb.y), bf_hi(xb.y), bf_lo(xb.z), bf_hi(xb.z), bf_lo(xb.w), bf_hi(xb.w)};
        float s = 0.f;
#pragma unroll
        for (int i = 0; i < 16; i++) s += xs[i];
#pragma unroll
        for (int m = 1; m < 32; m <<= 1) s += __shfl_xor_sync(~0u, s, m);
        const float mean = s * (1.0f / D_);
        float q = 0.f;
#pragma unroll
        for (int i = 0; i < 16; i++) q += (xs[i] - mean) * (xs[i] - mean);
#pragma unroll
        for (int m = 1; m < 32; m <<= 1) q += __shfl_xor_sync(~0u, q, m);
        const uint32_t mean2 = pack2(mean, mean);
        const float rsd = rcp_sd(q);

        mbar_wait(sb + BAR_FULL + 8 * (N_WQ + (w >> 1)), 0);
        const uint32_t tb = sb + SM_RING + (N_WQ + (w >> 1)) * TILE_BYTES + (w & 1) * 8192;
#pragma unroll
        for (int i = 0; i < 16; i++) ldsm4t(tb + (i >> 2) * 2048 + (sw128 ^ ((i & 3) * 32)), A[i]);
        __syncwarp();
        if (lane == 0) mbar_arrive_n(sb + BAR_EMPTY + 8 * (N_WQ + (w >> 1)), 4);

        Pkt2 m;
        for (uint32_t n = 0, k = 0; n < SPIN_LIMIT; n++) {
            fetch_mod(k ^ 4096);
            asm volatile("cp.async.wait_group 1;" ::: "memory");
            const uint4 u = lds128(ms + k);
            m.a = u.x | (u64)u.y << 32; m.b = u.z | (u64)u.w << 32;
            if (__all_sync(~0u, pkt_ok(m, tag))) break;
            k ^= 4096;
        }
        const uint32_t ca0 = __shfl_xor_sync(~0u, lo32(m.a), 16), ca1 = __shfl_xor_sync(~0u, lo32(m.b), 16);
        const uint32_t v0 = ln_mod2(xh0, mean2, rsd, hadd2(ONE2, ca0), lo32(m.a));
        const uint32_t v1 = ln_mod2(xh1, mean2, rsd, hadd2(ONE2, ca1), lo32(m.b));
        float acc[4][4];
#pragma unroll
        for (int i = 0; i < 4; i++) { acc[i][0] = acc[i][1] = acc[i][2] = acc[i][3] = 0.f; }
#pragma unroll
        for (int s4 = 0; s4 < 4; s4++) {
            const uint32_t b0 = __shfl_sync(~0u, v0, 4 * s4 + t), b1 = __shfl_sync(~0u, v1, 4 * s4 + t);
#pragma unroll
            for (int i = 0; i < 4; i++) mma4(acc[i], A[4 * s4 + i], b0, b1);
        }
        sts32f(sb + SM_OP + (w * 64 + 16 * t + g) * 4, sel(t2, sel(t1, acc[3][0], acc[2][0]), sel(t1, acc[1][0], acc[0][0])));
        sts32f(sb + SM_OP + (w * 64 + 16 * t + 8 + g) * 4, sel(t2, sel(t1, acc[3][2], acc[2][2]), sel(t1, acc[1][2], acc[0][2])));
        cbar();
        if (w == 0) {
            float2 sum = make_float2(0.f, 0.f);
#pragma unroll
            for (int i = 0; i < 8; i++) { const float2 u = lds64f(sb + SM_OP + (i * 64 + 2 * lane) * 4); sum.x += u.x; sum.y += u.y; }
            const uint32_t v = pack2(sum.x, sum.y), a = sb + SM_Q + rank * 128 + lane * 4;
            st_async_b32(mapa(a, rank ^ 1), v, mapa(sb + BAR_XQ, rank ^ 1));
            st_async_b32(mapa(a, rank), v, mapa(sb + BAR_XQ, rank));
        }
        mbar_wait_cluster(sb + BAR_XQ, 0);
    }

    Pkt2 mga, msb, mcb;
    uint32_t tx0, tx1;
    const uint2* tmp = &g_mod[ob][32 * w + 2 * (lane & 15)];
    {
        uint4 Q[4];
        uint32_t koff[4];
#pragma unroll
        for (int i = 0; i < 4; i++) {
            const int ch = t + 4 * (i ^ (g & 1));
            Q[i] = lds128(sb + SM_Q + ch * 16);
            koff[i] = (sub * 16 + g) * 256 + ch * 16;
        }
        float mx = -INFINITY;
        int stage = N_K + grp, phase = 0;
#pragma unroll 1
        for (int it = 0; it < NT / 2; it++) {
            const uint32_t tb = sb + SM_RING + stage * TILE_BYTES;
            mbar_wait(sb + BAR_FULL + 8 * stage, phase);
            uint4 Ka[4], Kb[4];
#pragma unroll
            for (int i = 0; i < 4; i++) { Ka[i] = lds128(tb + koff[i]); Kb[i] = lds128(tb + koff[i] + 2048); }
            float c0[4] = {0.f, 0.f, 0.f, 0.f}, c1[4] = {0.f, 0.f, 0.f, 0.f};
#pragma unroll
            for (int i = 0; i < 4; i++) {
                mma(c0, Ka[i].x, Kb[i].x, Ka[i].y, Kb[i].y, Q[i].x, Q[i].y);
                mma(c1, Ka[i].z, Kb[i].z, Ka[i].w, Kb[i].w, Q[i].z, Q[i].w);
            }
            __syncwarp();
            if (lane == 0) mbar_arrive_n(sb + BAR_EMPTY + 8 * stage, 2);
            const float lo = (g & 1) ? c0[1] + c1[1] : c0[0] + c1[0];
            const float hi = (g & 1) ? c0[3] + c1[3] : c0[2] + c1[2];
            const float sc = rbf(rbf(t1 ? hi : lo) * 0.08838834764831845f);
            mx = fmaxf(mx, sc);
            if (t < 2) sts16(sb + SM_P + ((2 * it + grp) * 128 + rank * 64 + sub * 16 + 4 * (g >> 1) + 2 * t + (g & 1)) * 2, __float_as_uint(sc) >> 16);
            stage += 2;
            if (stage >= STAGES) { stage -= STAGES; phase ^= 1; }
        }

        mga = ld_pkt2(tmp + 2 * 256); msb = ld_pkt2(tmp + 3 * 256); mcb = ld_pkt2(tmp + 4 * 256);
        const __nv_bfloat16* xp = q_.x + ob * D_ + 64 * w + 4 * (lane & 8) + (lane & 7);
        tx0 = ldg16(xp) | ldg16(xp + 8) << 16;
        tx1 = ldg16(xp + 16) | ldg16(xp + 24) << 16;

        asm volatile("cp.async.wait_all;" ::: "memory");

#pragma unroll
        for (int m = 1; m < 32; m <<= 1) mx = fmaxf(mx, __shfl_xor_sync(~0u, mx, m));
        if (lane == 0) sts32f(sb + SM_RED + w * 4, mx);
        cbar();
        {
            const float4 u = lds128f(sb + SM_RED), v = lds128f(sb + SM_RED + 16);
            mx = fmaxf(fmaxf(fmaxf(u.x, u.y), fmaxf(u.z, u.w)), fmaxf(fmaxf(v.x, v.y), fmaxf(v.z, v.w)));
        }
        const uint32_t pa = sb + SM_P + (tid >> 3) * 256 + rank * 128 + (tid & 7) * 16;
        const uint4 s0 = lds128(pa);
        const float sc[8] = {bf_lo(s0.x), bf_hi(s0.x), bf_lo(s0.y), bf_hi(s0.y), bf_lo(s0.z), bf_hi(s0.z), bf_lo(s0.w), bf_hi(s0.w)};
        float l = 0.f;
#pragma unroll
        for (int i = 0; i < 8; i++) l += __expf(sc[i] - mx);
#pragma unroll
        for (int m = 1; m < 32; m <<= 1) l += __shfl_xor_sync(~0u, l, m);
        if (lane == 0) sts32f(sb + SM_RED + 32 + w * 4, l);
        cbar();
        {
            const float4 u = lds128f(sb + SM_RED + 32), v = lds128f(sb + SM_RED + 48);
            l = ((u.x + u.y) + (u.z + u.w)) + ((v.x + v.y) + (v.z + v.w));
        }
        if (tid == 0) st_async_v2(mapa(sb + SM_ML, rank ^ 1), mx, l, mapa(sb + BAR_XML, rank ^ 1));
        mbar_wait_cluster(sb + BAR_XML, 0);
        const float2 o = lds64f(sb + SM_ML);
        const float m = fmaxf(mx, o.x);
        const float inv = __fdividef(1.0f, l * __expf(mx - m) + o.y * __expf(o.x - m));
        const uint32_t p0 = pack2(__expf(sc[0] - m) * inv, __expf(sc[1] - m) * inv), p1 = pack2(__expf(sc[2] - m) * inv, __expf(sc[3] - m) * inv);
        const uint32_t p2 = pack2(__expf(sc[4] - m) * inv, __expf(sc[5] - m) * inv), p3 = pack2(__expf(sc[6] - m) * inv, __expf(sc[7] - m) * inv);
        st_async_v4(mapa(pa, rank ^ 1), p0, p1, p2, p3, mapa(sb + BAR_XP, rank ^ 1));
        sts128(pa, p0, p1, p2, p3);
        cbar();
        mbar_wait_cluster(sb + BAR_XP, 0);
    }

    for (uint32_t n = 0; n < SPIN_LIMIT && !__all_sync(~0u, pkt_ok(mga, tag) && pkt_ok(msb, tag) && pkt_ok(mcb, tag)); n++) {
        mga = ld_pkt2(tmp + 2 * 256); msb = ld_pkt2(tmp + 3 * 256); mcb = ld_pkt2(tmp + 4 * 256);
    }
    const uint32_t ga0 = lo32(mga.a), ga1 = lo32(mga.b), sb0 = lo32(msb.a), sb1 = lo32(msb.b);
    const uint32_t cb0 = hadd2(ONE2, lo32(mcb.a)), cb1 = hadd2(ONE2, lo32(mcb.b));
    u64 red_p = s_line(e1_blk(1, w), 2 * b) + lane * 4, red2_p = s_line(e1_blk(1, w), 4 + b) + lane * 4;

    PIN64(red_p); PIN64(red2_p);
    float oa[4][4];
#pragma unroll
    for (int i = 0; i < 4; i++) { oa[i][0] = oa[i][1] = oa[i][2] = oa[i][3] = 0.f; }
    {
        int stage = N_V % STAGES, phase = tile_phase(N_V);
        auto v_tiles = [&](int v0, int v1) {
#pragma unroll 1
            for (int v = v0; v < v1; v++) {
                const uint32_t tb = sb + SM_RING + stage * TILE_BYTES + grp * 8192 + (sw128 ^ (sub * 32));
                uint2 P[4];
#pragma unroll
                for (int i = 0; i < 4; i++) P[i] = lds64(sb + SM_P + v * 256 + grp * 128 + i * 32 + t * 8);
                mbar_wait(sb + BAR_FULL + 8 * stage, phase);
                uint32_t a[4][4];
#pragma unroll
                for (int i = 0; i < 4; i++) ldsm4t(tb + i * 2048, a[i]);
#pragma unroll
                for (int i = 0; i < 4; i++) mma4(oa[i], a[i], P[i].x, P[i].y);
                __syncwarp();
                if (lane == 0) mbar_arrive(sb + BAR_EMPTY + 8 * stage);
                if (++stage == STAGES) { stage = 0; phase ^= 1; }
            }
        };
        v_tiles(0, WO_AT);
#pragma unroll
        for (int i = 0; i < 4 * WO_EARLY; i++) {
            if ((i & 3) == 0) mbar_wait(sb + full_bar(N_WO + (i >> 2)), tile_phase(N_WO + (i >> 2)));
            ldsm4t(sb + slot_addr(N_WO + (i >> 2)) + w * 2048 + (sw128 ^ ((i & 3) * 32)), A[i]);
        }
        asm volatile("bar.sync 2, 288;" ::: "memory");
        if (tid < WO_EARLY) mbar_arrive_n(sb + BAR_EMPTY + 8 * ((N_WO + tid) % STAGES), 8);
        stage = N_V2 % STAGES; phase = tile_phase(N_V2);
        v_tiles(WO_AT, NT);
    }

    if (t < 2) sts32f(sb + SM_OP + w * 64 + (g >> 1) * 16 + (g & 1) * 4 + t * 8,
                      sel(t1, (oa[0][2] + oa[1][2]) + (oa[2][2] + oa[3][2]), (oa[0][0] + oa[1][0]) + (oa[2][0] + oa[3][0])));
    cbar();

    {
        float acc[4][4];
#pragma unroll
        for (int i = 0; i < 4; i++) { acc[i][0] = acc[i][1] = acc[i][2] = acc[i][3] = 0.f; }
        const float2 u = lds64f(sb + SM_OP + (lane & 15) * 16 + vb * 8), v = lds64f(sb + SM_OP + 256 + (lane & 15) * 16 + vb * 8);
        const uint32_t o2 = pack2(u.x + v.x, u.y + v.y);
#pragma unroll
        for (int s4 = 0; s4 < 4; s4++) {
            const uint32_t b0 = __shfl_sync(~0u, o2, 4 * s4 + t), b1 = __shfl_sync(~0u, o2, 16 + 4 * s4 + t);
            if (s4 >= WO_EARLY) {
                mbar_wait(sb + full_bar(N_V + NT + s4), tile_phase(N_V + NT + s4));
                if (s4 == 3) { }
#pragma unroll
                for (int i = 0; i < 4; i++) ldsm4t(sb + slot_addr(N_V + NT + s4) + w * 2048 + (sw128 ^ (i * 32)), A[4 * s4 + i]);
            }
#pragma unroll
            for (int i = 0; i < 4; i++) mma4(acc[i], A[4 * s4 + i], b0, b1);
        }
        const float r0 = sel(t2, sel(t1, 1.0f, acc[1][0]), sel(t1, acc[0][2], acc[0][0]));
        const float r1 = sel(t2, sel(t1, 1.0f, acc[3][0]), sel(t1, acc[2][2], acc[2][0]));
        const float r2 = sel(t2, 1.0f, sel(t1, acc[3][2], acc[1][2]));
        asm volatile("red.relaxed.gpu.global.add.f32 [%0], %2;\nred.relaxed.gpu.global.add.f32 [%0 + 256], %3;\nred.relaxed.gpu.global.add.f32 [%1], %4;"
                     :: "l"(red_p), "l"(red2_p), "f"(r0), "f"(r1), "f"(r2) : "memory");
        asm volatile("red.relaxed.gpu.global.add.f32 [%0], %2;\nred.relaxed.gpu.global.add.f32 [%0 + 256], %3;\nred.relaxed.gpu.global.add.f32 [%1], %4;"
                     :: "l"(red_p ^ 4096), "l"(red2_p ^ 4096), "f"(r0), "f"(r1), "f"(r2) : "memory");
    }

    constexpr uint32_t CNT = 0x42800000u;
    if (is_gu) {
        uint32_t side;
        asm volatile("ld.volatile.shared.u32 %0, [%1];" : "=r"(side) : "r"(sb + SM_SIDE) : "memory");
        u64 acc_p = (s_line(e1_blk(0, w), lane >> 3) + (lane & 7) * 16) ^ side, acc2_p = (s_line(e1_blk(0, w), 4 + ob) + (lane & 7) * 16) ^ side;
        const int eb = e1_blk(w >> 2, w & 3);
        const uint32_t near = (w >> 2) * 4096 == side;
        u64 out_p = s_line(eb, lane >> 3) + S_OUT + (lane & 7) * 16, out2_p = s_line(eb, 4 + ob) + S_OUT + (lane & 15) * 8;
        u64 gb_p = (s_line(e1_blk(0, w), 6 + ob) + (lane & 15) * 8) ^ side, y_p = (u64)(q_.out + t1 * D_ + 64 * w + 4 * t2 + g);
        PIN64(acc_p); PIN64(acc2_p); PIN64(out_p); PIN64(out2_p); PIN64(gb_p); PIN64(y_p);
        auto keep = [&](uint32_t x) { return __shfl_sync(~0u, x, lane); };
        const int src = keep(8 * (g & 2) + t), src1 = keep(src + 4), src2 = keep(src + 8), src3 = keep(src + 12);
        const uint32_t p_st = keep(sb + SM_PART + w * 512 + lane * 16), r_st = keep(sb + SM_RED + (vb * 8 + w) * 8);
        tx0 = keep(tx0); tx1 = keep(tx1);
        const uint32_t g1 = g & 1;
        uint32_t cp[8], cn[8];
        float acc[4][4];
#pragma unroll
        for (int i = 0; i < 8; i++) {
            cp[i] = __shfl_sync(~0u, (i & 1) ? cb1 : cb0, 4 * (i >> 1) + src);
            cn[i] = selu(g1, __shfl_sync(~0u, (i & 1) ? sb1 : sb0, 4 * (i >> 1) + src), cp[i]);
        }
        const int frow = (lane & 7) + (lane & 16);
        const uint32_t fa = sb + slot_addr(N_FFN) + grp * 2 * TILE_BYTES + (64 * sub + frow) * 64 + ((lch ^ ((frow >> 1) & 3)) << 4);
        mbar_wait(sb + BAR_FFN + 8 * (w * NQ >> 3), 0);
        uint4 u = ld_strong128(acc_p), v = ld_strong128(acc2_p);
#pragma unroll
        for (int i = 0; i < 16; i++) ldsm4t((fa ^ ((i & 1) * 32)) + (i >> 3) * 2048 + ((i >> 2) & 1) * 512 + ((i >> 1) & 1) * TILE_BYTES, A[i]);
#pragma unroll
        for (int i = 0; i < 4; i++) { acc[i][0] = acc[i][1] = acc[i][2] = acc[i][3] = 0.f; }
#pragma unroll
        for (int i = 0; i < 16; i++) mma4(acc[i & 3], A[i], cn[2 * (i >> 2)], cn[2 * (i >> 2) + 1]);
        sts128f(sb + SM_P + w * 1024 + lane * 16, sel(t2, acc[1][0], acc[0][0]), sel(t2, acc[3][0], acc[2][0]), sel(t2, acc[1][2], acc[0][2]), sel(t2, acc[3][2], acc[2][2]));
        sts128f(sb + SM_P + w * 1024 + 512 + lane * 16, sel(t2, acc[1][1], acc[0][1]), sel(t2, acc[3][1], acc[2][1]), sel(t2, acc[1][3], acc[0][3]), sel(t2, acc[3][3], acc[2][3]));
        bar_arrive<3>();
#pragma unroll
        for (int i = 0; i < 8; i++) cn[i] = selu(g1, cp[i] ^ 0x80008000u, 0u);
        settle(tag, sb + SM_OP, cn[0], cn[1], cn[2], cn[3]); settle(tag, sb + SM_OP, cn[4], cn[5], cn[6], cn[7]);
        for (uint32_t n = 0; !__all_sync(~0u, u.w == CNT && v.w == CNT) && n < SPIN_LIMIT; n++) { u = ld_strong128(acc_p); v = ld_strong128(acc2_p); }
        const uint32_t x0 = hadd2(tx0, hmul2(ga0, pack2(__uint_as_float(u.x), __uint_as_float(u.y))));
        const uint32_t x1 = hadd2(tx1, hmul2(ga1, pack2(__uint_as_float(u.z), __uint_as_float(selu(lane & 8, v.y, v.x)))));
        float c[4] = {0.f, 0.f, 0.f, 0.f};
        mma(c, x0, ONE2, x1, ONE2, x0, x1);
#pragma unroll
        for (int i = 0; i < 4; i++) { acc[i][0] = acc[i][1] = acc[i][2] = acc[i][3] = 0.f; }
        float q, s;
#pragma unroll
        for (int s4 = 0; s4 < 4; s4++) {
            const int from = s4 == 0 ? src : s4 == 1 ? src1 : s4 == 2 ? src2 : src3;
            uint32_t b0 = __shfl_sync(~0u, x0, from), b1 = __shfl_sync(~0u, x1, from);
            b0 = hfma2(b0, cp[2 * s4], hmul2(b0, cn[2 * s4]));
            b1 = hfma2(b1, cp[2 * s4 + 1], hmul2(b1, cn[2 * s4 + 1]));
#pragma unroll
            for (int i = 0; i < 4; i++) mma4(acc[i], A[4 * s4 + i], b0, b1);
            if (s4 == 0) { q = sel(g1, c[1], c[0]); s = c[2] + c[3]; q += __shfl_xor_sync(~0u, q, 4); s += __shfl_xor_sync(~0u, s, 9); }
            if (s4 == 1) q += __shfl_xor_sync(~0u, q, 9);
            if (s4 == 2) { if (lane == 0 || lane == 18) sts64f(r_st, s, fmaxf(fmaf(s * (-1.0f / 64), s, q), 0.f)); }
        }
        sts128f(p_st, sel(t2, acc[1][0] + acc[1][1], acc[0][0] + acc[0][1]), sel(t2, acc[3][0] + acc[3][1], acc[2][0] + acc[2][1]),
                sel(t2, acc[1][2] + acc[1][3], acc[0][2] + acc[0][3]), sel(t2, acc[3][2] + acc[3][3], acc[2][2] + acc[2][3]));
        bar_arrive<4>();
        uint32_t xo[2];
#pragma unroll
        for (int j = 0; j < 2; j++) {
            const uint32_t e0 = __shfl_sync(~0u, x0, 16 * t1 + 8 * j + g), e1 = __shfl_sync(~0u, x1, 16 * t1 + 8 * j + g);
            xo[j] = __byte_perm(e0, e1, t2 ? 0x7632 : 0x5410);
        }
        mbar_wait(sb + BAR_W2 + 8 * (w * NW >> 3), 0);
#pragma unroll
        for (int i = 0; i < 8; i++)
            ldsm4t(sb + slot_addr(N_FFN + 4) + w * 4096 + (i >> 2) * 2048 + (sw128 ^ ((i & 3) * 32)), A[i]);
#pragma unroll
        for (int i = 0; i < 4; i++) { acc[i][0] = acc[i][1] = acc[i][2] = acc[i][3] = 0.f; }
        bar_sync<5>();
        asm volatile("{\n.reg .pred p;\nsetp.ne.u32 p, %0, 0;\n@p bar.sync 7, 256;\n}" :: "r"(near) : "memory");
        const uint4 hv = lds128(sb + SM_Q + ((g & 2) * 2 + t) * 16);
#pragma unroll
        for (int i = 0; i < 4; i++) mma4(acc[i], A[i], hv.x, hv.y);
#pragma unroll
        for (int i = 0; i < 4; i++) mma4(acc[i], A[4 + i], hv.z, hv.w);
        float r[4], o[6];
#pragma unroll
        for (int i = 0; i < 4; i++) r[i] = sel(t2, acc[i][2], acc[i][0]);
        asm volatile("atom.relaxed.gpu.global.add.v4.f32 {%0, %1, %2, %3}, [%4], {%5, %6, %7, %8};"
                     : "=f"(o[0]), "=f"(o[1]), "=f"(o[2]), "=f"(o[4]) : "l"(out_p), "f"(r[0]), "f"(r[1]), "f"(r[2]), "f"(1.0f) : "memory");
        asm volatile("atom.relaxed.gpu.global.add.v2.f32 {%0, %1}, [%2], {%3, %4};"
                     : "=f"(o[3]), "=f"(o[5]) : "l"(out2_p), "f"(r[3]), "f"(1.0f) : "memory");
        asm volatile("{\n.reg .pred p;\nsetp.eq.u32 p, %0, 0;\n@p bar.arrive 7, 256;\n}" :: "r"(near) : "memory");
        uint2 gb = ld_strong64(gb_p);
        const uint32_t f0 = pack2(o[0] + r[0], o[1] + r[1]), f1 = pack2(o[2] + r[2], o[3] + r[3]);
#pragma unroll 1
        for (uint32_t n = 0; n < SPIN_LIMIT; n++) {
            const uint32_t y0 = hadd2(xo[0], hmul2(gb.x, f0)), y1 = hadd2(xo[1], hmul2(gb.y, f1));
            uint32_t late;
            asm volatile("{\n.reg .pred p, q, m;\n.reg .b16 a, b, c, d;\n"
                         "mov.b32 {a, b}, %6;\nmov.b32 {c, d}, %7;\nsetp.ne.b16 m, a, 0xffff;\nsetp.ne.and.b16 m, b, 0xffff, m;\nsetp.ne.and.b16 m, c, 0xffff, m;\nsetp.ne.and.b16 m, d, 0xffff, m;\n"
                         "setp.eq.and.f32 p, %4, 0f42280000, m;\nsetp.eq.and.f32 q, %5, 0f42280000, m;\n"
                         "mov.b32 {a, b}, %2;\nmov.b32 {c, d}, %3;\n"
                         "@p st.global.u16 [%1], a;\n@p st.global.u16 [%1 + 32], b;\n@p st.global.u16 [%1 + 64], c;\n@q st.global.u16 [%1 + 96], d;\n"
                         "vote.sync.all.pred m, m, 0xffffffff;\nselp.u32 %0, 0, 1, m;\n}"
                         : "=r"(late) : "l"(y_p), "r"(y0), "r"(y1), "f"(o[4]), "f"(o[5]), "r"(gb.x), "r"(gb.y) : "memory");
            if (!late) break;
            gb = ld_strong64(gb_p);
        }
    } else if (is_gb) {
        const uint32_t fa = sb + slot_addr(N_FFN) + grp * 8192 + (64 * sub + lrow) * 32 + ((lch ^ ((lrow >> 2) & 1)) << 4);
        const int dl = (lane & 7) * 4 + ((lane >> 3) & 1) * 2 + ob;
        u64 gb_p = s_line(2 * (role >> 2), 6 + (dl >> 4)) + (dl & 15) * 8 + (role & 3) * 2;
        PIN64(gb_p);
        uint32_t bs[8];
#pragma unroll
        for (int i = 0; i < 8; i++) bs[i] = __shfl_sync(~0u, (i & 1) ? sc1 : sc0, 4 * (i >> 1) + 16 * ((g >> 1) & 1) + t);
        const uint32_t c_st = sb + SM_PART + (w * 32 + t1 * 16 + (t >> 1) * 8 + g) * 4;
        settle(tag, sb + SM_OP, bs[0], bs[1], bs[2], bs[3]); settle(tag, sb + SM_OP, bs[4], bs[5], bs[6], bs[7]); settle(tag, sb + SM_OP, c_st, fa, 0, 0);
        mbar_wait(sb + BAR_FFN + 8 * grp, 0);
        float c[4][4];
#pragma unroll
        for (int s4 = 0; s4 < 4; s4++) ldsm4t(fa + s4 * 512, A[s4]);
#pragma unroll
        for (int s4 = 0; s4 < 4; s4++) { c[s4][0] = c[s4][1] = c[s4][2] = c[s4][3] = 0.f; mma4(c[s4], A[s4], bs[2 * s4], bs[2 * s4 + 1]); }
        sts32f(c_st, sel(t2, (c[0][2] + c[1][2]) + (c[2][2] + c[3][2]), (c[0][0] + c[1][0]) + (c[2][0] + c[3][0])));
        cbar();
        if (w == 0) {
            float u[8];
#pragma unroll
            for (int i = 0; i < 8; i++) u[i] = lds32f(sb + SM_PART + i * 128 + lane * 4);
            const uint16_t v = (uint16_t)pack2(((u[0] + u[1]) + (u[2] + u[3])) + ((u[4] + u[5]) + (u[6] + u[7])), 0.f);
            asm volatile("st.relaxed.gpu.global.u16 [%0], %1;\nst.relaxed.gpu.global.u16 [%0 + 4096], %1;" :: "l"(gb_p), "h"(v) : "memory");
        }
    }
}

typedef CUresult (*EncodeFn)(CUtensorMap*, CUtensorMapDataType, cuuint32_t, void*, const cuuint64_t*, const cuuint64_t*,
                             const cuuint32_t*, const cuuint32_t*, CUtensorMapInterleave, CUtensorMapSwizzle,
                             CUtensorMapL2promotion, CUtensorMapFloatOOBfill);

void make_map(EncodeFn enc, CUtensorMap* m, void* ptr, int cols, int rows, int box_cols, int box_rows, CUtensorMapSwizzle sw) {
    cuuint64_t gd[2] = {(cuuint64_t)cols, (cuuint64_t)rows}, gs[1] = {(cuuint64_t)cols * 2};
    cuuint32_t bd[2] = {(cuuint32_t)box_cols, (cuuint32_t)box_rows}, es[2] = {1, 1};
    enc(m, CU_TENSOR_MAP_DATA_TYPE_BFLOAT16, 2, ptr, gd, gs, bd, es, CU_TENSOR_MAP_INTERLEAVE_NONE, sw,
        CU_TENSOR_MAP_L2_PROMOTION_NONE, CU_TENSOR_MAP_FLOAT_OOB_FILL_NONE);
}

}

extern "C" void kernel_launch(void* const* d_in, const int* in_sizes, int n_in, void* d_out, int out_size) {
    (void)in_sizes; (void)n_in; (void)out_size;
    static EncodeFn enc = nullptr;
    if (!enc) {
        void* fn = nullptr;
        cudaDriverEntryPointQueryResult qr;
        cudaGetDriverEntryPoint("cuTensorMapEncodeTiled", &fn, cudaEnableDefault, &qr);
        enc = (EncodeFn)fn;
        cudaFuncSetAttribute(fused_decode_kernel, cudaFuncAttributeMaxDynamicSharedMemorySize, SMEM_BYTES);
    }
    Params p;
    Ptrs q;
    make_map(enc, &p.m_wmod, d_in[10], MODW, D_, 32, 256, CU_TENSOR_MAP_SWIZZLE_64B);
    make_map(enc, &p.m_wq, d_in[3], QD, D_, 64, 128, CU_TENSOR_MAP_SWIZZLE_128B);
    make_map(enc, &p.m_v, d_in[2], DH, 64 * SK, 64, 128, CU_TENSOR_MAP_SWIZZLE_128B);
    {
        cuuint64_t gd[3] = {64, QD, 8}, gs[2] = {D_ * 2, 128};
        cuuint32_t bd[3] = {64, 16, 8}, es[3] = {1, 1, 1};
        enc(&p.m_wo, CU_TENSOR_MAP_DATA_TYPE_BFLOAT16, 3, d_in[4], gd, gs, bd, es, CU_TENSOR_MAP_INTERLEAVE_NONE,
            CU_TENSOR_MAP_SWIZZLE_128B, CU_TENSOR_MAP_L2_PROMOTION_NONE, CU_TENSOR_MAP_FLOAT_OOB_FILL_NONE);
    }
    for (int i = 0; i < 2; i++) {
        cuuint64_t gd[4] = {FF, 2, 8, D_ / 16}, gs[3] = {8 * FF * 2, FF * 2, 16 * FF * 2};
        cuuint32_t bd[4] = {32, 2, 8, 32 / NQ}, es[4] = {1, 1, 1, 1};
        enc(i ? &p.m_w3 : &p.m_w1, CU_TENSOR_MAP_DATA_TYPE_BFLOAT16, 4, d_in[6 + i], gd, gs, bd, es, CU_TENSOR_MAP_INTERLEAVE_NONE,
            CU_TENSOR_MAP_SWIZZLE_64B, CU_TENSOR_MAP_L2_PROMOTION_NONE, CU_TENSOR_MAP_FLOAT_OOB_FILL_NONE);
    }
    {
        cuuint64_t gd[5] = {64, 2, 8, FF / 16, 8}, gs[4] = {8 * D_ * 2, D_ * 2, 16 * D_ * 2, 128};
        cuuint32_t bd[5] = {64, 2, 8, 2, 8 / NW}, es[5] = {1, 1, 1, 1, 1};
        enc(&p.m_w2, CU_TENSOR_MAP_DATA_TYPE_BFLOAT16, 5, d_in[8], gd, gs, bd, es, CU_TENSOR_MAP_INTERLEAVE_NONE,
            CU_TENSOR_MAP_SWIZZLE_128B, CU_TENSOR_MAP_L2_PROMOTION_NONE, CU_TENSOR_MAP_FLOAT_OOB_FILL_NONE);
    }
    make_map(enc, &p.m_gb, d_in[10], MODW, D_, 16, 256, CU_TENSOR_MAP_SWIZZLE_32B);
    q.x = (const __nv_bfloat16*)d_in[0];
    q.kwin = (const __nv_bfloat16*)d_in[1] + (size_t)(SK - WIN) * DH;
    q.c = (const __nv_bfloat16*)d_in[9];
    q.out = (__nv_bfloat16*)d_out;
    fused_decode_kernel<<<NCTA, THREADS, SMEM_BYTES, cudaStreamPerThread>>>(q, p);
}
```

```cpp
#include <cuda_runtime.h>
#include <cuda.h>
#include <cuda_bf16.h>
#include <stdint.h>

namespace {

constexpr int D_ = 512, DH = 128, SK = 16384, WIN = 4096, FF = 1376, QD = 4096, MODW = 3072;
constexpr int NCTA = 128;
constexpr int TILE_BYTES = 16384;
constexpr int NT = 32;
constexpr int STAGES = 13;
constexpr int K_FIRST = 2;
constexpr int FIRST_N = 5;
constexpr int WO_AT = 20;
constexpr int WO_EARLY = 3;
constexpr int PACE = 656;
constexpr int LEAD_NS = 1350;
constexpr int GATE_X = 23;
constexpr int POLL_NS = 300;
constexpr int ALPHA16 = 4;
constexpr int GU_NS = 5075;
constexpr int W2_NS = 6240;
constexpr int GB_LEAD = 390;
constexpr int NQ = 8;
constexpr int PROBES = 6;
constexpr int PROBE_NS = 1000;
constexpr int EARLY_NS = 800;
constexpr int NW = 4;
constexpr int HEAD_TID = 256;
constexpr int N_WMOD = 0, N_WQ = 2, N_K = 6, N_V = N_K + NT, N_WO = N_V + WO_AT, N_V2 = N_WO + WO_EARLY, N_WO2 = N_V + NT + WO_EARLY, N_FFN = N_V + NT + 4;
constexpr int N_GATE = N_V + GATE_X + WO_EARLY;
constexpr int THREADS = 320;
constexpr int N_MOD_CTA = 80;
#define SPIN_LIMIT_S "4194304"
constexpr unsigned SPIN_LIMIT = 1u << 22;

constexpr int SM_RING = 0;
constexpr int SM_P = STAGES * TILE_BYTES;
constexpr int SM_PART = SM_P + WIN * 2;
constexpr int SM_OP = SM_PART + 8192;
constexpr int SM_Q = SM_OP + 2048;
constexpr int SM_RED = SM_Q + 256;
constexpr int SM_ML = SM_RED + 128;
constexpr int SM_PROG = SM_ML + 16;
constexpr int SM_SIDE = SM_PROG + 16;
constexpr int SM_BAR = SM_SIDE + 16;
constexpr int BAR_FULL = SM_BAR, BAR_EMPTY = SM_BAR + 8 * STAGES, BAR_XQ = SM_BAR + 16 * STAGES,
              BAR_XML = BAR_XQ + 8, BAR_XP = BAR_XQ + 16, BAR_FFN = BAR_XQ + 24;
constexpr int BAR_W2 = BAR_FFN + 8 * NQ;
constexpr int SMEM_BYTES = BAR_W2 + 8 * NW;
static_assert(SMEM_BYTES <= 232448, "shared memory");
__host__ __device__ constexpr uint32_t slot_addr(int n) { return SM_RING + (n % STAGES) * TILE_BYTES; }
__host__ __device__ constexpr uint32_t full_bar(int n) { return BAR_FULL + 8 * (n % STAGES); }
__host__ __device__ constexpr uint32_t empty_bar(int n) { return BAR_EMPTY + 8 * (n % STAGES); }
__host__ __device__ constexpr uint32_t tile_phase(int n) { return (n / STAGES) & 1; }
static_assert((N_FFN + 4) % STAGES + 2 <= STAGES && N_FFN % STAGES + 4 <= STAGES, "w1/w3 tiles and w2 tiles occupy consecutive slots");
static_assert(GATE_X >= WO_AT && N_GATE - STAGES < N_V2 && N_FFN + 5 - 2 * STAGES < N_WO && N_FFN + 5 - STAGES < N_WO2,
              "barrier parities the helper warp waits on are unambiguous after the rendezvous; the last wo tiles are not replaced");
__host__ __device__ constexpr int fill_tile(int j) { return j < K_FIRST ? N_K + j : j < K_FIRST + N_K ? j - K_FIRST : j; }

struct Ptrs {
    const __nv_bfloat16 *kwin, *x, *c;
    __nv_bfloat16* out;
};
struct Params {
    CUtensorMap m_wmod, m_wq, m_v, m_wo, m_w1, m_w3, m_w2, m_gb;
};

__device__ unsigned g_epoch;
__device__ __align__(128) uint2 g_mod[2][5 * D_ / 2];
__device__ __align__(256) unsigned char g_s[131072];
__device__ __forceinline__ unsigned long long s_line(int blk, int i) {
    return (((unsigned long long)g_s + 65535) & ~65535ull) + blk * 4096 + (i >> 1) * 1024 + (i & 1) * 256;
}
__device__ __forceinline__ int e1_blk(int r, int w) { return 2 * w + (r ^ (w & 1)); }
constexpr int S_OUT = 512, S_PROG = 128;
__device__ __align__(128) unsigned g_clear;

typedef unsigned long long u64;
__device__ __forceinline__ unsigned time_ns() {
    unsigned r;
    asm volatile("mov.u32 %0, %%globaltimer_lo;" : "=r"(r));
    return r;
}
__device__ __forceinline__ bool elect_one() {
    uint32_t r;
    asm volatile("{\n.reg .pred p;\nelect.sync _|p, 0xffffffff;\nselp.u32 %0, 1, 0, p;\n}" : "=r"(r));
    return r != 0;
}
#define PIN64(v) asm volatile("" : "+l"(v))

__device__ __forceinline__ void mbar_init(uint32_t bar, uint32_t cnt) {
    asm volatile("mbarrier.init.shared::cta.b64 [%0], %1;" :: "r"(bar), "r"(cnt) : "memory");
}
__device__ __forceinline__ void mbar_expect_tx(uint32_t bar, uint32_t bytes) {
    asm volatile("mbarrier.arrive.expect_tx.shared::cta.b64 _, [%0], %1;" :: "r"(bar), "r"(bytes) : "memory");
}
__device__ __forceinline__ void mbar_arrive(uint32_t bar) {
    asm volatile("mbarrier.arrive.shared::cta.b64 _, [%0];" :: "r"(bar) : "memory");
}
__device__ __forceinline__ void mbar_arrive_n(uint32_t bar, uint32_t n) {
    asm volatile("mbarrier.arrive.shared::cta.b64 _, [%0], %1;" :: "r"(bar), "r"(n) : "memory");
}
__device__ __forceinline__ void mbar_wait(uint32_t bar, uint32_t parity) {
    asm volatile("{\n.reg .pred p;\n.reg .u32 n;\nmov.u32 n, 0;\nW0:\n"
                 "mbarrier.try_wait.parity.shared::cta.b64 p, [%0], %1;\n@p bra W1;\n"
                 "add.u32 n, n, 1;\nsetp.lt.u32 p, n, " SPIN_LIMIT_S ";\n@p bra W0;\nW1:\n}"
                 :: "r"(bar), "r"(parity) : "memory");
}
__device__ __forceinline__ void mbar_wait_cluster(uint32_t bar, uint32_t parity) {
    asm volatile("{\n.reg .pred p;\n.reg .u32 n;\nmov.u32 n, 0;\nW0:\n"
                 "mbarrier.try_wait.parity.acquire.cluster.shared::cta.b64 p, [%0], %1;\n@p bra W1;\n"
                 "add.u32 n, n, 1;\nsetp.lt.u32 p, n, " SPIN_LIMIT_S ";\n@p bra W0;\nW1:\n}"
                 :: "r"(bar), "r"(parity) : "memory");
}
__device__ __forceinline__ void bulk_load(uint32_t dst, const void* src, uint32_t bytes, uint32_t bar, uint64_t pol) {
    asm volatile("cp.async.bulk.shared::cluster.global.mbarrier::complete_tx::bytes.L2::cache_hint [%0], [%1], %2, [%3], %4;"
                 :: "r"(dst), "l"(src), "r"(bytes), "r"(bar), "l"(pol) : "memory");
}
__device__ __forceinline__ void tma2d(uint32_t dst, const CUtensorMap* m, int c0, int c1, uint32_t bar) {
    asm volatile("cp.async.bulk.tensor.2d.shared::cluster.global.mbarrier::complete_tx::bytes [%0], [%1, {%3, %4}], [%2];"
                 :: "r"(dst), "l"(m), "r"(bar), "r"(c0), "r"(c1) : "memory");
}
__device__ __forceinline__ void tma2d_hint(uint32_t dst, const CUtensorMap* m, int c0, int c1, uint32_t bar, uint64_t pol) {
    asm volatile("cp.async.bulk.tensor.2d.shared::cluster.global.mbarrier::complete_tx::bytes.L2::cache_hint [%0], [%1, {%3, %4}], [%2], %5;"
                 :: "r"(dst), "l"(m), "r"(bar), "r"(c0), "r"(c1), "l"(pol) : "memory");
}
__device__ __forceinline__ void tma3d(uint32_t dst, const CUtensorMap* m, int c0, int c1, int c2, uint32_t bar) {
    asm volatile("cp.async.bulk.tensor.3d.shared::cluster.global.mbarrier::complete_tx::bytes [%0], [%1, {%3, %4, %5}], [%2];"
                 :: "r"(dst), "l"(m), "r"(bar), "r"(c0), "r"(c1), "r"(c2) : "memory");
}
__device__ __forceinline__ void tma4d(uint32_t dst, const CUtensorMap* m, int c0, int c3, uint32_t bar) {
    asm volatile("cp.async.bulk.tensor.4d.shared::cluster.global.mbarrier::complete_tx::bytes [%0], [%1, {%3, %5, %5, %4}], [%2];"
                 :: "r"(dst), "l"(m), "r"(bar), "r"(c0), "r"(c3), "r"(0) : "memory");
}
__device__ __forceinline__ void tma5d(uint32_t dst, const CUtensorMap* m, int c3, int c4, uint32_t bar) {
    asm volatile("cp.async.bulk.tensor.5d.shared::cluster.global.mbarrier::complete_tx::bytes [%0], [%1, {%5, %5, %5, %3, %4}], [%2];"
                 :: "r"(dst), "l"(m), "r"(bar), "r"(c3), "r"(c4), "r"(0) : "memory");
}
__device__ __forceinline__ uint32_t mapa(uint32_t addr, uint32_t rank) {
    uint32_t r;
    asm("mapa.shared::cluster.u32 %0, %1, %2;" : "=r"(r) : "r"(addr), "r"(rank));
    return r;
}
__device__ __forceinline__ void st_async_b32(uint32_t addr, uint32_t v, uint32_t bar) {
    asm volatile("st.async.weak.shared::cluster.mbarrier::complete_tx::bytes.b32 [%0], %1, [%2];" :: "r"(addr), "r"(v), "r"(bar) : "memory");
}
__device__ __forceinline__ void st_async_v2(uint32_t addr, float a, float b, uint32_t bar) {
    asm volatile("st.async.weak.shared::cluster.mbarrier::complete_tx::bytes.v2.f32 [%0], {%1, %2}, [%3];" :: "r"(addr), "f"(a), "f"(b), "r"(bar) : "memory");
}
__device__ __forceinline__ void st_async_v4(uint32_t addr, uint32_t a, uint32_t b, uint32_t c, uint32_t d, uint32_t bar) {
    asm volatile("st.async.weak.shared::cluster.mbarrier::complete_tx::bytes.v4.b32 [%0], {%1, %2, %3, %4}, [%5];"
                 :: "r"(addr), "r"(a), "r"(b), "r"(c), "r"(d), "r"(bar) : "memory");
}
template <int ID> __device__ __forceinline__ void bar_sync() { asm volatile("bar.sync %0, 288;" :: "n"(ID) : "memory"); }
template <int ID> __device__ __forceinline__ void bar_arrive() { asm volatile("bar.arrive %0, 288;" :: "n"(ID) : "memory"); }
__device__ __forceinline__ void cbar() { asm volatile("bar.sync 1, 256;" ::: "memory"); }

__device__ __forceinline__ uint4 ldg128(const void* p) {
    uint4 v;
    asm volatile("ld.global.nc.v4.u32 {%0,%1,%2,%3}, [%4];" : "=r"(v.x), "=r"(v.y), "=r"(v.z), "=r"(v.w) : "l"(p));
    return v;
}
__device__ __forceinline__ uint32_t ldg16(const void* p) {
    uint16_t v;
    asm volatile("ld.global.nc.u16 %0, [%1];" : "=h"(v) : "l"(p));
    return v;
}
__device__ __forceinline__ uint4 ld_strong128(unsigned long long p) {
    uint4 v;
    asm volatile("ld.relaxed.gpu.global.v4.b32 {%0,%1,%2,%3}, [%4];" : "=r"(v.x), "=r"(v.y), "=r"(v.z), "=r"(v.w) : "l"(p) : "memory");
    return v;
}
__device__ __forceinline__ uint2 ld_strong64(unsigned long long p) {
    uint2 v;
    asm volatile("ld.relaxed.gpu.global.v2.b32 {%0,%1}, [%2];" : "=r"(v.x), "=r"(v.y) : "l"(p) : "memory");
    return v;
}
__device__ __forceinline__ uint32_t ldg32(const void* p) {
    uint32_t v;
    asm volatile("ld.global.nc.u32 %0, [%1];" : "=r"(v) : "l"(p));
    return v;
}
struct Pkt2 { u64 a, b; };
__device__ __forceinline__ uint32_t lo32(u64 v) { return (uint32_t)v; }
__device__ __forceinline__ uint32_t hi32(u64 v) { return (uint32_t)(v >> 32); }
__device__ __forceinline__ Pkt2 ld_pkt2(const void* p) {
    Pkt2 r;
    asm volatile("ld.relaxed.gpu.global.v2.b64 {%0,%1}, [%2];" : "=l"(r.a), "=l"(r.b) : "l"(p) : "memory");
    return r;
}
__device__ __forceinline__ bool pkt_ok(const Pkt2& r, uint32_t tag) { return hi32(r.a) == tag && hi32(r.b) == tag; }
__device__ __forceinline__ void st_pkt(u64 p, uint32_t data, uint32_t tag) {
    asm volatile("{\n.reg .b64 v;\nmov.b64 v, {%1, %2};\nst.relaxed.gpu.global.b64 [%0], v;\n}" :: "l"(p), "r"(data), "r"(tag) : "memory");
}
__device__ __forceinline__ uint4 lds128(uint32_t a) {
    uint4 v;
    asm volatile("ld.shared.v4.u32 {%0,%1,%2,%3}, [%4];" : "=r"(v.x), "=r"(v.y), "=r"(v.z), "=r"(v.w) : "r"(a) : "memory");
    return v;
}
__device__ __forceinline__ float4 lds128f(uint32_t a) {
    float4 v;
    asm volatile("ld.shared.v4.f32 {%0,%1,%2,%3}, [%4];" : "=f"(v.x), "=f"(v.y), "=f"(v.z), "=f"(v.w) : "r"(a) : "memory");
    return v;
}
__device__ __forceinline__ uint2 lds64(uint32_t a) {
    uint2 v;
    asm volatile("ld.shared.v2.u32 {%0,%1}, [%2];" : "=r"(v.x), "=r"(v.y) : "r"(a) : "memory");
    return v;
}
__device__ __forceinline__ float2 lds64f(uint32_t a) {
    float2 v;
    asm volatile("ld.shared.v2.f32 {%0,%1}, [%2];" : "=f"(v.x), "=f"(v.y) : "r"(a) : "memory");
    return v;
}
__device__ __forceinline__ float lds32f(uint32_t a) {
    float v;
    asm volatile("ld.shared.f32 %0, [%1];" : "=f"(v) : "r"(a) : "memory");
    return v;
}
__device__ __forceinline__ void sts64f(uint32_t a, float x, float y) {
    asm volatile("st.shared.v2.f32 [%0], {%1,%2};" :: "r"(a), "f"(x), "f"(y) : "memory");
}
__device__ __forceinline__ void sts128f(uint32_t a, float x, float y, float z, float w) {
    asm volatile("st.shared.v4.f32 [%0], {%1,%2,%3,%4};" :: "r"(a), "f"(x), "f"(y), "f"(z), "f"(w) : "memory");
}
__device__ __forceinline__ void sts32f(uint32_t a, float x) {
    asm volatile("st.shared.f32 [%0], %1;" :: "r"(a), "f"(x) : "memory");
}
__device__ __forceinline__ void sts128(uint32_t a, uint32_t x, uint32_t y, uint32_t z, uint32_t w) {
    asm volatile("st.shared.v4.u32 [%0], {%1,%2,%3,%4};" :: "r"(a), "r"(x), "r"(y), "r"(z), "r"(w) : "memory");
}
__device__ __forceinline__ void settle(uint32_t tag, uint32_t a, uint32_t x, uint32_t y, uint32_t z, uint32_t w) {
    asm volatile("{\n.reg .pred p;\nsetp.eq.u32 p, %0, 0;\n@p st.shared.v4.u32 [%1], {%2,%3,%4,%5};\n}" :: "r"(tag), "r"(a), "r"(x), "r"(y), "r"(z), "r"(w) : "memory");
}
__device__ __forceinline__ void settle(uint32_t tag, uint32_t a, const float4& v) {
    settle(tag, a, __float_as_uint(v.x), __float_as_uint(v.y), __float_as_uint(v.z), __float_as_uint(v.w));
}
__device__ __forceinline__ void sts16(uint32_t a, uint32_t x) {
    asm volatile("st.shared.u16 [%0], %1;" :: "r"(a), "h"((uint16_t)x) : "memory");
}
__device__ __forceinline__ void ldsm4t(uint32_t a, uint32_t (&r)[4]) {
    asm volatile("ldmatrix.sync.aligned.m8n8.x4.trans.shared.b16 {%0,%1,%2,%3}, [%4];"
                 : "=r"(r[0]), "=r"(r[1]), "=r"(r[2]), "=r"(r[3]) : "r"(a) : "memory");
}
__device__ __forceinline__ void mma(float (&c)[4], uint32_t a0, uint32_t a1, uint32_t a2, uint32_t a3, uint32_t b0, uint32_t b1) {
    asm volatile("mma.sync.aligned.m16n8k16.row.col.f32.bf16.bf16.f32 {%0,%1,%2,%3}, {%4,%5,%6,%7}, {%8,%9}, {%0,%1,%2,%3};"
                 : "+f"(c[0]), "+f"(c[1]), "+f"(c[2]), "+f"(c[3]) : "r"(a0), "r"(a1), "r"(a2), "r"(a3), "r"(b0), "r"(b1));
}
__device__ __forceinline__ void mma4(float (&c)[4], const uint32_t (&a)[4], uint32_t b0, uint32_t b1) { mma(c, a[0], a[1], a[2], a[3], b0, b1); }
__device__ __forceinline__ float sel(uint32_t c, float a, float b) {
    float r;
    asm("{\n.reg .pred p;\nsetp.ne.u32 p, %3, 0;\nselp.f32 %0, %1, %2, p;\n}" : "=f"(r) : "f"(a), "f"(b), "r"(c));
    return r;
}
__device__ __forceinline__ float bf_lo(uint32_t v) { return __uint_as_float(v << 16); }
__device__ __forceinline__ float bf_hi(uint32_t v) { return __uint_as_float(v & 0xffff0000u); }
__device__ __forceinline__ uint32_t pack2(float lo, float hi) {
    uint32_t r;
    asm("cvt.rn.bf16x2.f32 %0, %1, %2;" : "=r"(r) : "f"(hi), "f"(lo));
    return r;
}
__device__ __forceinline__ float rbf(float x) { return __uint_as_float(pack2(0.f, x)); }
__device__ __forceinline__ uint32_t hadd2(uint32_t a, uint32_t b) { uint32_t r; asm("add.rn.bf16x2 %0, %1, %2;" : "=r"(r) : "r"(a), "r"(b)); return r; }
__device__ __forceinline__ uint32_t hsub2(uint32_t a, uint32_t b) { uint32_t r; asm("sub.rn.bf16x2 %0, %1, %2;" : "=r"(r) : "r"(a), "r"(b)); return r; }
__device__ __forceinline__ uint32_t hmul2(uint32_t a, uint32_t b) { uint32_t r; asm("mul.rn.bf16x2 %0, %1, %2;" : "=r"(r) : "r"(a), "r"(b)); return r; }
__device__ __forceinline__ uint32_t hfma2(uint32_t a, uint32_t b, uint32_t c) { uint32_t r; asm("fma.rn.bf16x2 %0, %1, %2, %3;" : "=r"(r) : "r"(a), "r"(b), "r"(c)); return r; }
__device__ __forceinline__ uint32_t selu(uint32_t c, uint32_t a, uint32_t b) { return __float_as_uint(sel(c, __uint_as_float(a), __uint_as_float(b))); }
constexpr uint32_t ONE2 = 0x3f803f80u;
__device__ __forceinline__ float silu_f(float x) {
    float e, r;
    asm("ex2.approx.ftz.f32 %0, %1;" : "=f"(e) : "f"(x * -1.4426950408889634f));
    asm("rcp.approx.ftz.f32 %0, %1;" : "=f"(r) : "f"(1.0f + e));
    return x * r;
}
__device__ __forceinline__ float rcp_sd(float m2) {
    float s, r;
    asm("sqrt.approx.ftz.f32 %0, %1;" : "=f"(s) : "f"(rbf(rbf(m2 * (1.0f / D_)) + 1e-5f)));
    asm("rcp.approx.ftz.f32 %0, %1;" : "=f"(r) : "f"(rbf(s)));
    return r;
}
__device__ __forceinline__ uint32_t ln_mod2(uint32_t x, uint32_t mean2, float rsd, uint32_t c1, uint32_t sh) {
    const uint32_t d = hsub2(x, mean2);
    return hadd2(hmul2(pack2(bf_lo(d) * rsd, bf_hi(d) * rsd), c1), sh);
}
__device__ __forceinline__ int pair_pos(int j) { return 2 * (j & 3) + (j >> 2); }

__global__ void __cluster_dims__(2, 1, 1) __launch_bounds__(THREADS, 1)
fused_decode_kernel(const __grid_constant__ Ptrs q_, const __grid_constant__ Params p) {
    extern __shared__ __align__(1024) unsigned char smem[];
    unsigned t_top;
    asm volatile("mov.u32 %0, %%globaltimer_lo;" : "=r"(t_top));
    const int tid = threadIdx.x;
    uint32_t z0;
    asm("and.b32 %0, %1, 1024;" : "=r"(z0) : "r"(tid));
    const char* kw = *(const char* const*)((const char*)&q_.kwin + z0);
    const uint32_t sb = (uint32_t)__cvta_generic_to_shared(smem);
    auto place = [](int cl) { return cl < 4 ? 8 * cl + 39 : cl - 4 + max((cl * 37 - 36 * 37) >> 8, 0); };
    uint32_t z2;
    asm("and.b32 %0, %1, 2048;" : "=r"(z2) : "r"(tid));
    const int cv = blockIdx.x + z2, pw = place(cv >> 1);
    static_assert(SK * DH * 2 == 1 << 22 && TILE_BYTES == 1 << 14, "koff");
    const char* kp;
    auto set_kp = [&](uint32_t off) {
        asm volatile("{\n.reg .u32 lo, hi;\nmov.b64 {lo, hi}, %1;\nadd.cc.u32 lo, lo, %2;\naddc.u32 hi, hi, 0;\nmov.b64 %0, {lo, hi};\n}"
                     : "=l"(kp) : "l"(kw), "r"(off));
    };
    uint64_t pol;
    asm("createpolicy.fractional.L2::evict_first.b64 %0, 1.0;" : "=l"(pol));
    auto fill_k = [&](int n) {
        mbar_expect_tx(sb + full_bar(n), TILE_BYTES);
        bulk_load(sb + slot_addr(n), kp + (n - N_K) * 2 * TILE_BYTES, TILE_BYTES, sb + full_bar(n), pol);
    };
    static_assert(K_FIRST >= 1, "head block starts with K tile 0");
    if (tid + (sb >> 28) == HEAD_TID) {
        mbar_init(sb + full_bar(N_K), 1);
        set_kp(((pw & 7) << 22) | ((pw & 8) << 24) | ((pw & 48) << 21) | ((cv & 1) << 14));
        bulk_load(sb + slot_addr(N_K), kp, TILE_BYTES, sb + full_bar(N_K), pol);
        mbar_expect_tx(sb + full_bar(N_K), TILE_BYTES);
#pragma unroll
        for (int j = 1; j < K_FIRST; j++) { mbar_init(sb + full_bar(N_K + j), 1); fill_k(N_K + j); }
    }
    __syncwarp();
    const int cta = blockIdx.x, rank = cta & 1, pv = place(cta >> 1);
    const int b = (pv >> 3) & 1, h = (pv & 7) | ((pv >> 1) & 24), bh = 32 * b + h;
    const int mc = 2 * pv + rank;
    auto first_fill = [&](int j) {
        const int n = fill_tile(j);
        if (n >= N_K) {
            fill_k(n);
        } else if (n >= N_WQ) {
            mbar_expect_tx(sb + full_bar(n), TILE_BYTES);
            tma2d(sb + slot_addr(n), &p.m_wq, h * DH + 64 * rank, 128 * (n - N_WQ), sb + full_bar(n));
        } else if (mc < N_MOD_CTA) {
            mbar_expect_tx(sb + full_bar(n), TILE_BYTES);
            tma2d(sb + slot_addr(n), &p.m_wmod, 32 * mc, 256 * n, sb + full_bar(n));
        } else {
            mbar_arrive(sb + full_bar(n));
        }
    };
    if (tid == HEAD_TID) {
#pragma unroll
        for (int j = K_FIRST; j < FIRST_N; j++) mbar_init(sb + full_bar(fill_tile(j)), 1);
#pragma unroll
        for (int j = K_FIRST; j < FIRST_N; j++) first_fill(j);
        asm volatile("fence.mbarrier_init.release.cluster;" ::: "memory");
    }
    __syncwarp();
    const int role = cta / 3;
    const bool is_gu = cta == 3 * role, is_gb = cta == 3 * role + 1 && role < 32;
    if (tid >= 288) {
        const unsigned t_start = t_top;
        asm volatile("barrier.cluster.arrive.relaxed.aligned;" ::: "memory");
        unsigned tag;
        asm volatile("ld.relaxed.gpu.global.u32 %0, [%1];" : "=r"(tag) : "l"(&g_epoch) : "memory");
        tag += 1;
        if (cta == NCTA - 1) {
#pragma unroll 2
            for (int i = tid - 288; i < 128 * 8; i += 32) {
                uint4* q = reinterpret_cast<uint4*>(s_line(i >> 6, (i >> 3) & 7)) + (i & 7);
                const uint32_t v = (i & 48) == 48 ? ~0u : 0u;
                q[0] = make_uint4(v, v, v, v);
                q[8] = q[32] = q[40] = make_uint4(0u, 0u, 0u, 0u);
            }
            __syncwarp();
            asm volatile("fence.acq_rel.gpu;" ::: "memory");
            if (tid == 288) asm volatile("st.relaxed.gpu.global.u32 [%0], %1;" :: "l"(&g_clear), "r"(tag) : "memory");
        }
        asm volatile("barrier.cluster.wait.acquire.aligned;" ::: "memory");
        mbar_wait_cluster(sb + BAR_XQ, 0);
        for (uint32_t n = 0; n < SPIN_LIMIT; n++) {
            unsigned c;
            asm volatile("ld.relaxed.gpu.global.u32 %0, [%1];" : "=r"(c) : "l"(&g_clear) : "memory");
            if (c == tag) break;
        }
        asm volatile("fence.acq_rel.gpu;" ::: "memory");
        asm volatile("st.volatile.shared.u32 [%0], %1;" :: "r"(sb + SM_SIDE), "r"(0) : "memory");
        asm volatile("bar.sync 2, 288;" ::: "memory");
        if (elect_one()) {
            asm volatile("prefetch.tensormap [%0];" :: "l"(is_gu ? &p.m_w1 : &p.m_gb) : "memory");
            asm volatile("prefetch.tensormap [%0];" :: "l"(&p.m_w3) : "memory");
            asm volatile("prefetch.tensormap [%0];" :: "l"(&p.m_w2) : "memory");
            const int issue = ((4 * N_GATE - 11 - 2 * WO_EARLY) * PACE >> 2) - LEAD_NS;
            unsigned now, c = 0, best[2] = {~0u, ~0u}, np = is_gu ? 0 : PROBES;
            auto probe = [&]() {
                const int k = np >> 1, i = (role >> 3) + 2 * k;
                const u64 a = (s_line(e1_blk(0, role & 7), i < 6 ? i : i - 6) + (k ? 512 * k - 384 : 0)) ^ ((np & 1) << 12);
                unsigned v, c0, c1 = 0;
                asm volatile("mov.u32 %0, %%clock;" : "=r"(c0));
                asm volatile("ld.relaxed.gpu.global.u32 %0, [%1];" : "=r"(v) : "l"(a) : "memory");
                asm volatile("{\n.reg .pred p;\nsetp.ne.u32 p, %1, 0xffffffff;\n@p mov.u32 %0, %%clock;\n}" : "+r"(c1) : "r"(v));
                if (np & 1) best[1] = min(best[1], c1 - c0); else best[0] = min(best[0], c1 - c0);
                np++;
                if (!(np & 1)) asm volatile("st.volatile.shared.u32 [%0], %1;" :: "r"(sb + SM_SIDE), "r"(best[0] <= best[1] ? 0 : 4096) : "memory");
            };
#pragma unroll 1
            while (np < PROBES) {
                now = time_ns();
                if ((int)(now - t_start) >= issue + EARLY_NS) break;
                probe();
            }
            mbar_wait(sb + full_bar(N_GATE), tile_phase(N_GATE));
            now = time_ns();
            const unsigned mine = (1u << 24) + min(now - t_start, 100000u);
            const u64 prog = s_line(0, 7) + S_PROG;
            asm volatile("red.relaxed.gpu.global.add.u32 [%0], %1;" :: "l"(prog), "r"(mine) : "memory");
            if (is_gu || is_gb) {
#pragma unroll
                for (int i = 0; i < 6; i++) mbar_wait(sb + empty_bar(N_FFN + i), tile_phase(N_FFN + i) ^ 1);
#pragma unroll
                for (int i = 0; i < NQ; i++) mbar_expect_tx(sb + BAR_FFN + 8 * i, is_gu ? 65536 / NQ : 8192);
#pragma unroll
                for (int i = 0; i < NW; i++) mbar_expect_tx(sb + BAR_W2 + 8 * i, 32768 / NW);
                unsigned due = 0, next = now;
                constexpr unsigned full = (unsigned)NCTA << 24;
                asm volatile("st.volatile.shared.u32 [%0], %1;" :: "r"(sb + SM_PROG), "r"(mine) : "memory");
#pragma unroll 1
                for (uint32_t n = 0; n < 4096; n++) {
                    unsigned v;
                    asm volatile("ld.volatile.shared.u32 %0, [%1];" : "=r"(v) : "r"(sb + SM_PROG) : "memory");
                    if (v > c) {
                        c = v;
                        const int arr = (int)__fdividef((float)(c & 0xffffffu), (float)(c >> 24));
                        due = arr - ((arr - issue) * ALPHA16 >> 4) + (is_gb ? W2_NS - GB_LEAD : GU_NS);
                    }
                    now = time_ns();
                    if (now - t_start + PROBE_NS >= due) np = PROBES;
                    if ((c >= full && np == PROBES) || now - t_start >= due) break;
                    if ((int)(now - next) >= 0 && c < full) {
                        asm volatile("cp.async.cg.shared.global [%0], [%1], 16;" :: "r"(sb + SM_PROG), "l"(prog) : "memory");
                        next = now + POLL_NS;
                    }
                    if (np < PROBES) probe();
                }
#pragma unroll 1
                for (uint32_t n = 0; n < 1024 && now - t_start < due; n++) now = time_ns();
                if (is_gu) {
#pragma unroll
                    for (int i = 0; i < 2 * NQ; i++) {
                        const int q = i >> 1, r0 = q * (512 / NQ);
                        tma4d(sb + slot_addr(N_FFN) + (r0 >> 8) * 2 * TILE_BYTES + (i & 1) * TILE_BYTES + (r0 & 255) * 64, (i & 1) ? &p.m_w3 : &p.m_w1, 32 * role, r0 / 16, sb + BAR_FFN + 8 * q);
                    }
#pragma unroll 1
                    for (uint32_t n = 0; n < 1024 && now - t_start < due + (W2_NS - GU_NS); n++) now = time_ns();
                    const int f = best[0] <= best[1] ? NW / 2 : 0;
#pragma unroll
                    for (int i = 0; i < NW; i++) tma5d(sb + slot_addr(N_FFN + 4) + (i ^ f) * (32768 / NW), &p.m_w2, 2 * role, (i ^ f) * (8 / NW), sb + BAR_W2 + 8 * (i ^ f));
                } else {
                    tma2d(sb + slot_addr(N_FFN), &p.m_gb, 5 * D_ + 16 * role, 0, sb + BAR_FFN);
                    tma2d(sb + slot_addr(N_FFN) + 8192, &p.m_gb, 5 * D_ + 16 * role, 256, sb + BAR_FFN + 8);
                }
                asm volatile("cp.async.wait_all;" ::: "memory");
            }
        }
        __syncwarp();
        if (is_gu) {
            const int lane = tid & 31;
            auto sum8 = [&](uint32_t a, int stride) {
                float4 u[8];
#pragma unroll
                for (int i = 0; i < 8; i++) u[i] = lds128f(a + i * stride);
                return make_float4(((u[0].x + u[1].x) + (u[2].x + u[3].x)) + ((u[4].x + u[5].x) + (u[6].x + u[7].x)),
                                   ((u[0].y + u[1].y) + (u[2].y + u[3].y)) + ((u[4].y + u[5].y) + (u[6].y + u[7].y)),
                                   ((u[0].z + u[1].z) + (u[2].z + u[3].z)) + ((u[4].z + u[5].z) + (u[6].z + u[7].z)),
                                   ((u[0].w + u[1].w) + (u[2].w + u[3].w)) + ((u[4].w + u[5].w) + (u[6].w + u[7].w)));
            };
            uint32_t h_st = sb + SM_Q + (((lane & 1) * 4 + ((lane >> 2) & 3)) * 4 + (lane & 2) + (lane >> 4)) * 4;
            bar_sync<3>();
            const float4 C = sum8(sb + SM_P + lane * 16, 1024), S = sum8(sb + SM_P + 512 + lane * 16, 1024);
            const uint32_t st_ld = sb + SM_RED + (lane & 1) * 64;
            settle(tag, sb + SM_OP, C); settle(tag, sb + SM_OP, S); settle(tag, sb + SM_OP, h_st, st_ld, 0, 0);
            bar_sync<4>();
            const float4 r0 = lds128f(st_ld), r1 = lds128f(st_ld + 16), r2 = lds128f(st_ld + 32), r3 = lds128f(st_ld + 48);
            const float4 Y = sum8(sb + SM_PART + lane * 16, 512);
            const float e1 = r0.z - r0.x, e2 = r1.x - r0.x, e3 = r1.z - r0.x, e4 = r2.x - r0.x, e5 = r2.z - r0.x, e6 = r3.x - r0.x, e7 = r3.z - r0.x;
            const float se = ((e1 + e2) + (e3 + e4)) + ((e5 + e6) + e7);
            const float ee = (fmaf(e1, e1, e2 * e2) + fmaf(e3, e3, e4 * e4)) + fmaf(e5, e5, fmaf(e6, e6, e7 * e7));
            const float sq = ((r0.y + r0.w) + (r1.y + r1.w)) + ((r2.y + r2.w) + (r3.y + r3.w));
            const float rsd = rcp_sd(fmaf(se * (-1.0f / D_), se, fmaf(ee, 1.0f / 64, sq))), mu = -rbf(fmaf(r0.x, 8.0f, se) * (1.0f / D_));
            const uint32_t gr = pack2(fmaf(rsd, fmaf(mu, C.x, Y.x), S.x), fmaf(rsd, fmaf(mu, C.z, Y.z), S.z));
            const uint32_t ur = pack2(fmaf(rsd, fmaf(mu, C.y, Y.y), S.y), fmaf(rsd, fmaf(mu, C.w, Y.w), S.w));
            const uint32_t hv = hmul2(pack2(silu_f(bf_lo(gr)), silu_f(bf_hi(gr))), ur);
            sts32f(h_st, __uint_as_float(hv));
            bar_arrive<5>();
            if (role == 0 && lane == 0) g_epoch = tag;
        }
        return;
    }
    if (tid >= 256) {
        set_kp(bh * (SK * DH * 2) + rank * TILE_BYTES);
        const unsigned t_start = t_top;
        auto pace = [&](int q4) {
            const int due = (q4 * PACE >> 2) - LEAD_NS;
            unsigned now, n = 0;
            do { now = time_ns(); } while ((int)(now - t_start) < due && ++n < 256);
        };
        if (tid == 256) {
#pragma unroll
            for (int j = FIRST_N; j < STAGES; j++) mbar_init(sb + full_bar(fill_tile(j)), 1);
#pragma unroll
            for (int s = 0; s < STAGES; s++) mbar_init(sb + BAR_EMPTY + 8 * s, 8);
            mbar_init(sb + BAR_XQ, 1); mbar_init(sb + BAR_XML, 1); mbar_init(sb + BAR_XP, 1);
#pragma unroll
            for (int i = 0; i < NQ + NW; i++) mbar_init(sb + BAR_FFN + 8 * i, 1);
            mbar_expect_tx(sb + BAR_XQ, 256); mbar_expect_tx(sb + BAR_XML, 8); mbar_expect_tx(sb + BAR_XP, WIN);
            asm volatile("fence.mbarrier_init.release.cluster;" ::: "memory");
            asm volatile("fence.proxy.async.shared::cta;" ::: "memory");
        }
        __syncwarp();
        asm volatile("barrier.cluster.arrive.relaxed.aligned;" ::: "memory");
        if (elect_one()) {
#pragma unroll
            for (int j = FIRST_N; j < STAGES; j++) {
                pace(j <= K_FIRST ? 4 * j : j <= K_FIRST + 2 ? 4 * K_FIRST + 5 * (j - K_FIRST) / 2 :
                     j <= K_FIRST + 6 ? 4 * K_FIRST + 5 + 2 * (j - K_FIRST - 2) : 4 * j - 11);
                first_fill(j);
            }
        }
        __syncwarp();
        asm volatile("barrier.cluster.wait.acquire.aligned;" ::: "memory");
        if (elect_one()) {
            asm volatile("prefetch.tensormap [%0];" :: "l"(&p.m_v) : "memory");
            asm volatile("prefetch.tensormap [%0];" :: "l"(&p.m_wo) : "memory");
            int s = 0, ph = 0;
#pragma unroll 1
            for (int n = STAGES; n < N_FFN; n++) {
                const uint32_t dst = sb + SM_RING + s * TILE_BYTES, bar = sb + BAR_FULL + 8 * s;
                mbar_wait(sb + BAR_EMPTY + 8 * s, ph);
                mbar_expect_tx(bar, TILE_BYTES);
                pace(n < N_WO ? 4 * n - 11 : n < N_V2 ? 2 * (N_WO + n) - 11 : n < N_WO2 ? 4 * n - 11 - 2 * WO_EARLY : 2 * (N_WO2 + n - WO_EARLY) - 11);
                if (n < N_V) bulk_load(dst, kp + (n - N_K) * 2 * TILE_BYTES, TILE_BYTES, bar, pol);
                else if (n >= N_WO2 || (n >= N_WO && n < N_V2)) tma3d(dst, &p.m_wo, 0, h * DH + 64 * rank + 16 * (n - (n < N_V2 ? N_WO : N_V + NT)), 0, bar);
                else tma2d_hint(dst, &p.m_v, 64 * rank, bh * SK + (SK - WIN) + 128 * (n - (n < N_WO ? N_V : N_V + WO_EARLY)), bar, pol);
                if (++s == STAGES) { s = 0; ph ^= 1; }
            }
        }
        return;
    }

    const unsigned t_c = t_top;
    const int lane = tid & 31, w = tid >> 5, g = lane >> 2, t = lane & 3;
    const int hgrp = 4 * w + (g & 3);
    const int vb = g >> 2;
    const uint32_t cv0 = ldg32(q_.c + vb * D_ + 16 * hgrp + 2 * t), cv1 = ldg32(q_.c + vb * D_ + 16 * hgrp + 8 + 2 * t);
    unsigned tag;
    asm volatile("ld.relaxed.gpu.global.u32 %0, [%1];" : "=r"(tag) : "l"(&g_epoch) : "memory");
    const uint4 xa = ldg128(q_.x + b * D_ + 16 * lane), xb = ldg128(q_.x + b * D_ + 16 * lane + 8);
    const uint32_t xh0 = ldg32(q_.x + b * D_ + 16 * hgrp + 2 * t), xh1 = ldg32(q_.x + b * D_ + 16 * hgrp + 8 + 2 * t);
    asm volatile("barrier.cluster.arrive.relaxed.aligned;" ::: "memory");
#pragma unroll 1
    for (uint32_t n = t_c; n < 2; n++) asm volatile("nanosleep.u32 1;" ::: "memory");
    const int grp = w >> 2, sub = w & 3;
    const int lrow = (lane & 7) + 8 * (lane >> 4);
    const int lch = (lane >> 3) & 1;
    const int ob = lane >> 4;
    const uint32_t t1 = t & 1, t2 = t & 2;
    const int gsrc = 16 * (g & 1) + t;
    const uint32_t sw128 = lrow * 128 + ((lch ^ (lrow & 7)) << 4);
    uint32_t A[16][4];

    const uint32_t sc0 = pack2(silu_f(bf_lo(cv0)), silu_f(bf_hi(cv0))), sc1 = pack2(silu_f(bf_lo(cv1)), silu_f(bf_hi(cv1)));
    tag += 1;
    asm volatile("barrier.cluster.wait.acquire.aligned;" ::: "memory");
    mbar_wait(sb + BAR_FULL + 8 * (N_WMOD + grp), 0);
    if (mc < N_MOD_CTA) {
        const uint32_t tb = sb + SM_RING + (N_WMOD + grp) * TILE_BYTES + (64 * sub + lrow) * 64;
#pragma unroll
        for (int i = 0; i < 8; i++)
            ldsm4t(tb + (i >> 1) * 1024 + (((2 * (i & 1) + lch) ^ ((lrow >> 1) & 3)) << 4), A[i]);
        float acc[2][4] = {{0.f, 0.f, 0.f, 0.f}, {0.f, 0.f, 0.f, 0.f}};
#pragma unroll
        for (int s = 0; s < 4; s++) {
            const uint32_t b0 = __shfl_sync(~0u, sc0, 4 * s + gsrc), b1 = __shfl_sync(~0u, sc1, 4 * s + gsrc);
            mma4(acc[0], A[2 * s], b0, b1);
            mma4(acc[1], A[2 * s + 1], b0, b1);
        }
        sts32f(sb + SM_P + (w * 64 + 8 * t + g) * 4, sel(t2, sel(t1, acc[1][2], acc[1][0]), sel(t1, acc[0][2], acc[0][0])));
        sts32f(sb + SM_P + (w * 64 + 32 + 8 * t + g) * 4, sel(t2, sel(t1, acc[1][3], acc[1][1]), sel(t1, acc[0][3], acc[0][1])));
        cbar();
        if (w == 0) {
            const bool adj = mc < 32;
            const uint32_t a0 = sb + SM_P + (adj ? 2 * lane : ob * 32 + (lane & 1) * 16 + ((lane >> 1) & 7)) * 4, a1 = a0 + (adj ? 4 : 32);
            float2 sum = make_float2(0.f, 0.f);
#pragma unroll
            for (int i = 0; i < 8; i++) { sum.x += lds32f(a0 + i * 256); sum.y += lds32f(a1 + i * 256); }
            st_pkt((u64)&g_mod[ob][16 * mc + (adj ? (lane & 8) + pair_pos(lane & 7) : lane & 15)], pack2(sum.x, sum.y), tag);
        }
    }
    __syncwarp();
    if (lane == 0) mbar_arrive_n(sb + BAR_EMPTY + 8 * (N_WMOD + grp), 2);

    {
        const uint2* mp = &g_mod[b][vb * 256 + 8 * hgrp + 2 * t];
        const uint32_t ms = sb + SM_PART + tid * 16;
        auto fetch_mod = [&](uint32_t k) {
            asm volatile("cp.async.cg.shared.global [%0], [%1], 16;\ncp.async.commit_group;" :: "r"(ms + k), "l"(mp) : "memory");
        };
        fetch_mod(0);
        float xs[16] = {bf_lo(xa.x), bf_hi(xa.x), bf_lo(xa.y), bf_hi(xa.y), bf_lo(xa.z), bf_hi(xa.z), bf_lo(xa.w), bf_hi(xa.w),
                        bf_lo(xb.x), bf_hi(xb.x), bf_lo(xb.y), bf_hi(xb.y), bf_lo(xb.z), bf_hi(xb.z), bf_lo(xb.w), bf_hi(xb.w)};
        float s = 0.f;
#pragma unroll
        for (int i = 0; i < 16; i++) s += xs[i];
#pragma unroll
        for (int m = 1; m < 32; m <<= 1) s += __shfl_xor_sync(~0u, s, m);
        const float mean = s * (1.0f / D_);
        float q = 0.f;
#pragma unroll
        for (int i = 0; i < 16; i++) q += (xs[i] - mean) * (xs[i] - mean);
#pragma unroll
        for (int m = 1; m < 32; m <<= 1) q += __shfl_xor_sync(~0u, q, m);
        const uint32_t mean2 = pack2(mean, mean);
        const float rsd = rcp_sd(q);

        mbar_wait(sb + BAR_FULL + 8 * (N_WQ + (w >> 1)), 0);
        const uint32_t tb = sb + SM_RING + (N_WQ + (w >> 1)) * TILE_BYTES + (w & 1) * 8192;
#pragma unroll
        for (int i = 0; i < 16; i++) ldsm4t(tb + (i >> 2) * 2048 + (sw128 ^ ((i & 3) * 32)), A[i]);
        __syncwarp();
        if (lane == 0) mbar_arrive_n(sb + BAR_EMPTY + 8 * (N_WQ + (w >> 1)), 4);

        Pkt2 m;
        for (uint32_t n = 0, k = 0; n < SPIN_LIMIT; n++) {
            fetch_mod(k ^ 4096);
            asm volatile("cp.async.wait_group 1;" ::: "memory");
            const uint4 u = lds128(ms + k);
            m.a = u.x | (u64)u.y << 32; m.b = u.z | (u64)u.w << 32;
            if (__all_sync(~0u, pkt_ok(m, tag))) break;
            k ^= 4096;
        }
        const uint32_t ca0 = __shfl_xor_sync(~0u, lo32(m.a), 16), ca1 = __shfl_xor_sync(~0u, lo32(m.b), 16);
        const uint32_t v0 = ln_mod2(xh0, mean2, rsd, hadd2(ONE2, ca0), lo32(m.a));
        const uint32_t v1 = ln_mod2(xh1, mean2, rsd, hadd2(ONE2, ca1), lo32(m.b));
        float acc[4][4];
#pragma unroll
        for (int i = 0; i < 4; i++) { acc[i][0] = acc[i][1] = acc[i][2] = acc[i][3] = 0.f; }
#pragma unroll
        for (int s4 = 0; s4 < 4; s4++) {
            const uint32_t b0 = __shfl_sync(~0u, v0, 4 * s4 + t), b1 = __shfl_sync(~0u, v1, 4 * s4 + t);
#pragma unroll
            for (int i = 0; i < 4; i++) mma4(acc[i], A[4 * s4 + i], b0, b1);
        }
        sts32f(sb + SM_OP + (w * 64 + 16 * t + g) * 4, sel(t2, sel(t1, acc[3][0], acc[2][0]), sel(t1, acc[1][0], acc[0][0])));
        sts32f(sb + SM_OP + (w * 64 + 16 * t + 8 + g) * 4, sel(t2, sel(t1, acc[3][2], acc[2][2]), sel(t1, acc[1][2], acc[0][2])));
        cbar();
        if (w == 0) {
            float2 sum = make_float2(0.f, 0.f);
#pragma unroll
            for (int i = 0; i < 8; i++) { const float2 u = lds64f(sb + SM_OP + (i * 64 + 2 * lane) * 4); sum.x += u.x; sum.y += u.y; }
            const uint32_t v = pack2(sum.x, sum.y), a = sb + SM_Q + rank * 128 + lane * 4;
            st_async_b32(mapa(a, rank ^ 1), v, mapa(sb + BAR_XQ, rank ^ 1));
            st_async_b32(mapa(a, rank), v, mapa(sb + BAR_XQ, rank));
        }
        mbar_wait_cluster(sb + BAR_XQ, 0);
    }

    Pkt2 mga, msb, mcb;
    uint32_t tx0, tx1;
    const uint2* tmp = &g_mod[ob][32 * w + 2 * (lane & 15)];
    {
        uint4 Q[4];
        uint32_t koff[4];
#pragma unroll
        for (int i = 0; i < 4; i++) {
            const int ch = t + 4 * (i ^ (g & 1));
            Q[i] = lds128(sb + SM_Q + ch * 16);
            koff[i] = (sub * 16 + g) * 256 + ch * 16;
        }
        float mx = -INFINITY;
        int stage = N_K + grp, phase = 0;
#pragma unroll 1
        for (int it = 0; it < NT / 2; it++) {
            const uint32_t tb = sb + SM_RING + stage * TILE_BYTES;
            mbar_wait(sb + BAR_FULL + 8 * stage, phase);
            uint4 Ka[4], Kb[4];
#pragma unroll
            for (int i = 0; i < 4; i++) { Ka[i] = lds128(tb + koff[i]); Kb[i] = lds128(tb + koff[i] + 2048); }
            float c0[4] = {0.f, 0.f, 0.f, 0.f}, c1[4] = {0.f, 0.f, 0.f, 0.f};
#pragma unroll
            for (int i = 0; i < 4; i++) {
                mma(c0, Ka[i].x, Kb[i].x, Ka[i].y, Kb[i].y, Q[i].x, Q[i].y);
                mma(c1, Ka[i].z, Kb[i].z, Ka[i].w, Kb[i].w, Q[i].z, Q[i].w);
            }
            __syncwarp();
            if (lane == 0) mbar_arrive_n(sb + BAR_EMPTY + 8 * stage, 2);
            const float lo = (g & 1) ? c0[1] + c1[1] : c0[0] + c1[0];
            const float hi = (g & 1) ? c0[3] + c1[3] : c0[2] + c1[2];
            const float sc = rbf(rbf(t1 ? hi : lo) * 0.08838834764831845f);
            mx = fmaxf(mx, sc);
            if (t < 2) sts16(sb + SM_P + ((2 * it + grp) * 128 + rank * 64 + sub * 16 + 4 * (g >> 1) + 2 * t + (g & 1)) * 2, __float_as_uint(sc) >> 16);
            stage += 2;
            if (stage >= STAGES) { stage -= STAGES; phase ^= 1; }
        }

        mga = ld_pkt2(tmp + 2 * 256); msb = ld_pkt2(tmp + 3 * 256); mcb = ld_pkt2(tmp + 4 * 256);
        const __nv_bfloat16* xp = q_.x + ob * D_ + 64 * w + 4 * (lane & 8) + (lane & 7);
        tx0 = ldg16(xp) | ldg16(xp + 8) << 16;
        tx1 = ldg16(xp + 16) | ldg16(xp + 24) << 16;

        asm volatile("cp.async.wait_all;" ::: "memory");

#pragma unroll
        for (int m = 1; m < 32; m <<= 1) mx = fmaxf(mx, __shfl_xor_sync(~0u, mx, m));
        if (lane == 0) sts32f(sb + SM_RED + w * 4, mx);
        cbar();
        {
            const float4 u = lds128f(sb + SM_RED), v = lds128f(sb + SM_RED + 16);
            mx = fmaxf(fmaxf(fmaxf(u.x, u.y), fmaxf(u.z, u.w)), fmaxf(fmaxf(v.x, v.y), fmaxf(v.z, v.w)));
        }
        const uint32_t pa = sb + SM_P + (tid >> 3) * 256 + rank * 128 + (tid & 7) * 16;
        const uint4 s0 = lds128(pa);
        const float sc[8] = {bf_lo(s0.x), bf_hi(s0.x), bf_lo(s0.y), bf_hi(s0.y), bf_lo(s0.z), bf_hi(s0.z), bf_lo(s0.w), bf_hi(s0.w)};
        float l = 0.f;
#pragma unroll
        for (int i = 0; i < 8; i++) l += __expf(sc[i] - mx);
#pragma unroll
        for (int m = 1; m < 32; m <<= 1) l += __shfl_xor_sync(~0u, l, m);
        if (lane == 0) sts32f(sb + SM_RED + 32 + w * 4, l);
        cbar();
        {
            const float4 u = lds128f(sb + SM_RED + 32), v = lds128f(sb + SM_RED + 48);
            l = ((u.x + u.y) + (u.z + u.w)) + ((v.x + v.y) + (v.z + v.w));
        }
        if (tid == 0) st_async_v2(mapa(sb + SM_ML, rank ^ 1), mx, l, mapa(sb + BAR_XML, rank ^ 1));
        mbar_wait_cluster(sb + BAR_XML, 0);
        const float2 o = lds64f(sb + SM_ML);
        const float m = fmaxf(mx, o.x);
        const float inv = __fdividef(1.0f, l * __expf(mx - m) + o.y * __expf(o.x - m));
        const uint32_t p0 = pack2(__expf(sc[0] - m) * inv, __expf(sc[1] - m) * inv), p1 = pack2(__expf(sc[2] - m) * inv, __expf(sc[3] - m) * inv);
        const uint32_t p2 = pack2(__expf(sc[4] - m) * inv, __expf(sc[5] - m) * inv), p3 = pack2(__expf(sc[6] - m) * inv, __expf(sc[7] - m) * inv);
        st_async_v4(mapa(pa, rank ^ 1), p0, p1, p2, p3, mapa(sb + BAR_XP, rank ^ 1));
        sts128(pa, p0, p1, p2, p3);
        cbar();
        mbar_wait_cluster(sb + BAR_XP, 0);
    }

    for (uint32_t n = 0; n < SPIN_LIMIT && !__all_sync(~0u, pkt_ok(mga, tag) && pkt_ok(msb, tag) && pkt_ok(mcb, tag)); n++) {
        mga = ld_pkt2(tmp + 2 * 256); msb = ld_pkt2(tmp + 3 * 256); mcb = ld_pkt2(tmp + 4 * 256);
    }
    const uint32_t ga0 = lo32(mga.a), ga1 = lo32(mga.b), sb0 = lo32(msb.a), sb1 = lo32(msb.b);
    const uint32_t cb0 = hadd2(ONE2, lo32(mcb.a)), cb1 = hadd2(ONE2, lo32(mcb.b));
    u64 red_p = s_line(e1_blk(1, w), 2 * b) + lane * 4, red2_p = s_line(e1_blk(1, w), 4 + b) + lane * 4;

    PIN64(red_p); PIN64(red2_p);
    float oa[4][4];
#pragma unroll
    for (int i = 0; i < 4; i++) { oa[i][0] = oa[i][1] = oa[i][2] = oa[i][3] = 0.f; }
    {
        int stage = N_V % STAGES, phase = tile_phase(N_V);
        auto v_tiles = [&](int v0, int v1) {
#pragma unroll 1
            for (int v = v0; v < v1; v++) {
                const uint32_t tb = sb + SM_RING + stage * TILE_BYTES + grp * 8192 + (sw128 ^ (sub * 32));
                uint2 P[4];
#pragma unroll
                for (int i = 0; i < 4; i++) P[i] = lds64(sb + SM_P + v * 256 + grp * 128 + i * 32 + t * 8);
                mbar_wait(sb + BAR_FULL + 8 * stage, phase);
                uint32_t a[4][4];
#pragma unroll
                for (int i = 0; i < 4; i++) ldsm4t(tb + i * 2048, a[i]);
#pragma unroll
                for (int i = 0; i < 4; i++) mma4(oa[i], a[i], P[i].x, P[i].y);
                __syncwarp();
                if (lane == 0) mbar_arrive(sb + BAR_EMPTY + 8 * stage);
                if (++stage == STAGES) { stage = 0; phase ^= 1; }
            }
        };
        v_tiles(0, WO_AT);
#pragma unroll
        for (int i = 0; i < 4 * WO_EARLY; i++) {
            if ((i & 3) == 0) mbar_wait(sb + full_bar(N_WO + (i >> 2)), tile_phase(N_WO + (i >> 2)));
            ldsm4t(sb + slot_addr(N_WO + (i >> 2)) + w * 2048 + (sw128 ^ ((i & 3) * 32)), A[i]);
        }
        asm volatile("bar.sync 2, 288;" ::: "memory");
        if (tid < WO_EARLY) mbar_arrive_n(sb + BAR_EMPTY + 8 * ((N_WO + tid) % STAGES), 8);
        stage = N_V2 % STAGES; phase = tile_phase(N_V2);
        v_tiles(WO_AT, NT);
    }

    if (t < 2) sts32f(sb + SM_OP + w * 64 + (g >> 1) * 16 + (g & 1) * 4 + t * 8,
                      sel(t1, (oa[0][2] + oa[1][2]) + (oa[2][2] + oa[3][2]), (oa[0][0] + oa[1][0]) + (oa[2][0] + oa[3][0])));
    cbar();

    {
        float acc[4][4];
#pragma unroll
        for (int i = 0; i < 4; i++) { acc[i][0] = acc[i][1] = acc[i][2] = acc[i][3] = 0.f; }
        const float2 u = lds64f(sb + SM_OP + (lane & 15) * 16 + vb * 8), v = lds64f(sb + SM_OP + 256 + (lane & 15) * 16 + vb * 8);
        const uint32_t o2 = pack2(u.x + v.x, u.y + v.y);
#pragma unroll
        for (int s4 = 0; s4 < 4; s4++) {
            const uint32_t b0 = __shfl_sync(~0u, o2, 4 * s4 + t), b1 = __shfl_sync(~0u, o2, 16 + 4 * s4 + t);
            if (s4 >= WO_EARLY) {
                mbar_wait(sb + full_bar(N_V + NT + s4), tile_phase(N_V + NT + s4));
                if (s4 == 3) { }
#pragma unroll
                for (int i = 0; i < 4; i++) ldsm4t(sb + slot_addr(N_V + NT + s4) + w * 2048 + (sw128 ^ (i * 32)), A[4 * s4 + i]);
            }
#pragma unroll
            for (int i = 0; i < 4; i++) mma4(acc[i], A[4 * s4 + i], b0, b1);
        }
        const float r0 = sel(t2, sel(t1, 1.0f, acc[1][0]), sel(t1, acc[0][2], acc[0][0]));
        const float r1 = sel(t2, sel(t1, 1.0f, acc[3][0]), sel(t1, acc[2][2], acc[2][0]));
        const float r2 = sel(t2, 1.0f, sel(t1, acc[3][2], acc[1][2]));
        asm volatile("red.relaxed.gpu.global.add.f32 [%0], %2;\nred.relaxed.gpu.global.add.f32 [%0 + 256], %3;\nred.relaxed.gpu.global.add.f32 [%1], %4;"
                     :: "l"(red_p), "l"(red2_p), "f"(r0), "f"(r1), "f"(r2) : "memory");
        asm volatile("red.relaxed.gpu.global.add.f32 [%0], %2;\nred.relaxed.gpu.global.add.f32 [%0 + 256], %3;\nred.relaxed.gpu.global.add.f32 [%1], %4;"
                     :: "l"(red_p ^ 4096), "l"(red2_p ^ 4096), "f"(r0), "f"(r1), "f"(r2) : "memory");
    }

    constexpr uint32_t CNT = 0x42800000u;
    if (is_gu) {
        uint32_t side;
        asm volatile("ld.volatile.shared.u32 %0, [%1];" : "=r"(side) : "r"(sb + SM_SIDE) : "memory");
        u64 acc_p = (s_line(e1_blk(0, w), lane >> 3) + (lane & 7) * 16) ^ side, acc2_p = (s_line(e1_blk(0, w), 4 + ob) + (lane & 7) * 16) ^ side;
        const int eb = e1_blk(w >> 2, w & 3);
        const uint32_t near = (w >> 2) * 4096 == side;
        u64 out_p = s_line(eb, lane >> 3) + S_OUT + (lane & 7) * 16, out2_p = s_line(eb, 4 + ob) + S_OUT + (lane & 15) * 8;
        u64 gb_p = (s_line(e1_blk(0, w), 6 + ob) + (lane & 15) * 8) ^ side, y_p = (u64)(q_.out + t1 * D_ + 64 * w + 4 * t2 + g);
        PIN64(acc_p); PIN64(acc2_p); PIN64(out_p); PIN64(out2_p); PIN64(gb_p); PIN64(y_p);
        auto keep = [&](uint32_t x) { return __shfl_sync(~0u, x, lane); };
        const int src = keep(8 * (g & 2) + t), src1 = keep(src + 4), src2 = keep(src + 8), src3 = keep(src + 12);
        const uint32_t p_st = keep(sb + SM_PART + w * 512 + lane * 16), r_st = keep(sb + SM_RED + (vb * 8 + w) * 8);
        tx0 = keep(tx0); tx1 = keep(tx1);
        const uint32_t g1 = g & 1;
        uint32_t cp[8], cn[8];
        float acc[4][4];
#pragma unroll
        for (int i = 0; i < 8; i++) {
            cp[i] = __shfl_sync(~0u, (i & 1) ? cb1 : cb0, 4 * (i >> 1) + src);
            cn[i] = selu(g1, __shfl_sync(~0u, (i & 1) ? sb1 : sb0, 4 * (i >> 1) + src), cp[i]);
        }
        const int frow = (lane & 7) + (lane & 16);
        const uint32_t fa = sb + slot_addr(N_FFN) + grp * 2 * TILE_BYTES + (64 * sub + frow) * 64 + ((lch ^ ((frow >> 1) & 3)) << 4);
        mbar_wait(sb + BAR_FFN + 8 * (w * NQ >> 3), 0);
        uint4 u = ld_strong128(acc_p), v = ld_strong128(acc2_p);
#pragma unroll
        for (int i = 0; i < 16; i++) ldsm4t((fa ^ ((i & 1) * 32)) + (i >> 3) * 2048 + ((i >> 2) & 1) * 512 + ((i >> 1) & 1) * TILE_BYTES, A[i]);
#pragma unroll
        for (int i = 0; i < 4; i++) { acc[i][0] = acc[i][1] = acc[i][2] = acc[i][3] = 0.f; }
#pragma unroll
        for (int i = 0; i < 16; i++) mma4(acc[i & 3], A[i], cn[2 * (i >> 2)], cn[2 * (i >> 2) + 1]);
        sts128f(sb + SM_P + w * 1024 + lane * 16, sel(t2, acc[1][0], acc[0][0]), sel(t2, acc[3][0], acc[2][0]), sel(t2, acc[1][2], acc[0][2]), sel(t2, acc[3][2], acc[2][2]));
        sts128f(sb + SM_P + w * 1024 + 512 + lane * 16, sel(t2, acc[1][1], acc[0][1]), sel(t2, acc[3][1], acc[2][1]), sel(t2, acc[1][3], acc[0][3]), sel(t2, acc[3][3], acc[2][3]));
        bar_arrive<3>();
#pragma unroll
        for (int i = 0; i < 8; i++) cn[i] = selu(g1, cp[i] ^ 0x80008000u, 0u);
        settle(tag, sb + SM_OP, cn[0], cn[1], cn[2], cn[3]); settle(tag, sb + SM_OP, cn[4], cn[5], cn[6], cn[7]);
        for (uint32_t n = 0; !__all_sync(~0u, u.w == CNT && v.w == CNT) && n < SPIN_LIMIT; n++) { u = ld_strong128(acc_p); v = ld_strong128(acc2_p); }
        const uint32_t x0 = hadd2(tx0, hmul2(ga0, pack2(__uint_as_float(u.x), __uint_as_float(u.y))));
        const uint32_t x1 = hadd2(tx1, hmul2(ga1, pack2(__uint_as_float(u.z), __uint_as_float(selu(lane & 8, v.y, v.x)))));
        float c[4] = {0.f, 0.f, 0.f, 0.f};
        mma(c, x0, ONE2, x1, ONE2, x0, x1);
#pragma unroll
        for (int i = 0; i < 4; i++) { acc[i][0] = acc[i][1] = acc[i][2] = acc[i][3] = 0.f; }
        float q, s;
#pragma unroll
        for (int s4 = 0; s4 < 4; s4++) {
            const int from = s4 == 0 ? src : s4 == 1 ? src1 : s4 == 2 ? src2 : src3;
            uint32_t b0 = __shfl_sync(~0u, x0, from), b1 = __shfl_sync(~0u, x1, from);
            b0 = hfma2(b0, cp[2 * s4], hmul2(b0, cn[2 * s4]));
            b1 = hfma2(b1, cp[2 * s4 + 1], hmul2(b1, cn[2 * s4 + 1]));
#pragma unroll
            for (int i = 0; i < 4; i++) mma4(acc[i], A[4 * s4 + i], b0, b1);
            if (s4 == 0) { q = sel(g1, c[1], c[0]); s = c[2] + c[3]; q += __shfl_xor_sync(~0u, q, 4); s += __shfl_xor_sync(~0u, s, 9); }
            if (s4 == 1) q += __shfl_xor_sync(~0u, q, 9);
            if (s4 == 2) { if (lane == 0 || lane == 18) sts64f(r_st, s, fmaxf(fmaf(s * (-1.0f / 64), s, q), 0.f)); }
        }
        sts128f(p_st, sel(t2, acc[1][0] + acc[1][1], acc[0][0] + acc[0][1]), sel(t2, acc[3][0] + acc[3][1], acc[2][0] + acc[2][1]),
                sel(t2, acc[1][2] + acc[1][3], acc[0][2] + acc[0][3]), sel(t2, acc[3][2] + acc[3][3], acc[2][2] + acc[2][3]));
        bar_arrive<4>();
        uint32_t xo[2];
#pragma unroll
        for (int j = 0; j < 2; j++) {
            const uint32_t e0 = __shfl_sync(~0u, x0, 16 * t1 + 8 * j + g), e1 = __shfl_sync(~0u, x1, 16 * t1 + 8 * j + g);
            xo[j] = __byte_perm(e0, e1, t2 ? 0x7632 : 0x5410);
        }
        mbar_wait(sb + BAR_W2 + 8 * (w * NW >> 3), 0);
#pragma unroll
        for (int i = 0; i < 8; i++)
            ldsm4t(sb + slot_addr(N_FFN + 4) + w * 4096 + (i >> 2) * 2048 + (sw128 ^ ((i & 3) * 32)), A[i]);
#pragma unroll
        for (int i = 0; i < 4; i++) { acc[i][0] = acc[i][1] = acc[i][2] = acc[i][3] = 0.f; }
        bar_sync<5>();
        asm volatile("{\n.reg .pred p;\nsetp.ne.u32 p, %0, 0;\n@p bar.sync 7, 256;\n}" :: "r"(near) : "memory");
        const uint4 hv = lds128(sb + SM_Q + ((g & 2) * 2 + t) * 16);
#pragma unroll
        for (int i = 0; i < 4; i++) mma4(acc[i], A[i], hv.x, hv.y);
#pragma unroll
        for (int i = 0; i < 4; i++) mma4(acc[i], A[4 + i], hv.z, hv.w);
        float r[4], o[6];
#pragma unroll
        for (int i = 0; i < 4; i++) r[i] = sel(t2, acc[i][2], acc[i][0]);
        asm volatile("atom.relaxed.gpu.global.add.v4.f32 {%0, %1, %2, %3}, [%4], {%5, %6, %7, %8};"
                     : "=f"(o[0]), "=f"(o[1]), "=f"(o[2]), "=f"(o[4]) : "l"(out_p), "f"(r[0]), "f"(r[1]), "f"(r[2]), "f"(1.0f) : "memory");
        asm volatile("atom.relaxed.gpu.global.add.v2.f32 {%0, %1}, [%2], {%3, %4};"
                     : "=f"(o[3]), "=f"(o[5]) : "l"(out2_p), "f"(r[3]), "f"(1.0f) : "memory");
        asm volatile("{\n.reg .pred p;\nsetp.eq.u32 p, %0, 0;\n@p bar.arrive 7, 256;\n}" :: "r"(near) : "memory");
        uint2 gb = ld_strong64(gb_p);
        const uint32_t f0 = pack2(o[0] + r[0], o[1] + r[1]), f1 = pack2(o[2] + r[2], o[3] + r[3]);
#pragma unroll 1
        for (uint32_t n = 0; n < SPIN_LIMIT; n++) {
            const uint32_t y0 = hadd2(xo[0], hmul2(gb.x, f0)), y1 = hadd2(xo[1], hmul2(gb.y, f1));
            uint32_t late;
            asm volatile("{\n.reg .pred p, q, m;\n.reg .b16 a, b, c, d;\n"
                         "mov.b32 {a, b}, %6;\nmov.b32 {c, d}, %7;\nsetp.ne.b16 m, a, 0xffff;\nsetp.ne.and.b16 m, b, 0xffff, m;\nsetp.ne.and.b16 m, c, 0xffff, m;\nsetp.ne.and.b16 m, d, 0xffff, m;\n"
                         "setp.eq.and.f32 p, %4, 0f42280000, m;\nsetp.eq.and.f32 q, %5, 0f42280000, m;\n"
                         "mov.b32 {a, b}, %2;\nmov.b32 {c, d}, %3;\n"
                         "@p st.global.u16 [%1], a;\n@p st.global.u16 [%1 + 32], b;\n@p st.global.u16 [%1 + 64], c;\n@q st.global.u16 [%1 + 96], d;\n"
                         "vote.sync.all.pred m, m, 0xffffffff;\nselp.u32 %0, 0, 1, m;\n}"
                         : "=r"(late) : "l"(y_p), "r"(y0), "r"(y1), "f"(o[4]), "f"(o[5]), "r"(gb.x), "r"(gb.y) : "memory");
            if (!late) break;
            gb = ld_strong64(gb_p);
        }
    } else if (is_gb) {
        const uint32_t fa = sb + slot_addr(N_FFN) + grp * 8192 + (64 * sub + lrow) * 32 + ((lch ^ ((lrow >> 2) & 1)) << 4);
        const int dl = (lane & 7) * 4 + ((lane >> 3) & 1) * 2 + ob;
        u64 gb_p = s_line(2 * (role >> 2), 6 + (dl >> 4)) + (dl & 15) * 8 + (role & 3) * 2;
        PIN64(gb_p);
        uint32_t bs[8];
#pragma unroll
        for (int i = 0; i < 8; i++) bs[i] = __shfl_sync(~0u, (i & 1) ? sc1 : sc0, 4 * (i >> 1) + 16 * ((g >> 1) & 1) + t);
        const uint32_t c_st = sb + SM_PART + (w * 32 + t1 * 16 + (t >> 1) * 8 + g) * 4;
        settle(tag, sb + SM_OP, bs[0], bs[1], bs[2], bs[3]); settle(tag, sb + SM_OP, bs[4], bs[5], bs[6], bs[7]); settle(tag, sb + SM_OP, c_st, fa, 0, 0);
        mbar_wait(sb + BAR_FFN + 8 * grp, 0);
        float c[4][4];
#pragma unroll
        for (int s4 = 0; s4 < 4; s4++) ldsm4t(fa + s4 * 512, A[s4]);
#pragma unroll
        for (int s4 = 0; s4 < 4; s4++) { c[s4][0] = c[s4][1] = c[s4][2] = c[s4][3] = 0.f; mma4(c[s4], A[s4], bs[2 * s4], bs[2 * s4 + 1]); }
        sts32f(c_st, sel(t2, (c[0][2] + c[1][2]) + (c[2][2] + c[3][2]), (c[0][0] + c[1][0]) + (c[2][0] + c[3][0])));
        cbar();
        if (w == 0) {
            float u[8];
#pragma unroll
            for (int i = 0; i < 8; i++) u[i] = lds32f(sb + SM_PART + i * 128 + lane * 4);
            const uint16_t v = (uint16_t)pack2(((u[0] + u[1]) + (u[2] + u[3])) + ((u[4] + u[5]) + (u[6] + u[7])), 0.f);
            asm volatile("st.relaxed.gpu.global.u16 [%0], %1;\nst.relaxed.gpu.global.u16 [%0 + 4096], %1;" :: "l"(gb_p), "h"(v) : "memory");
        }
    }
}

typedef CUresult (*EncodeFn)(CUtensorMap*, CUtensorMapDataType, cuuint32_t, void*, const cuuint64_t*, const cuuint64_t*,
                             const cuuint32_t*, const cuuint32_t*, CUtensorMapInterleave, CUtensorMapSwizzle,
                             CUtensorMapL2promotion, CUtensorMapFloatOOBfill);

void make_map(EncodeFn enc, CUtensorMap* m, void* ptr, int cols, int rows, int box_cols, int box_rows, CUtensorMapSwizzle sw) {
    cuuint64_t gd[2] = {(cuuint64_t)cols, (cuuint64_t)rows}, gs[1] = {(cuuint64_t)cols * 2};
    cuuint32_t bd[2] = {(cuuint32_t)box_cols, (cuuint32_t)box_rows}, es[2] = {1, 1};
    enc(m, CU_TENSOR_MAP_DATA_TYPE_BFLOAT16, 2, ptr, gd, gs, bd, es, CU_TENSOR_MAP_INTERLEAVE_NONE, sw,
        CU_TENSOR_MAP_L2_PROMOTION_NONE, CU_TENSOR_MAP_FLOAT_OOB_FILL_NONE);
}

}

extern "C" void kernel_launch(void* const* d_in, const int* in_sizes, int n_in, void* d_out, int out_size) {
    (void)in_sizes; (void)n_in; (void)out_size;
    static EncodeFn enc = nullptr;
    if (!enc) {
        void* fn = nullptr;
        cudaDriverEntryPointQueryResult qr;
        cudaGetDriverEntryPoint("cuTensorMapEncodeTiled", &fn, cudaEnableDefault, &qr);
        enc = (EncodeFn)fn;
        cudaFuncSetAttribute(fused_decode_kernel, cudaFuncAttributeMaxDynamicSharedMemorySize, SMEM_BYTES);
    }
    Params p;
    Ptrs q;
    make_map(enc, &p.m_wmod, d_in[10], MODW, D_, 32, 256, CU_TENSOR_MAP_SWIZZLE_64B);
    make_map(enc, &p.m_wq, d_in[3], QD, D_, 64, 128, CU_TENSOR_MAP_SWIZZLE_128B);
    make_map(enc, &p.m_v, d_in[2], DH, 64 * SK, 64, 128, CU_TENSOR_MAP_SWIZZLE_128B);
    {
        cuuint64_t gd[3] = {64, QD, 8}, gs[2] = {D_ * 2, 128};
        cuuint32_t bd[3] = {64, 16, 8}, es[3] = {1, 1, 1};
        enc(&p.m_wo, CU_TENSOR_MAP_DATA_TYPE_BFLOAT16, 3, d_in[4], gd, gs, bd, es, CU_TENSOR_MAP_INTERLEAVE_NONE,
            CU_TENSOR_MAP_SWIZZLE_128B, CU_TENSOR_MAP_L2_PROMOTION_NONE, CU_TENSOR_MAP_FLOAT_OOB_FILL_NONE);
    }
    for (int i = 0; i < 2; i++) {
        cuuint64_t gd[4] = {FF, 2, 8, D_ / 16}, gs[3] = {8 * FF * 2, FF * 2, 16 * FF * 2};
        cuuint32_t bd[4] = {32, 2, 8, 32 / NQ}, es[4] = {1, 1, 1, 1};
        enc(i ? &p.m_w3 : &p.m_w1, CU_TENSOR_MAP_DATA_TYPE_BFLOAT16, 4, d_in[6 + i], gd, gs, bd, es, CU_TENSOR_MAP_INTERLEAVE_NONE,
            CU_TENSOR_MAP_SWIZZLE_64B, CU_TENSOR_MAP_L2_PROMOTION_NONE, CU_TENSOR_MAP_FLOAT_OOB_FILL_NONE);
    }
    {
        cuuint64_t gd[5] = {64, 2, 8, FF / 16, 8}, gs[4] = {8 * D_ * 2, D_ * 2, 16 * D_ * 2, 128};
        cuuint32_t bd[5] = {64, 2, 8, 2, 8 / NW}, es[5] = {1, 1, 1, 1, 1};
        enc(&p.m_w2, CU_TENSOR_MAP_DATA_TYPE_BFLOAT16, 5, d_in[8], gd, gs, bd, es, CU_TENSOR_MAP_INTERLEAVE_NONE,
            CU_TENSOR_MAP_SWIZZLE_128B, CU_TENSOR_MAP_L2_PROMOTION_NONE, CU_TENSOR_MAP_FLOAT_OOB_FILL_NONE);
    }
    make_map(enc, &p.m_gb, d_in[10], MODW, D_, 16, 256, CU_TENSOR_MAP_SWIZZLE_32B);
    q.x = (const __nv_bfloat16*)d_in[0];
    q.kwin = (const __nv_bfloat16*)d_in[1] + (size_t)(SK - WIN) * DH;
    q.c = (const __nv_bfloat16*)d_in[9];
    q.out = (__nv_bfloat16*)d_out;
    fused_decode_kernel<<<NCTA, THREADS, SMEM_BYTES, cudaStreamPerThread>>>(q, p);
}
```

```cpp
#include <cuda_runtime.h>
#include <cuda.h>
#include <cuda_bf16.h>
#include <stdint.h>

namespace {

constexpr int D_ = 512, DH = 128, SK = 16384, WIN = 4096, FF = 1376, QD = 4096, MODW = 3072;
constexpr int NCTA = 128;
constexpr int TILE_BYTES = 16384;
constexpr int NT = 32;
constexpr int STAGES = 13;
constexpr int K_FIRST = 2;
constexpr int FIRST_N = 5;
constexpr int WO_AT = 16;
constexpr int WO_EARLY = 1;
constexpr int PACE = 656;
constexpr int LEAD_NS = 1370;
constexpr int GATE_X = 25;
constexpr int POLL_NS = 300;
constexpr int ALPHA16 = 4;
constexpr int GU_NS = 4330;
constexpr int W2_NS = 5560;
constexpr int GB_LEAD = 360;
constexpr int NQ = 8;
constexpr int PROBES = 6;
constexpr int PROBE_NS = 1000;
constexpr int EARLY_NS = 800;
constexpr int NW = 4;
constexpr int HEAD_TID = 256;
constexpr int N_WMOD = 0, N_WQ = 2, N_K = 6, N_V = N_K + NT, N_WO = N_V + WO_AT, N_V2 = N_WO + WO_EARLY, N_WO2 = N_V + NT + WO_EARLY, N_FFN = N_V + NT + 4;
constexpr int N_GATE = N_V + GATE_X + WO_EARLY;
constexpr int THREADS = 320;
constexpr int N_MOD_CTA = 80;
#define SPIN_LIMIT_S "4194304"
constexpr unsigned SPIN_LIMIT = 1u << 22;

constexpr int SM_RING = 0;
constexpr int SM_P = STAGES * TILE_BYTES;
constexpr int SM_PART = SM_P + WIN * 2;
constexpr int SM_OP = SM_PART + 8192;
constexpr int SM_Q = SM_OP + 2048;
constexpr int SM_RED = SM_Q + 256;
constexpr int SM_ML = SM_RED + 128;
constexpr int SM_PROG = SM_ML + 16;
constexpr int SM_SIDE = SM_PROG + 16;
constexpr int SM_BAR = SM_SIDE + 16;
constexpr int BAR_FULL = SM_BAR, BAR_EMPTY = SM_BAR + 8 * STAGES, BAR_XQ = SM_BAR + 16 * STAGES,
              BAR_XML = BAR_XQ + 8, BAR_XP = BAR_XQ + 16, BAR_FFN = BAR_XQ + 24;
constexpr int BAR_W2 = BAR_FFN + 8 * NQ;
constexpr int SMEM_BYTES = BAR_W2 + 8 * NW;
static_assert(SMEM_BYTES <= 232448, "shared memory");
__host__ __device__ constexpr uint32_t slot_addr(int n) { return SM_RING + (n % STAGES) * TILE_BYTES; }
__host__ __device__ constexpr uint32_t full_bar(int n) { return BAR_FULL + 8 * (n % STAGES); }
__host__ __device__ constexpr uint32_t empty_bar(int n) { return BAR_EMPTY + 8 * (n % STAGES); }
__host__ __device__ constexpr uint32_t tile_phase(int n) { return (n / STAGES) & 1; }
static_assert((N_FFN + 4) % STAGES + 2 <= STAGES && N_FFN % STAGES + 4 <= STAGES, "w1/w3 tiles and w2 tiles occupy consecutive slots");
static_assert(GATE_X >= WO_AT && N_GATE - STAGES < N_V2 && N_FFN + 5 - 2 * STAGES < N_WO && N_FFN + 5 - STAGES < N_WO2,
              "barrier parities the helper warp waits on are unambiguous after the rendezvous; the last wo tiles are not replaced");
__host__ __device__ constexpr int fill_tile(int j) { return j < K_FIRST ? N_K + j : j < K_FIRST + N_K ? j - K_FIRST : j; }

struct Ptrs {
    const __nv_bfloat16 *kwin, *x, *c;
    __nv_bfloat16* out;
};
struct Params {
    CUtensorMap m_wmod, m_wq, m_v, m_wo, m_w1, m_w3, m_w2, m_gb;
};

__device__ unsigned g_epoch;
__device__ __align__(128) uint2 g_mod[2][5 * D_ / 2];
__device__ __align__(256) unsigned char g_s[131072];
__device__ __forceinline__ unsigned long long s_line(int blk, int i) {
    return (((unsigned long long)g_s + 65535) & ~65535ull) + blk * 4096 + (i >> 1) * 1024 + (i & 1) * 256;
}
__device__ __forceinline__ int e1_blk(int r, int w) { return 2 * w + (r ^ (w & 1)); }
constexpr int S_OUT = 512, S_PROG = 128;
__device__ __align__(128) unsigned g_clear;

typedef unsigned long long u64;
__device__ __forceinline__ unsigned time_ns() {
    unsigned r;
    asm volatile("mov.u32 %0, %%globaltimer_lo;" : "=r"(r));
    return r;
}
__device__ __forceinline__ bool elect_one() {
    uint32_t r;
    asm volatile("{\n.reg .pred p;\nelect.sync _|p, 0xffffffff;\nselp.u32 %0, 1, 0, p;\n}" : "=r"(r));
    return r != 0;
}
#define PIN64(v) asm volatile("" : "+l"(v))

__device__ __forceinline__ void mbar_init(uint32_t bar, uint32_t cnt) {
    asm volatile("mbarrier.init.shared::cta.b64 [%0], %1;" :: "r"(bar), "r"(cnt) : "memory");
}
__device__ __forceinline__ void mbar_expect_tx(uint32_t bar, uint32_t bytes) {
    asm volatile("mbarrier.arrive.expect_tx.shared::cta.b64 _, [%0], %1;" :: "r"(bar), "r"(bytes) : "memory");
}
__device__ __forceinline__ void mbar_arrive(uint32_t bar) {
    asm volatile("mbarrier.arrive.shared::cta.b64 _, [%0];" :: "r"(bar) : "memory");
}
__device__ __forceinline__ void mbar_arrive_n(uint32_t bar, uint32_t n) {
    asm volatile("mbarrier.arrive.shared::cta.b64 _, [%0], %1;" :: "r"(bar), "r"(n) : "memory");
}
__device__ __forceinline__ void mbar_wait(uint32_t bar, uint32_t parity) {
    asm volatile("{\n.reg .pred p;\n.reg .u32 n;\nmov.u32 n, 0;\nW0:\n"
                 "mbarrier.try_wait.parity.shared::cta.b64 p, [%0], %1;\n@p bra W1;\n"
                 "add.u32 n, n, 1;\nsetp.lt.u32 p, n, " SPIN_LIMIT_S ";\n@p bra W0;\nW1:\n}"
                 :: "r"(bar), "r"(parity) : "memory");
}
__device__ __forceinline__ void mbar_wait_cluster(uint32_t bar, uint32_t parity) {
    asm volatile("{\n.reg .pred p;\n.reg .u32 n;\nmov.u32 n, 0;\nW0:\n"
                 "mbarrier.try_wait.parity.acquire.cluster.shared::cta.b64 p, [%0], %1;\n@p bra W1;\n"
                 "add.u32 n, n, 1;\nsetp.lt.u32 p, n, " SPIN_LIMIT_S ";\n@p bra W0;\nW1:\n}"
                 :: "r"(bar), "r"(parity) : "memory");
}
__device__ __forceinline__ void bulk_load(uint32_t dst, const void* src, uint32_t bytes, uint32_t bar, uint64_t pol) {
    asm volatile("cp.async.bulk.shared::cluster.global.mbarrier::complete_tx::bytes.L2::cache_hint [%0], [%1], %2, [%3], %4;"
                 :: "r"(dst), "l"(src), "r"(bytes), "r"(bar), "l"(pol) : "memory");
}
__device__ __forceinline__ void tma2d(uint32_t dst, const CUtensorMap* m, int c0, int c1, uint32_t bar) {
    asm volatile("cp.async.bulk.tensor.2d.shared::cluster.global.mbarrier::complete_tx::bytes [%0], [%1, {%3, %4}], [%2];"
                 :: "r"(dst), "l"(m), "r"(bar), "r"(c0), "r"(c1) : "memory");
}
__device__ __forceinline__ void tma2d_hint(uint32_t dst, const CUtensorMap* m, int c0, int c1, uint32_t bar, uint64_t pol) {
    asm volatile("cp.async.bulk.tensor.2d.shared::cluster.global.mbarrier::complete_tx::bytes.L2::cache_hint [%0], [%1, {%3, %4}], [%2], %5;"
                 :: "r"(dst), "l"(m), "r"(bar), "r"(c0), "r"(c1), "l"(pol) : "memory");
}
__device__ __forceinline__ void tma3d(uint32_t dst, const CUtensorMap* m, int c0, int c1, int c2, uint32_t bar) {
    asm volatile("cp.async.bulk.tensor.3d.shared::cluster.global.mbarrier::complete_tx::bytes [%0], [%1, {%3, %4, %5}], [%2];"
                 :: "r"(dst), "l"(m), "r"(bar), "r"(c0), "r"(c1), "r"(c2) : "memory");
}
__device__ __forceinline__ void tma4d(uint32_t dst, const CUtensorMap* m, int c0, int c3, uint32_t bar) {
    asm volatile("cp.async.bulk.tensor.4d.shared::cluster.global.mbarrier::complete_tx::bytes [%0], [%1, {%3, %5, %5, %4}], [%2];"
                 :: "r"(dst), "l"(m), "r"(bar), "r"(c0), "r"(c3), "r"(0) : "memory");
}
__device__ __forceinline__ void tma5d(uint32_t dst, const CUtensorMap* m, int c3, int c4, uint32_t bar) {
    asm volatile("cp.async.bulk.tensor.5d.shared::cluster.global.mbarrier::complete_tx::bytes [%0], [%1, {%5, %5, %5, %3, %4}], [%2];"
                 :: "r"(dst), "l"(m), "r"(bar), "r"(c3), "r"(c4), "r"(0) : "memory");
}
__device__ __forceinline__ uint32_t mapa(uint32_t addr, uint32_t rank) {
    uint32_t r;
    asm("mapa.shared::cluster.u32 %0, %1, %2;" : "=r"(r) : "r"(addr), "r"(rank));
    return r;
}
__device__ __forceinline__ void st_async_b32(uint32_t addr, uint32_t v, uint32_t bar) {
    asm volatile("st.async.weak.shared::cluster.mbarrier::complete_tx::bytes.b32 [%0], %1, [%2];" :: "r"(addr), "r"(v), "r"(bar) : "memory");
}
__device__ __forceinline__ void st_async_v2(uint32_t addr, float a, float b, uint32_t bar) {
    asm volatile("st.async.weak.shared::cluster.mbarrier::complete_tx::bytes.v2.f32 [%0], {%1, %2}, [%3];" :: "r"(addr), "f"(a), "f"(b), "r"(bar) : "memory");
}
__device__ __forceinline__ void st_async_v4(uint32_t addr, uint32_t a, uint32_t b, uint32_t c, uint32_t d, uint32_t bar) {
    asm volatile("st.async.weak.shared::cluster.mbarrier::complete_tx::bytes.v4.b32 [%0], {%1, %2, %3, %4}, [%5];"
                 :: "r"(addr), "r"(a), "r"(b), "r"(c), "r"(d), "r"(bar) : "memory");
}
template <int ID> __device__ __forceinline__ void bar_sync() { asm volatile("bar.sync %0, 288;" :: "n"(ID) : "memory"); }
template <int ID> __device__ __forceinline__ void bar_arrive() { asm volatile("bar.arrive %0, 288;" :: "n"(ID) : "memory"); }
__device__ __forceinline__ void cbar() { asm volatile("bar.sync 1, 256;" ::: "memory"); }

__device__ __forceinline__ uint4 ldg128(const void* p) {
    uint4 v;
    asm volatile("ld.global.nc.v4.u32 {%0,%1,%2,%3}, [%4];" : "=r"(v.x), "=r"(v.y), "=r"(v.z), "=r"(v.w) : "l"(p));
    return v;
}
__device__ __forceinline__ uint32_t ldg16(const void* p) {
    uint16_t v;
    asm volatile("ld.global.nc.u16 %0, [%1];" : "=h"(v) : "l"(p));
    return v;
}
__device__ __forceinline__ uint4 ld_strong128(unsigned long long p) {
    uint4 v;
    asm volatile("ld.relaxed.gpu.global.v4.b32 {%0,%1,%2,%3}, [%4];" : "=r"(v.x), "=r"(v.y), "=r"(v.z), "=r"(v.w) : "l"(p) : "memory");
    return v;
}
__device__ __forceinline__ uint2 ld_strong64(unsigned long long p) {
    uint2 v;
    asm volatile("ld.relaxed.gpu.global.v2.b32 {%0,%1}, [%2];" : "=r"(v.x), "=r"(v.y) : "l"(p) : "memory");
    return v;
}
__device__ __forceinline__ uint32_t ldg32(const void* p) {
    uint32_t v;
    asm volatile("ld.global.nc.u32 %0, [%1];" : "=r"(v) : "l"(p));
    return v;
}
struct Pkt2 { u64 a, b; };
__device__ __forceinline__ uint32_t lo32(u64 v) { return (uint32_t)v; }
__device__ __forceinline__ uint32_t hi32(u64 v) { return (uint32_t)(v >> 32); }
__device__ __forceinline__ Pkt2 ld_pkt2(const void* p) {
    Pkt2 r;
    asm volatile("ld.relaxed.gpu.global.v2.b64 {%0,%1}, [%2];" : "=l"(r.a), "=l"(r.b) : "l"(p) : "memory");
    return r;
}
__device__ __forceinline__ bool pkt_ok(const Pkt2& r, uint32_t tag) { return hi32(r.a) == tag && hi32(r.b) == tag; }
__device__ __forceinline__ void st_pkt(u64 p, uint32_t data, uint32_t tag) {
    asm volatile("{\n.reg .b64 v;\nmov.b64 v, {%1, %2};\nst.relaxed.gpu.global.b64 [%0], v;\n}" :: "l"(p), "r"(data), "r"(tag) : "memory");
}
__device__ __forceinline__ uint4 lds128(uint32_t a) {
    uint4 v;
    asm volatile("ld.shared.v4.u32 {%0,%1,%2,%3}, [%4];" : "=r"(v.x), "=r"(v.y), "=r"(v.z), "=r"(v.w) : "r"(a) : "memory");
    return v;
}
__device__ __forceinline__ float4 lds128f(uint32_t a) {
    float4 v;
    asm volatile("ld.shared.v4.f32 {%0,%1,%2,%3}, [%4];" : "=f"(v.x), "=f"(v.y), "=f"(v.z), "=f"(v.w) : "r"(a) : "memory");
    return v;
}
__device__ __forceinline__ uint2 lds64(uint32_t a) {
    uint2 v;
    asm volatile("ld.shared.v2.u32 {%0,%1}, [%2];" : "=r"(v.x), "=r"(v.y) : "r"(a) : "memory");
    return v;
}
__device__ __forceinline__ float2 lds64f(uint32_t a) {
    float2 v;
    asm volatile("ld.shared.v2.f32 {%0,%1}, [%2];" : "=f"(v.x), "=f"(v.y) : "r"(a) : "memory");
    return v;
}
__device__ __forceinline__ float lds32f(uint32_t a) {
    float v;
    asm volatile("ld.shared.f32 %0, [%1];" : "=f"(v) : "r"(a) : "memory");
    return v;
}
__device__ __forceinline__ void sts64f(uint32_t a, float x, float y) {
    asm volatile("st.shared.v2.f32 [%0], {%1,%2};" :: "r"(a), "f"(x), "f"(y) : "memory");
}
__device__ __forceinline__ void sts128f(uint32_t a, float x, float y, float z, float w) {
    asm volatile("st.shared.v4.f32 [%0], {%1,%2,%3,%4};" :: "r"(a), "f"(x), "f"(y), "f"(z), "f"(w) : "memory");
}
__device__ __forceinline__ void sts32f(uint32_t a, float x) {
    asm volatile("st.shared.f32 [%0], %1;" :: "r"(a), "f"(x) : "memory");
}
__device__ __forceinline__ void sts128(uint32_t a, uint32_t x, uint32_t y, uint32_t z, uint32_t w) {
    asm volatile("st.shared.v4.u32 [%0], {%1,%2,%3,%4};" :: "r"(a), "r"(x), "r"(y), "r"(z), "r"(w) : "memory");
}
__device__ __forceinline__ void settle(uint32_t tag, uint32_t a, uint32_t x, uint32_t y, uint32_t z, uint32_t w) {
    asm volatile("{\n.reg .pred p;\nsetp.eq.u32 p, %0, 0;\n@p st.shared.v4.u32 [%1], {%2,%3,%4,%5};\n}" :: "r"(tag), "r"(a), "r"(x), "r"(y), "r"(z), "r"(w) : "memory");
}
__device__ __forceinline__ void settle(uint32_t tag, uint32_t a, const float4& v) {
    settle(tag, a, __float_as_uint(v.x), __float_as_uint(v.y), __float_as_uint(v.z), __float_as_uint(v.w));
}
__device__ __forceinline__ void sts16(uint32_t a, uint32_t x) {
    asm volatile("st.shared.u16 [%0], %1;" :: "r"(a), "h"((uint16_t)x) : "memory");
}
__device__ __forceinline__ void ldsm4t(uint32_t a, uint32_t (&r)[4]) {
    asm volatile("ldmatrix.sync.aligned.m8n8.x4.trans.shared.b16 {%0,%1,%2,%3}, [%4];"
                 : "=r"(r[0]), "=r"(r[1]), "=r"(r[2]), "=r"(r[3]) : "r"(a) : "memory");
}
__device__ __forceinline__ void mma(float (&c)[4], uint32_t a0, uint32_t a1, uint32_t a2, uint32_t a3, uint32_t b0, uint32_t b1) {
    asm volatile("mma.sync.aligned.m16n8k16.row.col.f32.bf16.bf16.f32 {%0,%1,%2,%3}, {%4,%5,%6,%7}, {%8,%9}, {%0,%1,%2,%3};"
                 : "+f"(c[0]), "+f"(c[1]), "+f"(c[2]), "+f"(c[3]) : "r"(a0), "r"(a1), "r"(a2), "r"(a3), "r"(b0), "r"(b1));
}
__device__ __forceinline__ void mma4(float (&c)[4], const uint32_t (&a)[4], uint32_t b0, uint32_t b1) { mma(c, a[0], a[1], a[2], a[3], b0, b1); }
__device__ __forceinline__ float sel(uint32_t c, float a, float b) {
    float r;
    asm("{\n.reg .pred p;\nsetp.ne.u32 p, %3, 0;\nselp.f32 %0, %1, %2, p;\n}" : "=f"(r) : "f"(a), "f"(b), "r"(c));
    return r;
}
__device__ __forceinline__ float bf_lo(uint32_t v) { return __uint_as_float(v << 16); }
__device__ __forceinline__ float bf_hi(uint32_t v) { return __uint_as_float(v & 0xffff0000u); }
__device__ __forceinline__ uint32_t pack2(float lo, float hi) {
    uint32_t r;
    asm("cvt.rn.bf16x2.f32 %0, %1, %2;" : "=r"(r) : "f"(hi), "f"(lo));
    return r;
}
__device__ __forceinline__ float rbf(float x) { return __uint_as_float(pack2(0.f, x)); }
__device__ __forceinline__ uint32_t hadd2(uint32_t a, uint32_t b) { uint32_t r; asm("add.rn.bf16x2 %0, %1, %2;" : "=r"(r) : "r"(a), "r"(b)); return r; }
__device__ __forceinline__ uint32_t hsub2(uint32_t a, uint32_t b) { uint32_t r; asm("sub.rn.bf16x2 %0, %1, %2;" : "=r"(r) : "r"(a), "r"(b)); return r; }
__device__ __forceinline__ uint32_t hmul2(uint32_t a, uint32_t b) { uint32_t r; asm("mul.rn.bf16x2 %0, %1, %2;" : "=r"(r) : "r"(a), "r"(b)); return r; }
__device__ __forceinline__ uint32_t hfma2(uint32_t a, uint32_t b, uint32_t c) { uint32_t r; asm("fma.rn.bf16x2 %0, %1, %2, %3;" : "=r"(r) : "r"(a), "r"(b), "r"(c)); return r; }
__device__ __forceinline__ uint32_t selu(uint32_t c, uint32_t a, uint32_t b) { return __float_as_uint(sel(c, __uint_as_float(a), __uint_as_float(b))); }
constexpr uint32_t ONE2 = 0x3f803f80u;
__device__ __forceinline__ float silu_f(float x) {
    float e, r;
    asm("ex2.approx.ftz.f32 %0, %1;" : "=f"(e) : "f"(x * -1.4426950408889634f));
    asm("rcp.approx.ftz.f32 %0, %1;" : "=f"(r) : "f"(1.0f + e));
    return x * r;
}
__device__ __forceinline__ float rcp_sd(float m2) {
    float s, r;
    asm("sqrt.approx.ftz.f32 %0, %1;" : "=f"(s) : "f"(rbf(rbf(m2 * (1.0f / D_)) + 1e-5f)));
    asm("rcp.approx.ftz.f32 %0, %1;" : "=f"(r) : "f"(rbf(s)));
    return r;
}
__device__ __forceinline__ uint32_t ln_mod2(uint32_t x, uint32_t mean2, float rsd, uint32_t c1, uint32_t sh) {
    const uint32_t d = hsub2(x, mean2);
    return hadd2(hmul2(pack2(bf_lo(d) * rsd, bf_hi(d) * rsd), c1), sh);
}
__device__ __forceinline__ int pair_pos(int j) { return 2 * (j & 3) + (j >> 2); }

__global__ void __cluster_dims__(2, 1, 1) __launch_bounds__(THREADS, 1)
fused_decode_kernel(const __grid_constant__ Ptrs q_, const __grid_constant__ Params p) {
    extern __shared__ __align__(1024) unsigned char smem[];
    unsigned t_top;
    asm volatile("mov.u32 %0, %%globaltimer_lo;" : "=r"(t_top));
    const int tid = threadIdx.x;
    uint32_t z0;
    asm("and.b32 %0, %1, 1024;" : "=r"(z0) : "r"(tid));
    const char* kw = *(const char* const*)((const char*)&q_.kwin + z0);
    const uint32_t sb = (uint32_t)__cvta_generic_to_shared(smem);
    auto place = [](int cl) { return cl < 4 ? 8 * cl + 39 : cl - 4 + max((cl * 37 - 36 * 37) >> 8, 0); };
    uint32_t z2;
    asm("and.b32 %0, %1, 2048;" : "=r"(z2) : "r"(tid));
    const int cv = blockIdx.x + z2, pw = place(cv >> 1);
    static_assert(SK * DH * 2 == 1 << 22 && TILE_BYTES == 1 << 14, "koff");
    const char* kp;
    auto set_kp = [&](uint32_t off) {
        asm volatile("{\n.reg .u32 lo, hi;\nmov.b64 {lo, hi}, %1;\nadd.cc.u32 lo, lo, %2;\naddc.u32 hi, hi, 0;\nmov.b64 %0, {lo, hi};\n}"
                     : "=l"(kp) : "l"(kw), "r"(off));
    };
    uint64_t pol;
    asm("createpolicy.fractional.L2::evict_first.b64 %0, 1.0;" : "=l"(pol));
    auto fill_k = [&](int n) {
        mbar_expect_tx(sb + full_bar(n), TILE_BYTES);
        bulk_load(sb + slot_addr(n), kp + (n - N_K) * 2 * TILE_BYTES, TILE_BYTES, sb + full_bar(n), pol);
    };
    static_assert(K_FIRST >= 1, "head block starts with K tile 0");
    if (tid + (sb >> 28) == HEAD_TID) {
        mbar_init(sb + full_bar(N_K), 1);
        set_kp(((pw & 7) << 22) | ((pw & 8) << 24) | ((pw & 48) << 21) | ((cv & 1) << 14));
        bulk_load(sb + slot_addr(N_K), kp, TILE_BYTES, sb + full_bar(N_K), pol);
        mbar_expect_tx(sb + full_bar(N_K), TILE_BYTES);
#pragma unroll
        for (int j = 1; j < K_FIRST; j++) { mbar_init(sb + full_bar(N_K + j), 1); fill_k(N_K + j); }
    }
    __syncwarp();
    const int cta = blockIdx.x, rank = cta & 1, pv = place(cta >> 1);
    const int b = (pv >> 3) & 1, h = (pv & 7) | ((pv >> 1) & 24), bh = 32 * b + h;
    const int mc = 2 * pv + rank;
    auto first_fill = [&](int j) {
        const int n = fill_tile(j);
        if (n >= N_K) {
            fill_k(n);
        } else if (n >= N_WQ) {
            mbar_expect_tx(sb + full_bar(n), TILE_BYTES);
            tma2d(sb + slot_addr(n), &p.m_wq, h * DH + 64 * rank, 128 * (n - N_WQ), sb + full_bar(n));
        } else if (mc < N_MOD_CTA) {
            mbar_expect_tx(sb + full_bar(n), TILE_BYTES);
            tma2d(sb + slot_addr(n), &p.m_wmod, 32 * mc, 256 * n, sb + full_bar(n));
        } else {
            mbar_arrive(sb + full_bar(n));
        }
    };
    if (tid == HEAD_TID) {
#pragma unroll
        for (int j = K_FIRST; j < FIRST_N; j++) mbar_init(sb + full_bar(fill_tile(j)), 1);
#pragma unroll
        for (int j = K_FIRST; j < FIRST_N; j++) first_fill(j);
        asm volatile("fence.mbarrier_init.release.cluster;" ::: "memory");
    }
    __syncwarp();
    const int role = cta / 3;
    const bool is_gu = cta == 3 * role, is_gb = cta == 3 * role + 1 && role < 32;
    if (tid >= 288) {
        const unsigned t_start = t_top;
        asm volatile("barrier.cluster.arrive.relaxed.aligned;" ::: "memory");
        unsigned tag;
        asm volatile("ld.relaxed.gpu.global.u32 %0, [%1];" : "=r"(tag) : "l"(&g_epoch) : "memory");
        tag += 1;
        if (cta == NCTA - 1) {
#pragma unroll 2
            for (int i = tid - 288; i < 128 * 8; i += 32) {
                uint4* q = reinterpret_cast<uint4*>(s_line(i >> 6, (i >> 3) & 7)) + (i & 7);
                const uint32_t v = (i & 48) == 48 ? ~0u : 0u;
                q[0] = make_uint4(v, v, v, v);
                q[8] = q[32] = q[40] = make_uint4(0u, 0u, 0u, 0u);
            }
            __syncwarp();
            asm volatile("fence.acq_rel.gpu;" ::: "memory");
            if (tid == 288) asm volatile("st.relaxed.gpu.global.u32 [%0], %1;" :: "l"(&g_clear), "r"(tag) : "memory");
        }
        asm volatile("barrier.cluster.wait.acquire.aligned;" ::: "memory");
        mbar_wait_cluster(sb + BAR_XQ, 0);
        for (uint32_t n = 0; n < SPIN_LIMIT; n++) {
            unsigned c;
            asm volatile("ld.relaxed.gpu.global.u32 %0, [%1];" : "=r"(c) : "l"(&g_clear) : "memory");
            if (c == tag) break;
        }
        asm volatile("fence.acq_rel.gpu;" ::: "memory");
        asm volatile("st.volatile.shared.u32 [%0], %1;" :: "r"(sb + SM_SIDE), "r"(0) : "memory");
        asm volatile("bar.sync 2, 288;" ::: "memory");
        if (elect_one()) {
            asm volatile("prefetch.tensormap [%0];" :: "l"(is_gu ? &p.m_w1 : &p.m_gb) : "memory");
            asm volatile("prefetch.tensormap [%0];" :: "l"(&p.m_w3) : "memory");
            asm volatile("prefetch.tensormap [%0];" :: "l"(&p.m_w2) : "memory");
            const int issue = ((4 * N_GATE - 11 - 2 * WO_EARLY) * PACE >> 2) - LEAD_NS;
            unsigned now, c = 0, best[2] = {~0u, ~0u}, np = is_gu ? 0 : PROBES;
            auto probe = [&]() {
                const int k = np >> 1, i = (role >> 3) + 2 * k;
                const u64 a = (s_line(e1_blk(0, role & 7), i < 6 ? i : i - 6) + (k ? 512 * k - 384 : 0)) ^ ((np & 1) << 12);
                unsigned v, c0, c1 = 0;
                asm volatile("mov.u32 %0, %%clock;" : "=r"(c0));
                asm volatile("ld.relaxed.gpu.global.u32 %0, [%1];" : "=r"(v) : "l"(a) : "memory");
                asm volatile("{\n.reg .pred p;\nsetp.ne.u32 p, %1, 0xffffffff;\n@p mov.u32 %0, %%clock;\n}" : "+r"(c1) : "r"(v));
                if (np & 1) best[1] = min(best[1], c1 - c0); else best[0] = min(best[0], c1 - c0);
                np++;
                if (!(np & 1)) asm volatile("st.volatile.shared.u32 [%0], %1;" :: "r"(sb + SM_SIDE), "r"(best[0] <= best[1] ? 0 : 4096) : "memory");
            };
#pragma unroll 1
            while (np < PROBES) {
                now = time_ns();
                if ((int)(now - t_start) >= issue + EARLY_NS) break;
                probe();
            }
            mbar_wait(sb + full_bar(N_GATE), tile_phase(N_GATE));
            now = time_ns();
            const unsigned mine = (1u << 24) + min(now - t_start, 100000u);
            const u64 prog = s_line(0, 7) + S_PROG;
            asm volatile("red.relaxed.gpu.global.add.u32 [%0], %1;" :: "l"(prog), "r"(mine) : "memory");
            if (is_gu || is_gb) {
#pragma unroll
                for (int i = 0; i < 6; i++) mbar_wait(sb + empty_bar(N_FFN + i), tile_phase(N_FFN + i) ^ 1);
#pragma unroll
                for (int i = 0; i < NQ; i++) mbar_expect_tx(sb + BAR_FFN + 8 * i, is_gu ? 65536 / NQ : 8192);
#pragma unroll
                for (int i = 0; i < NW; i++) mbar_expect_tx(sb + BAR_W2 + 8 * i, 32768 / NW);
                unsigned due = 0, next = now;
                constexpr unsigned full = (unsigned)NCTA << 24;
                asm volatile("st.volatile.shared.u32 [%0], %1;" :: "r"(sb + SM_PROG), "r"(mine) : "memory");
#pragma unroll 1
                for (uint32_t n = 0; n < 4096; n++) {
                    unsigned v;
                    asm volatile("ld.volatile.shared.u32 %0, [%1];" : "=r"(v) : "r"(sb + SM_PROG) : "memory");
                    if (v > c) {
                        c = v;
                        const int arr = (int)__fdividef((float)(c & 0xffffffu), (float)(c >> 24));
                        due = arr - ((arr - issue) * ALPHA16 >> 4) + (is_gb ? W2_NS - GB_LEAD : GU_NS);
                    }
                    now = time_ns();
                    if (now - t_start + PROBE_NS >= due) np = PROBES;
                    if ((c >= full && np == PROBES) || now - t_start >= due) break;
                    if ((int)(now - next) >= 0 && c < full) {
                        asm volatile("cp.async.cg.shared.global [%0], [%1], 16;" :: "r"(sb + SM_PROG), "l"(prog) : "memory");
                        next = now + POLL_NS;
                    }
                    if (np < PROBES) probe();
                }
#pragma unroll 1
                for (uint32_t n = 0; n < 1024 && now - t_start < due; n++) now = time_ns();
                if (is_gu) {
#pragma unroll
                    for (int i = 0; i < 2 * NQ; i++) {
                        const int q = i >> 1, r0 = q * (512 / NQ);
                        tma4d(sb + slot_addr(N_FFN) + (r0 >> 8) * 2 * TILE_BYTES + (i & 1) * TILE_BYTES + (r0 & 255) * 64, (i & 1) ? &p.m_w3 : &p.m_w1, 32 * role, r0 / 16, sb + BAR_FFN + 8 * q);
                    }
#pragma unroll 1
                    for (uint32_t n = 0; n < 1024 && now - t_start < due + (W2_NS - GU_NS); n++) now = time_ns();
                    const int f = best[0] <= best[1] ? NW / 2 : 0;
#pragma unroll
                    for (int i = 0; i < NW; i++) tma5d(sb + slot_addr(N_FFN + 4) + (i ^ f) * (32768 / NW), &p.m_w2, 2 * role, (i ^ f) * (8 / NW), sb + BAR_W2 + 8 * (i ^ f));
                } else {
                    tma2d(sb + slot_addr(N_FFN), &p.m_gb, 5 * D_ + 16 * role, 0, sb + BAR_FFN);
                    tma2d(sb + slot_addr(N_FFN) + 8192, &p.m_gb, 5 * D_ + 16 * role, 256, sb + BAR_FFN + 8);
                }
                asm volatile("cp.async.wait_all;" ::: "memory");
            }
        }
        __syncwarp();
        if (is_gu) {
            const int lane = tid & 31;
            auto sum8 = [&](uint32_t a, int stride) {
                float4 u[8];
#pragma unroll
                for (int i = 0; i < 8; i++) u[i] = lds128f(a + i * stride);
                return make_float4(((u[0].x + u[1].x) + (u[2].x + u[3].x)) + ((u[4].x + u[5].x) + (u[6].x + u[7].x)),
                                   ((u[0].y + u[1].y) + (u[2].y + u[3].y)) + ((u[4].y + u[5].y) + (u[6].y + u[7].y)),
                                   ((u[0].z + u[1].z) + (u[2].z + u[3].z)) + ((u[4].z + u[5].z) + (u[6].z + u[7].z)),
                                   ((u[0].w + u[1].w) + (u[2].w + u[3].w)) + ((u[4].w + u[5].w) + (u[6].w + u[7].w)));
            };
            uint32_t h_st = sb + SM_Q + (((lane & 1) * 4 + ((lane >> 2) & 3)) * 4 + (lane & 2) + (lane >> 4)) * 4;
            bar_sync<3>();
            const float4 C = sum8(sb + SM_P + lane * 16, 1024), S = sum8(sb + SM_P + 512 + lane * 16, 1024);
            const uint32_t st_ld = sb + SM_RED + (lane & 1) * 64;
            settle(tag, sb + SM_OP, C); settle(tag, sb + SM_OP, S); settle(tag, sb + SM_OP, h_st, st_ld, 0, 0);
            bar_sync<4>();
            const float4 r0 = lds128f(st_ld), r1 = lds128f(st_ld + 16), r2 = lds128f(st_ld + 32), r3 = lds128f(st_ld + 48);
            const float4 Y = sum8(sb + SM_PART + lane * 16, 512);
            const float e1 = r0.z - r0.x, e2 = r1.x - r0.x, e3 = r1.z - r0.x, e4 = r2.x - r0.x, e5 = r2.z - r0.x, e6 = r3.x - r0.x, e7 = r3.z - r0.x;
            const float se = ((e1 + e2) + (e3 + e4)) + ((e5 + e6) + e7);
            const float ee = (fmaf(e1, e1, e2 * e2) + fmaf(e3, e3, e4 * e4)) + fmaf(e5, e5, fmaf(e6, e6, e7 * e7));
            const float sq = ((r0.y + r0.w) + (r1.y + r1.w)) + ((r2.y + r2.w) + (r3.y + r3.w));
            const float rsd = rcp_sd(fmaf(se * (-1.0f / D_), se, fmaf(ee, 1.0f / 64, sq))), mu = -rbf(fmaf(r0.x, 8.0f, se) * (1.0f / D_));
            const uint32_t gr = pack2(fmaf(rsd, fmaf(mu, C.x, Y.x), S.x), fmaf(rsd, fmaf(mu, C.z, Y.z), S.z));
            const uint32_t ur = pack2(fmaf(rsd, fmaf(mu, C.y, Y.y), S.y), fmaf(rsd, fmaf(mu, C.w, Y.w), S.w));
            const uint32_t hv = hmul2(pack2(silu_f(bf_lo(gr)), silu_f(bf_hi(gr))), ur);
            sts32f(h_st, __uint_as_float(hv));
            bar_arrive<5>();
            if (role == 0 && lane == 0) g_epoch = tag;
        }
        return;
    }
    if (tid >= 256) {
        set_kp(bh * (SK * DH * 2) + rank * TILE_BYTES);
        const unsigned t_start = t_top;
        auto pace = [&](int q4) {
            const int due = (q4 * PACE >> 2) - LEAD_NS;
            unsigned now, n = 0;
            do { now = time_ns(); } while ((int)(now - t_start) < due && ++n < 256);
        };
        if (tid == 256) {
#pragma unroll
            for (int j = FIRST_N; j < STAGES; j++) mbar_init(sb + full_bar(fill_tile(j)), 1);
#pragma unroll
            for (int s = 0; s < STAGES; s++) mbar_init(sb + BAR_EMPTY + 8 * s, 8);
            mbar_init(sb + BAR_XQ, 1); mbar_init(sb + BAR_XML, 1); mbar_init(sb + BAR_XP, 1);
#pragma unroll
            for (int i = 0; i < NQ + NW; i++) mbar_init(sb + BAR_FFN + 8 * i, 1);
            mbar_expect_tx(sb + BAR_XQ, 256); mbar_expect_tx(sb + BAR_XML, 8); mbar_expect_tx(sb + BAR_XP, WIN);
            asm volatile("fence.mbarrier_init.release.cluster;" ::: "memory");
            asm volatile("fence.proxy.async.shared::cta;" ::: "memory");
        }
        __syncwarp();
        asm volatile("barrier.cluster.arrive.relaxed.aligned;" ::: "memory");
        if (elect_one()) {
#pragma unroll
            for (int j = FIRST_N; j < STAGES; j++) {
                pace(j <= K_FIRST ? 4 * j : j <= K_FIRST + 2 ? 4 * K_FIRST + 5 * (j - K_FIRST) / 2 :
                     j <= K_FIRST + 6 ? 4 * K_FIRST + 5 + 2 * (j - K_FIRST - 2) : 4 * j - 11);
                first_fill(j);
            }
        }
        __syncwarp();
        asm volatile("barrier.cluster.wait.acquire.aligned;" ::: "memory");
        if (elect_one()) {
            asm volatile("prefetch.tensormap [%0];" :: "l"(&p.m_v) : "memory");
            asm volatile("prefetch.tensormap [%0];" :: "l"(&p.m_wo) : "memory");
            int s = 0, ph = 0;
#pragma unroll 1
            for (int n = STAGES; n < N_FFN; n++) {
                const uint32_t dst = sb + SM_RING + s * TILE_BYTES, bar = sb + BAR_FULL + 8 * s;
                mbar_wait(sb + BAR_EMPTY + 8 * s, ph);
                mbar_expect_tx(bar, TILE_BYTES);
                pace(n < N_WO ? 4 * n - 11 : n < N_V2 ? 2 * (N_WO + n) - 11 : n < N_WO2 ? 4 * n - 11 - 2 * WO_EARLY : 2 * (N_WO2 + n - WO_EARLY) - 11);
                if (n < N_V) bulk_load(dst, kp + (n - N_K) * 2 * TILE_BYTES, TILE_BYTES, bar, pol);
                else if (n >= N_WO2 || (n >= N_WO && n < N_V2)) tma3d(dst, &p.m_wo, 0, h * DH + 64 * rank + 16 * (n - (n < N_V2 ? N_WO : N_V + NT)), 0, bar);
                else tma2d_hint(dst, &p.m_v, 64 * rank, bh * SK + (SK - WIN) + 128 * (n - (n < N_WO ? N_V : N_V + WO_EARLY)), bar, pol);
                if (++s == STAGES) { s = 0; ph ^= 1; }
            }
        }
        return;
    }

    const unsigned t_c = t_top;
    const int lane = tid & 31, w = tid >> 5, g = lane >> 2, t = lane & 3;
    const int hgrp = 4 * w + (g & 3);
    const int vb = g >> 2;
    const uint32_t cv0 = ldg32(q_.c + vb * D_ + 16 * hgrp + 2 * t), cv1 = ldg32(q_.c + vb * D_ + 16 * hgrp + 8 + 2 * t);
    unsigned tag;
    asm volatile("ld.relaxed.gpu.global.u32 %0, [%1];" : "=r"(tag) : "l"(&g_epoch) : "memory");
    const uint4 xa = ldg128(q_.x + b * D_ + 16 * lane), xb = ldg128(q_.x + b * D_ + 16 * lane + 8);
    const uint32_t xh0 = ldg32(q_.x + b * D_ + 16 * hgrp + 2 * t), xh1 = ldg32(q_.x + b * D_ + 16 * hgrp + 8 + 2 * t);
    asm volatile("barrier.cluster.arrive.relaxed.aligned;" ::: "memory");
#pragma unroll 1
    for (uint32_t n = t_c; n < 2; n++) asm volatile("nanosleep.u32 1;" ::: "memory");
    const int grp = w >> 2, sub = w & 3;
    const int lrow = (lane & 7) + 8 * (lane >> 4);
    const int lch = (lane >> 3) & 1;
    const int ob = lane >> 4;
    const uint32_t t1 = t & 1, t2 = t & 2;
    const int gsrc = 16 * (g & 1) + t;
    const uint32_t sw128 = lrow * 128 + ((lch ^ (lrow & 7)) << 4);
    uint32_t A[16][4];

    const uint32_t sc0 = pack2(silu_f(bf_lo(cv0)), silu_f(bf_hi(cv0))), sc1 = pack2(silu_f(bf_lo(cv1)), silu_f(bf_hi(cv1)));
    tag += 1;
    asm volatile("barrier.cluster.wait.acquire.aligned;" ::: "memory");
    mbar_wait(sb + BAR_FULL + 8 * (N_WMOD + grp), 0);
    if (mc < N_MOD_CTA) {
        const uint32_t tb = sb + SM_RING + (N_WMOD + grp) * TILE_BYTES + (64 * sub + lrow) * 64;
#pragma unroll
        for (int i = 0; i < 8; i++)
            ldsm4t(tb + (i >> 1) * 1024 + (((2 * (i & 1) + lch) ^ ((lrow >> 1) & 3)) << 4), A[i]);
        float acc[2][4] = {{0.f, 0.f, 0.f, 0.f}, {0.f, 0.f, 0.f, 0.f}};
#pragma unroll
        for (int s = 0; s < 4; s++) {
            const uint32_t b0 = __shfl_sync(~0u, sc0, 4 * s + gsrc), b1 = __shfl_sync(~0u, sc1, 4 * s + gsrc);
            mma4(acc[0], A[2 * s], b0, b1);
            mma4(acc[1], A[2 * s + 1], b0, b1);
        }
        sts32f(sb + SM_P + (w * 64 + 8 * t + g) * 4, sel(t2, sel(t1, acc[1][2], acc[1][0]), sel(t1, acc[0][2], acc[0][0])));
        sts32f(sb + SM_P + (w * 64 + 32 + 8 * t + g) * 4, sel(t2, sel(t1, acc[1][3], acc[1][1]), sel(t1, acc[0][3], acc[0][1])));
        cbar();
        if (w == 0) {
            const bool adj = mc < 32;
            const uint32_t a0 = sb + SM_P + (adj ? 2 * lane : ob * 32 + (lane & 1) * 16 + ((lane >> 1) & 7)) * 4, a1 = a0 + (adj ? 4 : 32);
            float2 sum = make_float2(0.f, 0.f);
#pragma unroll
            for (int i = 0; i < 8; i++) { sum.x += lds32f(a0 + i * 256); sum.y += lds32f(a1 + i * 256); }
            st_pkt((u64)&g_mod[ob][16 * mc + (adj ? (lane & 8) + pair_pos(lane & 7) : lane & 15)], pack2(sum.x, sum.y), tag);
        }
    }
    __syncwarp();
    if (lane == 0) mbar_arrive_n(sb + BAR_EMPTY + 8 * (N_WMOD + grp), 2);

    {
        const uint2* mp = &g_mod[b][vb * 256 + 8 * hgrp + 2 * t];
        const uint32_t ms = sb + SM_PART + tid * 16;
        auto fetch_mod = [&](uint32_t k) {
            asm volatile("cp.async.cg.shared.global [%0], [%1], 16;\ncp.async.commit_group;" :: "r"(ms + k), "l"(mp) : "memory");
        };
        fetch_mod(0);
        float xs[16] = {bf_lo(xa.x), bf_hi(xa.x), bf_lo(xa.y), bf_hi(xa.y), bf_lo(xa.z), bf_hi(xa.z), bf_lo(xa.w), bf_hi(xa.w),
                        bf_lo(xb.x), bf_hi(xb.x), bf_lo(xb.y), bf_hi(xb.y), bf_lo(xb.z), bf_hi(xb.z), bf_lo(xb.w), bf_hi(xb.w)};
        float s = 0.f;
#pragma unroll
        for (int i = 0; i < 16; i++) s += xs[i];
#pragma unroll
        for (int m = 1; m < 32; m <<= 1) s += __shfl_xor_sync(~0u, s, m);
        const float mean = s * (1.0f / D_);
        float q = 0.f;
#pragma unroll
        for (int i = 0; i < 16; i++) q += (xs[i] - mean) * (xs[i] - mean);
#pragma unroll
        for (int m = 1; m < 32; m <<= 1) q += __shfl_xor_sync(~0u, q, m);
        const uint32_t mean2 = pack2(mean, mean);
        const float rsd = rcp_sd(q);

        mbar_wait(sb + BAR_FULL + 8 * (N_WQ + (w >> 1)), 0);
        const uint32_t tb = sb + SM_RING + (N_WQ + (w >> 1)) * TILE_BYTES + (w & 1) * 8192;
#pragma unroll
        for (int i = 0; i < 16; i++) ldsm4t(tb + (i >> 2) * 2048 + (sw128 ^ ((i & 3) * 32)), A[i]);
        __syncwarp();
        if (lane == 0) mbar_arrive_n(sb + BAR_EMPTY + 8 * (N_WQ + (w >> 1)), 4);

        Pkt2 m;
        for (uint32_t n = 0, k = 0; n < SPIN_LIMIT; n++) {
            fetch_mod(k ^ 4096);
            asm volatile("cp.async.wait_group 1;" ::: "memory");
            const uint4 u = lds128(ms + k);
            m.a = u.x | (u64)u.y << 32; m.b = u.z | (u64)u.w << 32;
            if (__all_sync(~0u, pkt_ok(m, tag))) break;
            k ^= 4096;
        }
        const uint32_t ca0 = __shfl_xor_sync(~0u, lo32(m.a), 16), ca1 = __shfl_xor_sync(~0u, lo32(m.b), 16);
        const uint32_t v0 = ln_mod2(xh0, mean2, rsd, hadd2(ONE2, ca0), lo32(m.a));
        const uint32_t v1 = ln_mod2(xh1, mean2, rsd, hadd2(ONE2, ca1), lo32(m.b));
        float acc[4][4];
#pragma unroll
        for (int i = 0; i < 4; i++) { acc[i][0] = acc[i][1] = acc[i][2] = acc[i][3] = 0.f; }
#pragma unroll
        for (int s4 = 0; s4 < 4; s4++) {
            const uint32_t b0 = __shfl_sync(~0u, v0, 4 * s4 + t), b1 = __shfl_sync(~0u, v1, 4 * s4 + t);
#pragma unroll
            for (int i = 0; i < 4; i++) mma4(acc[i], A[4 * s4 + i], b0, b1);
        }
        sts32f(sb + SM_OP + (w * 64 + 16 * t + g) * 4, sel(t2, sel(t1, acc[3][0], acc[2][0]), sel(t1, acc[1][0], acc[0][0])));
        sts32f(sb + SM_OP + (w * 64 + 16 * t + 8 + g) * 4, sel(t2, sel(t1, acc[3][2], acc[2][2]), sel(t1, acc[1][2], acc[0][2])));
        cbar();
        if (w == 0) {
            float2 sum = make_float2(0.f, 0.f);
#pragma unroll
            for (int i = 0; i < 8; i++) { const float2 u = lds64f(sb + SM_OP + (i * 64 + 2 * lane) * 4); sum.x += u.x; sum.y += u.y; }
            const uint32_t v = pack2(sum.x, sum.y), a = sb + SM_Q + rank * 128 + lane * 4;
            st_async_b32(mapa(a, rank ^ 1), v, mapa(sb + BAR_XQ, rank ^ 1));
            st_async_b32(mapa(a, rank), v, mapa(sb + BAR_XQ, rank));
        }
        mbar_wait_cluster(sb + BAR_XQ, 0);
    }

    Pkt2 mga, msb, mcb;
    uint32_t tx0, tx1;
    const uint2* tmp = &g_mod[ob][32 * w + 2 * (lane & 15)];
    {
        uint4 Q[4];
        uint32_t koff[4];
#pragma unroll
        for (int i = 0; i < 4; i++) {
            const int ch = t + 4 * (i ^ (g & 1));
            Q[i] = lds128(sb + SM_Q + ch * 16);
            koff[i] = (sub * 16 + g) * 256 + ch * 16;
        }
        float mx = -INFINITY;
        int stage = N_K + grp, phase = 0;
#pragma unroll 1
        for (int it = 0; it < NT / 2; it++) {
            const uint32_t tb = sb + SM_RING + stage * TILE_BYTES;
            mbar_wait(sb + BAR_FULL + 8 * stage, phase);
            uint4 Ka[4], Kb[4];
#pragma unroll
            for (int i = 0; i < 4; i++) { Ka[i] = lds128(tb + koff[i]); Kb[i] = lds128(tb + koff[i] + 2048); }
            float c0[4] = {0.f, 0.f, 0.f, 0.f}, c1[4] = {0.f, 0.f, 0.f, 0.f};
#pragma unroll
            for (int i = 0; i < 4; i++) {
                mma(c0, Ka[i].x, Kb[i].x, Ka[i].y, Kb[i].y, Q[i].x, Q[i].y);
                mma(c1, Ka[i].z, Kb[i].z, Ka[i].w, Kb[i].w, Q[i].z, Q[i].w);
            }
            __syncwarp();
            if (lane == 0) mbar_arrive_n(sb + BAR_EMPTY + 8 * stage, 2);
            const float lo = (g & 1) ? c0[1] + c1[1] : c0[0] + c1[0];
            const float hi = (g & 1) ? c0[3] + c1[3] : c0[2] + c1[2];
            const float sc = rbf(rbf(t1 ? hi : lo) * 0.08838834764831845f);
            mx = fmaxf(mx, sc);
            if (t < 2) sts16(sb + SM_P + ((2 * it + grp) * 128 + rank * 64 + sub * 16 + 4 * (g >> 1) + 2 * t + (g & 1)) * 2, __float_as_uint(sc) >> 16);
            stage += 2;
            if (stage >= STAGES) { stage -= STAGES; phase ^= 1; }
        }

        mga = ld_pkt2(tmp + 2 * 256); msb = ld_pkt2(tmp + 3 * 256); mcb = ld_pkt2(tmp + 4 * 256);
        const __nv_bfloat16* xp = q_.x + ob * D_ + 64 * w + 4 * (lane & 8) + (lane & 7);
        tx0 = ldg16(xp) | ldg16(xp + 8) << 16;
        tx1 = ldg16(xp + 16) | ldg16(xp + 24) << 16;

        asm volatile("cp.async.wait_all;" ::: "memory");

#pragma unroll
        for (int m = 1; m < 32; m <<= 1) mx = fmaxf(mx, __shfl_xor_sync(~0u, mx, m));
        if (lane == 0) sts32f(sb + SM_RED + w * 4, mx);
        cbar();
        {
            const float4 u = lds128f(sb + SM_RED), v = lds128f(sb + SM_RED + 16);
            mx = fmaxf(fmaxf(fmaxf(u.x, u.y), fmaxf(u.z, u.w)), fmaxf(fmaxf(v.x, v.y), fmaxf(v.z, v.w)));
        }
        const uint32_t pa = sb + SM_P + (tid >> 3) * 256 + rank * 128 + (tid & 7) * 16;
        const uint4 s0 = lds128(pa);
        const float sc[8] = {bf_lo(s0.x), bf_hi(s0.x), bf_lo(s0.y), bf_hi(s0.y), bf_lo(s0.z), bf_hi(s0.z), bf_lo(s0.w), bf_hi(s0.w)};
        float l = 0.f;
#pragma unroll
        for (int i = 0; i < 8; i++) l += __expf(sc[i] - mx);
#pragma unroll
        for (int m = 1; m < 32; m <<= 1) l += __shfl_xor_sync(~0u, l, m);
        if (lane == 0) sts32f(sb + SM_RED + 32 + w * 4, l);
        cbar();
        {
            const float4 u = lds128f(sb + SM_RED + 32), v = lds128f(sb + SM_RED + 48);
            l = ((u.x + u.y) + (u.z + u.w)) + ((v.x + v.y) + (v.z + v.w));
        }
        if (tid == 0) st_async_v2(mapa(sb + SM_ML, rank ^ 1), mx, l, mapa(sb + BAR_XML, rank ^ 1));
        mbar_wait_cluster(sb + BAR_XML, 0);
        const float2 o = lds64f(sb + SM_ML);
        const float m = fmaxf(mx, o.x);
        const float inv = __fdividef(1.0f, l * __expf(mx - m) + o.y * __expf(o.x - m));
        const uint32_t p0 = pack2(__expf(sc[0] - m) * inv, __expf(sc[1] - m) * inv), p1 = pack2(__expf(sc[2] - m) * inv, __expf(sc[3] - m) * inv);
        const uint32_t p2 = pack2(__expf(sc[4] - m) * inv, __expf(sc[5] - m) * inv), p3 = pack2(__expf(sc[6] - m) * inv, __expf(sc[7] - m) * inv);
        st_async_v4(mapa(pa, rank ^ 1), p0, p1, p2, p3, mapa(sb + BAR_XP, rank ^ 1));
        sts128(pa, p0, p1, p2, p3);
        cbar();
        mbar_wait_cluster(sb + BAR_XP, 0);
    }

    for (uint32_t n = 0; n < SPIN_LIMIT && !__all_sync(~0u, pkt_ok(mga, tag) && pkt_ok(msb, tag) && pkt_ok(mcb, tag)); n++) {
        mga = ld_pkt2(tmp + 2 * 256); msb = ld_pkt2(tmp + 3 * 256); mcb = ld_pkt2(tmp + 4 * 256);
    }
    const uint32_t ga0 = lo32(mga.a), ga1 = lo32(mga.b), sb0 = lo32(msb.a), sb1 = lo32(msb.b);
    const uint32_t cb0 = hadd2(ONE2, lo32(mcb.a)), cb1 = hadd2(ONE2, lo32(mcb.b));
    u64 red_p = s_line(e1_blk(1, w), 2 * b) + lane * 4, red2_p = s_line(e1_blk(1, w), 4 + b) + lane * 4;

    PIN64(red_p); PIN64(red2_p);
    float oa[4][4];
#pragma unroll
    for (int i = 0; i < 4; i++) { oa[i][0] = oa[i][1] = oa[i][2] = oa[i][3] = 0.f; }
    {
        int stage = N_V % STAGES, phase = tile_phase(N_V);
        auto v_tiles = [&](int v0, int v1) {
#pragma unroll 1
            for (int v = v0; v < v1; v++) {
                const uint32_t tb = sb + SM_RING + stage * TILE_BYTES + grp * 8192 + (sw128 ^ (sub * 32));
                uint2 P[4];
#pragma unroll
                for (int i = 0; i < 4; i++) P[i] = lds64(sb + SM_P + v * 256 + grp * 128 + i * 32 + t * 8);
                mbar_wait(sb + BAR_FULL + 8 * stage, phase);
                uint32_t a[4][4];
#pragma unroll
                for (int i = 0; i < 4; i++) ldsm4t(tb + i * 2048, a[i]);
#pragma unroll
                for (int i = 0; i < 4; i++) mma4(oa[i], a[i], P[i].x, P[i].y);
                __syncwarp();
                if (lane == 0) mbar_arrive(sb + BAR_EMPTY + 8 * stage);
                if (++stage == STAGES) { stage = 0; phase ^= 1; }
            }
        };
        v_tiles(0, WO_AT);
#pragma unroll
        for (int i = 0; i < 4 * WO_EARLY; i++) {
            if ((i & 3) == 0) mbar_wait(sb + full_bar(N_WO + (i >> 2)), tile_phase(N_WO + (i >> 2)));
            ldsm4t(sb + slot_addr(N_WO + (i >> 2)) + w * 2048 + (sw128 ^ ((i & 3) * 32)), A[i]);
        }
        asm volatile("bar.sync 2, 288;" ::: "memory");
        if (tid < WO_EARLY) mbar_arrive_n(sb + BAR_EMPTY + 8 * ((N_WO + tid) % STAGES), 8);
        stage = N_V2 % STAGES; phase = tile_phase(N_V2);
        v_tiles(WO_AT, NT);
    }

    if (t < 2) sts32f(sb + SM_OP + w * 64 + (g >> 1) * 16 + (g & 1) * 4 + t * 8,
                      sel(t1, (oa[0][2] + oa[1][2]) + (oa[2][2] + oa[3][2]), (oa[0][0] + oa[1][0]) + (oa[2][0] + oa[3][0])));
    cbar();

    {
        float acc[4][4];
#pragma unroll
        for (int i = 0; i < 4; i++) { acc[i][0] = acc[i][1] = acc[i][2] = acc[i][3] = 0.f; }
        const float2 u = lds64f(sb + SM_OP + (lane & 15) * 16 + vb * 8), v = lds64f(sb + SM_OP + 256 + (lane & 15) * 16 + vb * 8);
        const uint32_t o2 = pack2(u.x + v.x, u.y + v.y);
#pragma unroll
        for (int s4 = 0; s4 < 4; s4++) {
            const uint32_t b0 = __shfl_sync(~0u, o2, 4 * s4 + t), b1 = __shfl_sync(~0u, o2, 16 + 4 * s4 + t);
            if (s4 >= WO_EARLY) {
                mbar_wait(sb + full_bar(N_V + NT + s4), tile_phase(N_V + NT + s4));
                if (s4 == 3) { }
#pragma unroll
                for (int i = 0; i < 4; i++) ldsm4t(sb + slot_addr(N_V + NT + s4) + w * 2048 + (sw128 ^ (i * 32)), A[4 * s4 + i]);
            }
#pragma unroll
            for (int i = 0; i < 4; i++) mma4(acc[i], A[4 * s4 + i], b0, b1);
        }
        const float r0 = sel(t2, sel(t1, 1.0f, acc[1][0]), sel(t1, acc[0][2], acc[0][0]));
        const float r1 = sel(t2, sel(t1, 1.0f, acc[3][0]), sel(t1, acc[2][2], acc[2][0]));
        const float r2 = sel(t2, 1.0f, sel(t1, acc[3][2], acc[1][2]));
        asm volatile("red.relaxed.gpu.global.add.f32 [%0], %2;\nred.relaxed.gpu.global.add.f32 [%0 + 256], %3;\nred.relaxed.gpu.global.add.f32 [%1], %4;"
                     :: "l"(red_p), "l"(red2_p), "f"(r0), "f"(r1), "f"(r2) : "memory");
        asm volatile("red.relaxed.gpu.global.add.f32 [%0], %2;\nred.relaxed.gpu.global.add.f32 [%0 + 256], %3;\nred.relaxed.gpu.global.add.f32 [%1], %4;"
                     :: "l"(red_p ^ 4096), "l"(red2_p ^ 4096), "f"(r0), "f"(r1), "f"(r2) : "memory");
    }

    constexpr uint32_t CNT = 0x42800000u;
    if (is_gu) {
        uint32_t side;
        asm volatile("ld.volatile.shared.u32 %0, [%1];" : "=r"(side) : "r"(sb + SM_SIDE) : "memory");
        u64 acc_p = (s_line(e1_blk(0, w), lane >> 3) + (lane & 7) * 16) ^ side, acc2_p = (s_line(e1_blk(0, w), 4 + ob) + (lane & 7) * 16) ^ side;
        const int eb = e1_blk(w >> 2, w & 3);
        const uint32_t near = (w >> 2) * 4096 == side;
        u64 out_p = s_line(eb, lane >> 3) + S_OUT + (lane & 7) * 16, out2_p = s_line(eb, 4 + ob) + S_OUT + (lane & 15) * 8;
        u64 gb_p = (s_line(e1_blk(0, w), 6 + ob) + (lane & 15) * 8) ^ side, y_p = (u64)(q_.out + t1 * D_ + 64 * w + 4 * t2 + g);
        PIN64(acc_p); PIN64(acc2_p); PIN64(out_p); PIN64(out2_p); PIN64(gb_p); PIN64(y_p);
        auto keep = [&](uint32_t x) { return __shfl_sync(~0u, x, lane); };
        const int src = keep(8 * (g & 2) + t), src1 = keep(src + 4), src2 = keep(src + 8), src3 = keep(src + 12);
        const uint32_t p_st = keep(sb + SM_PART + w * 512 + lane * 16), r_st = keep(sb + SM_RED + (vb * 8 + w) * 8);
        tx0 = keep(tx0); tx1 = keep(tx1);
        const uint32_t g1 = g & 1;
        uint32_t cp[8], cn[8];
        float acc[4][4];
#pragma unroll
        for (int i = 0; i < 8; i++) {
            cp[i] = __shfl_sync(~0u, (i & 1) ? cb1 : cb0, 4 * (i >> 1) + src);
            cn[i] = selu(g1, __shfl_sync(~0u, (i & 1) ? sb1 : sb0, 4 * (i >> 1) + src), cp[i]);
        }
        const int frow = (lane & 7) + (lane & 16);
        const uint32_t fa = sb + slot_addr(N_FFN) + grp * 2 * TILE_BYTES + (64 * sub + frow) * 64 + ((lch ^ ((frow >> 1) & 3)) << 4);
        mbar_wait(sb + BAR_FFN + 8 * (w * NQ >> 3), 0);
        uint4 u = ld_strong128(acc_p), v = ld_strong128(acc2_p);
#pragma unroll
        for (int i = 0; i < 16; i++) ldsm4t((fa ^ ((i & 1) * 32)) + (i >> 3) * 2048 + ((i >> 2) & 1) * 512 + ((i >> 1) & 1) * TILE_BYTES, A[i]);
#pragma unroll
        for (int i = 0; i < 4; i++) { acc[i][0] = acc[i][1] = acc[i][2] = acc[i][3] = 0.f; }
#pragma unroll
        for (int i = 0; i < 16; i++) mma4(acc[i & 3], A[i], cn[2 * (i >> 2)], cn[2 * (i >> 2) + 1]);
        sts128f(sb + SM_P + w * 1024 + lane * 16, sel(t2, acc[1][0], acc[0][0]), sel(t2, acc[3][0], acc[2][0]), sel(t2, acc[1][2], acc[0][2]), sel(t2, acc[3][2], acc[2][2]));
        sts128f(sb + SM_P + w * 1024 + 512 + lane * 16, sel(t2, acc[1][1], acc[0][1]), sel(t2, acc[3][1], acc[2][1]), sel(t2, acc[1][3], acc[0][3]), sel(t2, acc[3][3], acc[2][3]));
        bar_arrive<3>();
#pragma unroll
        for (int i = 0; i < 8; i++) cn[i] = selu(g1, cp[i] ^ 0x80008000u, 0u);
        settle(tag, sb + SM_OP, cn[0], cn[1], cn[2], cn[3]); settle(tag, sb + SM_OP, cn[4], cn[5], cn[6], cn[7]);
        for (uint32_t n = 0; !__all_sync(~0u, u.w == CNT && v.w == CNT) && n < SPIN_LIMIT; n++) { u = ld_strong128(acc_p); v = ld_strong128(acc2_p); }
        const uint32_t x0 = hadd2(tx0, hmul2(ga0, pack2(__uint_as_float(u.x), __uint_as_float(u.y))));
        const uint32_t x1 = hadd2(tx1, hmul2(ga1, pack2(__uint_as_float(u.z), __uint_as_float(selu(lane & 8, v.y, v.x)))));
        float c[4] = {0.f, 0.f, 0.f, 0.f};
        mma(c, x0, ONE2, x1, ONE2, x0, x1);
#pragma unroll
        for (int i = 0; i < 4; i++) { acc[i][0] = acc[i][1] = acc[i][2] = acc[i][3] = 0.f; }
        float q, s;
#pragma unroll
        for (int s4 = 0; s4 < 4; s4++) {
            const int from = s4 == 0 ? src : s4 == 1 ? src1 : s4 == 2 ? src2 : src3;
            uint32_t b0 = __shfl_sync(~0u, x0, from), b1 = __shfl_sync(~0u, x1, from);
            b0 = hfma2(b0, cp[2 * s4], hmul2(b0, cn[2 * s4]));
            b1 = hfma2(b1, cp[2 * s4 + 1], hmul2(b1, cn[2 * s4 + 1]));
#pragma unroll
            for (int i = 0; i < 4; i++) mma4(acc[i], A[4 * s4 + i], b0, b1);
            if (s4 == 0) { q = sel(g1, c[1], c[0]); s = c[2] + c[3]; q += __shfl_xor_sync(~0u, q, 4); s += __shfl_xor_sync(~0u, s, 9); }
            if (s4 == 1) q += __shfl_xor_sync(~0u, q, 9);
            if (s4 == 2) { if (lane == 0 || lane == 18) sts64f(r_st, s, fmaxf(fmaf(s * (-1.0f / 64), s, q), 0.f)); }
        }
        sts128f(p_st, sel(t2, acc[1][0] + acc[1][1], acc[0][0] + acc[0][1]), sel(t2, acc[3][0] + acc[3][1], acc[2][0] + acc[2][1]),
                sel(t2, acc[1][2] + acc[1][3], acc[0][2] + acc[0][3]), sel(t2, acc[3][2] + acc[3][3], acc[2][2] + acc[2][3]));
        bar_arrive<4>();
        uint32_t xo[2];
#pragma unroll
        for (int j = 0; j < 2; j++) {
            const uint32_t e0 = __shfl_sync(~0u, x0, 16 * t1 + 8 * j + g), e1 = __shfl_sync(~0u, x1, 16 * t1 + 8 * j + g);
            xo[j] = __byte_perm(e0, e1, t2 ? 0x7632 : 0x5410);
        }
        mbar_wait(sb + BAR_W2 + 8 * (w * NW >> 3), 0);
#pragma unroll
        for (int i = 0; i < 8; i++)
            ldsm4t(sb + slot_addr(N_FFN + 4) + w * 4096 + (i >> 2) * 2048 + (sw128 ^ ((i & 3) * 32)), A[i]);
#pragma unroll
        for (int i = 0; i < 4; i++) { acc[i][0] = acc[i][1] = acc[i][2] = acc[i][3] = 0.f; }
        bar_sync<5>();
        asm volatile("{\n.reg .pred p;\nsetp.ne.u32 p, %0, 0;\n@p bar.sync 7, 256;\n}" :: "r"(near) : "memory");
        const uint4 hv = lds128(sb + SM_Q + ((g & 2) * 2 + t) * 16);
#pragma unroll
        for (int i = 0; i < 4; i++) mma4(acc[i], A[i], hv.x, hv.y);
#pragma unroll
        for (int i = 0; i < 4; i++) mma4(acc[i], A[4 + i], hv.z, hv.w);
        float r[4], o[6];
#pragma unroll
        for (int i = 0; i < 4; i++) r[i] = sel(t2, acc[i][2], acc[i][0]);
        asm volatile("atom.relaxed.gpu.global.add.v4.f32 {%0, %1, %2, %3}, [%4], {%5, %6, %7, %8};"
                     : "=f"(o[0]), "=f"(o[1]), "=f"(o[2]), "=f"(o[4]) : "l"(out_p), "f"(r[0]), "f"(r[1]), "f"(r[2]), "f"(1.0f) : "memory");
        asm volatile("atom.relaxed.gpu.global.add.v2.f32 {%0, %1}, [%2], {%3, %4};"
                     : "=f"(o[3]), "=f"(o[5]) : "l"(out2_p), "f"(r[3]), "f"(1.0f) : "memory");
        asm volatile("{\n.reg .pred p;\nsetp.eq.u32 p, %0, 0;\n@p bar.arrive 7, 256;\n}" :: "r"(near) : "memory");
        uint2 gb = ld_strong64(gb_p);
        const uint32_t f0 = pack2(o[0] + r[0], o[1] + r[1]), f1 = pack2(o[2] + r[2], o[3] + r[3]);
#pragma unroll 1
        for (uint32_t n = 0; n < SPIN_LIMIT; n++) {
            const uint32_t y0 = hadd2(xo[0], hmul2(gb.x, f0)), y1 = hadd2(xo[1], hmul2(gb.y, f1));
            uint32_t late;
            asm volatile("{\n.reg .pred p, q, m;\n.reg .b16 a, b, c, d;\n"
                         "mov.b32 {a, b}, %6;\nmov.b32 {c, d}, %7;\nsetp.ne.b16 m, a, 0xffff;\nsetp.ne.and.b16 m, b, 0xffff, m;\nsetp.ne.and.b16 m, c, 0xffff, m;\nsetp.ne.and.b16 m, d, 0xffff, m;\n"
                         "setp.eq.and.f32 p, %4, 0f42280000, m;\nsetp.eq.and.f32 q, %5, 0f42280000, m;\n"
                         "mov.b32 {a, b}, %2;\nmov.b32 {c, d}, %3;\n"
                         "@p st.global.u16 [%1], a;\n@p st.global.u16 [%1 + 32], b;\n@p st.global.u16 [%1 + 64], c;\n@q st.global.u16 [%1 + 96], d;\n"
                         "vote.sync.all.pred m, m, 0xffffffff;\nselp.u32 %0, 0, 1, m;\n}"
                         : "=r"(late) : "l"(y_p), "r"(y0), "r"(y1), "f"(o[4]), "f"(o[5]), "r"(gb.x), "r"(gb.y) : "memory");
            if (!late) break;
            gb = ld_strong64(gb_p);
        }
    } else if (is_gb) {
        const uint32_t fa = sb + slot_addr(N_FFN) + grp * 8192 + (64 * sub + lrow) * 32 + ((lch ^ ((lrow >> 2) & 1)) << 4);
        const int dl = (lane & 7) * 4 + ((lane >> 3) & 1) * 2 + ob;
        u64 gb_p = s_line(2 * (role >> 2), 6 + (dl >> 4)) + (dl & 15) * 8 + (role & 3) * 2;
        PIN64(gb_p);
        uint32_t bs[8];
#pragma unroll
        for (int i = 0; i < 8; i++) bs[i] = __shfl_sync(~0u, (i & 1) ? sc1 : sc0, 4 * (i >> 1) + 16 * ((g >> 1) & 1) + t);
        const uint32_t c_st = sb + SM_PART + (w * 32 + t1 * 16 + (t >> 1) * 8 + g) * 4;
        settle(tag, sb + SM_OP, bs[0], bs[1], bs[2], bs[3]); settle(tag, sb + SM_OP, bs[4], bs[5], bs[6], bs[7]); settle(tag, sb + SM_OP, c_st, fa, 0, 0);
        mbar_wait(sb + BAR_FFN + 8 * grp, 0);
        float c[4][4];
#pragma unroll
        for (int s4 = 0; s4 < 4; s4++) ldsm4t(fa + s4 * 512, A[s4]);
#pragma unroll
        for (int s4 = 0; s4 < 4; s4++) { c[s4][0] = c[s4][1] = c[s4][2] = c[s4][3] = 0.f; mma4(c[s4], A[s4], bs[2 * s4], bs[2 * s4 + 1]); }
        sts32f(c_st, sel(t2, (c[0][2] + c[1][2]) + (c[2][2] + c[3][2]), (c[0][0] + c[1][0]) + (c[2][0] + c[3][0])));
        cbar();
        if (w == 0) {
            float u[8];
#pragma unroll
            for (int i = 0; i < 8; i++) u[i] = lds32f(sb + SM_PART + i * 128 + lane * 4);
            const uint16_t v = (uint16_t)pack2(((u[0] + u[1]) + (u[2] + u[3])) + ((u[4] + u[5]) + (u[6] + u[7])), 0.f);
            asm volatile("st.relaxed.gpu.global.u16 [%0], %1;\nst.relaxed.gpu.global.u16 [%0 + 4096], %1;" :: "l"(gb_p), "h"(v) : "memory");
        }
    }
}

typedef CUresult (*EncodeFn)(CUtensorMap*, CUtensorMapDataType, cuuint32_t, void*, const cuuint64_t*, const cuuint64_t*,
                             const cuuint32_t*, const cuuint32_t*, CUtensorMapInterleave, CUtensorMapSwizzle,
                             CUtensorMapL2promotion, CUtensorMapFloatOOBfill);

void make_map(EncodeFn enc, CUtensorMap* m, void* ptr, int cols, int rows, int box_cols, int box_rows, CUtensorMapSwizzle sw) {
    cuuint64_t gd[2] = {(cuuint64_t)cols, (cuuint64_t)rows}, gs[1] = {(cuuint64_t)cols * 2};
    cuuint32_t bd[2] = {(cuuint32_t)box_cols, (cuuint32_t)box_rows}, es[2] = {1, 1};
    enc(m, CU_TENSOR_MAP_DATA_TYPE_BFLOAT16, 2, ptr, gd, gs, bd, es, CU_TENSOR_MAP_INTERLEAVE_NONE, sw,
        CU_TENSOR_MAP_L2_PROMOTION_NONE, CU_TENSOR_MAP_FLOAT_OOB_FILL_NONE);
}

}

extern "C" void kernel_launch(void* const* d_in, const int* in_sizes, int n_in, void* d_out, int out_size) {
    (void)in_sizes; (void)n_in; (void)out_size;
    static EncodeFn enc = nullptr;
    if (!enc) {
        void* fn = nullptr;
        cudaDriverEntryPointQueryResult qr;
        cudaGetDriverEntryPoint("cuTensorMapEncodeTiled", &fn, cudaEnableDefault, &qr);
        enc = (EncodeFn)fn;
        cudaFuncSetAttribute(fused_decode_kernel, cudaFuncAttributeMaxDynamicSharedMemorySize, SMEM_BYTES);
    }
    Params p;
    Ptrs q;
    make_map(enc, &p.m_wmod, d_in[10], MODW, D_, 32, 256, CU_TENSOR_MAP_SWIZZLE_64B);
    make_map(enc, &p.m_wq, d_in[3], QD, D_, 64, 128, CU_TENSOR_MAP_SWIZZLE_128B);
    make_map(enc, &p.m_v, d_in[2], DH, 64 * SK, 64, 128, CU_TENSOR_MAP_SWIZZLE_128B);
    {
        cuuint64_t gd[3] = {64, QD, 8}, gs[2] = {D_ * 2, 128};
        cuuint32_t bd[3] = {64, 16, 8}, es[3] = {1, 1, 1};
        enc(&p.m_wo, CU_TENSOR_MAP_DATA_TYPE_BFLOAT16, 3, d_in[4], gd, gs, bd, es, CU_TENSOR_MAP_INTERLEAVE_NONE,
            CU_TENSOR_MAP_SWIZZLE_128B, CU_TENSOR_MAP_L2_PROMOTION_NONE, CU_TENSOR_MAP_FLOAT_OOB_FILL_NONE);
    }
    for (int i = 0; i < 2; i++) {
        cuuint64_t gd[4] = {FF, 2, 8, D_ / 16}, gs[3] = {8 * FF * 2, FF * 2, 16 * FF * 2};
        cuuint32_t bd[4] = {32, 2, 8, 32 / NQ}, es[4] = {1, 1, 1, 1};
        enc(i ? &p.m_w3 : &p.m_w1, CU_TENSOR_MAP_DATA_TYPE_BFLOAT16, 4, d_in[6 + i], gd, gs, bd, es, CU_TENSOR_MAP_INTERLEAVE_NONE,
            CU_TENSOR_MAP_SWIZZLE_64B, CU_TENSOR_MAP_L2_PROMOTION_NONE, CU_TENSOR_MAP_FLOAT_OOB_FILL_NONE);
    }
    {
        cuuint64_t gd[5] = {64, 2, 8, FF / 16, 8}, gs[4] = {8 * D_ * 2, D_ * 2, 16 * D_ * 2, 128};
        cuuint32_t bd[5] = {64, 2, 8, 2, 8 / NW}, es[5] = {1, 1, 1, 1, 1};
        enc(&p.m_w2, CU_TENSOR_MAP_DATA_TYPE_BFLOAT16, 5, d_in[8], gd, gs, bd, es, CU_TENSOR_MAP_INTERLEAVE_NONE,
            CU_TENSOR_MAP_SWIZZLE_128B, CU_TENSOR_MAP_L2_PROMOTION_NONE, CU_TENSOR_MAP_FLOAT_OOB_FILL_NONE);
    }
    make_map(enc, &p.m_gb, d_in[10], MODW, D_, 16, 256, CU_TENSOR_MAP_SWIZZLE_32B);
    q.x = (const __nv_bfloat16*)d_in[0];
    q.kwin = (const __nv_bfloat16*)d_in[1] + (size_t)(SK - WIN) * DH;
    q.c = (const __nv_bfloat16*)d_in[9];
    q.out = (__nv_bfloat16*)d_out;
    fused_decode_kernel<<<NCTA, THREADS, SMEM_BYTES, cudaStreamPerThread>>>(q, p);
}
```

```cpp
#include <cuda_runtime.h>
#include <cuda.h>
#include <cuda_bf16.h>
#include <stdint.h>

namespace {

constexpr int D_ = 512, DH = 128, SK = 16384, WIN = 4096, FF = 1376, QD = 4096, MODW = 3072;
constexpr int NCTA = 128;
constexpr int TILE_BYTES = 16384;
constexpr int NT = 32;
constexpr int STAGES = 13;
constexpr int K_FIRST = 2;
constexpr int FIRST_N = 5;
constexpr int MEET_AT = 16;
constexpr int PACE = 656;
constexpr int LEAD_NS = 1290;
constexpr int GATE_X = 25;
constexpr int POLL_NS = 300;
constexpr int ALPHA16 = 4;
constexpr int GU_NS = 4630;
constexpr int W2_NS = 5830;
constexpr int GB_LEAD = 350;
constexpr int NQ = 8;
constexpr int PROBES = 6;
constexpr int PROBE_NS = 1000;
constexpr int EARLY_NS = 800;
constexpr int NW = 4;
constexpr int HEAD_TID = 256;
constexpr int N_WMOD = 0, N_WQ = 2, N_K = 6, N_V = N_K + NT, N_WO = N_V + NT, N_FFN = N_WO + 4;
constexpr int N_GATE = N_V + GATE_X;
constexpr int THREADS = 320;
constexpr int N_MOD_CTA = 80;
#define SPIN_LIMIT_S "4194304"
constexpr unsigned SPIN_LIMIT = 1u << 22;

constexpr int SM_RING = 0;
constexpr int SM_P = STAGES * TILE_BYTES;
constexpr int SM_PART = SM_P + WIN * 2;
constexpr int SM_OP = SM_PART + 8192;
constexpr int SM_Q = SM_OP + 2048;
constexpr int SM_RED = SM_Q + 256;
constexpr int SM_ML = SM_RED + 128;
constexpr int SM_PROG = SM_ML + 16;
constexpr int SM_SIDE = SM_PROG + 16;
constexpr int SM_BAR = SM_SIDE + 16;
constexpr int BAR_FULL = SM_BAR, BAR_EMPTY = SM_BAR + 8 * STAGES, BAR_XQ = SM_BAR + 16 * STAGES,
              BAR_XML = BAR_XQ + 8, BAR_XP = BAR_XQ + 16, BAR_XO = BAR_XQ + 24, BAR_FFN = BAR_XQ + 32;
constexpr int BAR_W2 = BAR_FFN + 8 * NQ;
constexpr int SMEM_BYTES = BAR_W2 + 8 * NW;
static_assert(SMEM_BYTES <= 232448, "shared memory");
__host__ __device__ constexpr uint32_t slot_addr(int n) { return SM_RING + (n % STAGES) * TILE_BYTES; }
__host__ __device__ constexpr uint32_t full_bar(int n) { return BAR_FULL + 8 * (n % STAGES); }
__host__ __device__ constexpr uint32_t empty_bar(int n) { return BAR_EMPTY + 8 * (n % STAGES); }
__host__ __device__ constexpr uint32_t tile_phase(int n) { return (n / STAGES) & 1; }
static_assert((N_FFN + 4) % STAGES + 2 <= STAGES && N_FFN % STAGES + 4 <= STAGES, "w1/w3 tiles and w2 tiles occupy consecutive slots");
static_assert(GATE_X >= MEET_AT && N_GATE - STAGES < N_V + MEET_AT && N_FFN + 5 - 2 * STAGES < N_V + MEET_AT && N_FFN + 5 - STAGES < N_WO,
              "barrier parities the helper warp waits on are unambiguous after the rendezvous; the wo tiles are not replaced");
__host__ __device__ constexpr int fill_tile(int j) { return j < K_FIRST ? N_K + j : j < K_FIRST + N_K ? j - K_FIRST : j; }

struct Ptrs {
    const __nv_bfloat16 *kwin, *x, *c;
    __nv_bfloat16* out;
};
struct Params {
    CUtensorMap m_wmod, m_wq, m_v, m_wo, m_w1, m_w3, m_w2, m_gb;
};

__device__ unsigned g_epoch;
__device__ __align__(128) uint2 g_mod[2][5 * D_ / 2];
__device__ __align__(256) unsigned char g_s[131072];
__device__ __forceinline__ unsigned long long s_line(int blk, int i) {
    return (((unsigned long long)g_s + 65535) & ~65535ull) + blk * 4096 + (i >> 1) * 1024 + (i & 1) * 256;
}
__device__ __forceinline__ int e1_blk(int r, int w) { return 2 * w + (r ^ (w & 1)); }
constexpr int S_OUT = 512, S_PROG = 128;
__device__ __align__(128) unsigned g_clear;

typedef unsigned long long u64;
__device__ __forceinline__ unsigned time_ns() {
    unsigned r;
    asm volatile("mov.u32 %0, %%globaltimer_lo;" : "=r"(r));
    return r;
}
__device__ __forceinline__ bool elect_one() {
    uint32_t r;
    asm volatile("{\n.reg .pred p;\nelect.sync _|p, 0xffffffff;\nselp.u32 %0, 1, 0, p;\n}" : "=r"(r));
    return r != 0;
}
#define PIN64(v) asm volatile("" : "+l"(v))

__device__ __forceinline__ void mbar_init(uint32_t bar, uint32_t cnt) {
    asm volatile("mbarrier.init.shared::cta.b64 [%0], %1;" :: "r"(bar), "r"(cnt) : "memory");
}
__device__ __forceinline__ void mbar_expect_tx(uint32_t bar, uint32_t bytes) {
    asm volatile("mbarrier.arrive.expect_tx.shared::cta.b64 _, [%0], %1;" :: "r"(bar), "r"(bytes) : "memory");
}
__device__ __forceinline__ void mbar_arrive(uint32_t bar) {
    asm volatile("mbarrier.arrive.shared::cta.b64 _, [%0];" :: "r"(bar) : "memory");
}
__device__ __forceinline__ void mbar_arrive_n(uint32_t bar, uint32_t n) {
    asm volatile("mbarrier.arrive.shared::cta.b64 _, [%0], %1;" :: "r"(bar), "r"(n) : "memory");
}
__device__ __forceinline__ void mbar_wait(uint32_t bar, uint32_t parity) {
    asm volatile("{\n.reg .pred p;\n.reg .u32 n;\nmov.u32 n, 0;\nW0:\n"
                 "mbarrier.try_wait.parity.shared::cta.b64 p, [%0], %1;\n@p bra W1;\n"
                 "add.u32 n, n, 1;\nsetp.lt.u32 p, n, " SPIN_LIMIT_S ";\n@p bra W0;\nW1:\n}"
                 :: "r"(bar), "r"(parity) : "memory");
}
__device__ __forceinline__ void mbar_wait_cluster(uint32_t bar, uint32_t parity) {
    asm volatile("{\n.reg .pred p;\n.reg .u32 n;\nmov.u32 n, 0;\nW0:\n"
                 "mbarrier.try_wait.parity.acquire.cluster.shared::cta.b64 p, [%0], %1;\n@p bra W1;\n"
                 "add.u32 n, n, 1;\nsetp.lt.u32 p, n, " SPIN_LIMIT_S ";\n@p bra W0;\nW1:\n}"
                 :: "r"(bar), "r"(parity) : "memory");
}
__device__ __forceinline__ void bulk_load(uint32_t dst, const void* src, uint32_t bytes, uint32_t bar, uint64_t pol) {
    asm volatile("cp.async.bulk.shared::cluster.global.mbarrier::complete_tx::bytes.L2::cache_hint [%0], [%1], %2, [%3], %4;"
                 :: "r"(dst), "l"(src), "r"(bytes), "r"(bar), "l"(pol) : "memory");
}
__device__ __forceinline__ void tma2d(uint32_t dst, const CUtensorMap* m, int c0, int c1, uint32_t bar) {
    asm volatile("cp.async.bulk.tensor.2d.shared::cluster.global.mbarrier::complete_tx::bytes [%0], [%1, {%3, %4}], [%2];"
                 :: "r"(dst), "l"(m), "r"(bar), "r"(c0), "r"(c1) : "memory");
}
__device__ __forceinline__ void tma2d_hint(uint32_t dst, const CUtensorMap* m, int c0, int c1, uint32_t bar, uint64_t pol) {
    asm volatile("cp.async.bulk.tensor.2d.shared::cluster.global.mbarrier::complete_tx::bytes.L2::cache_hint [%0], [%1, {%3, %4}], [%2], %5;"
                 :: "r"(dst), "l"(m), "r"(bar), "r"(c0), "r"(c1), "l"(pol) : "memory");
}
__device__ __forceinline__ void tma3d(uint32_t dst, const CUtensorMap* m, int c0, int c1, int c2, uint32_t bar) {
    asm volatile("cp.async.bulk.tensor.3d.shared::cluster.global.mbarrier::complete_tx::bytes [%0], [%1, {%3, %4, %5}], [%2];"
                 :: "r"(dst), "l"(m), "r"(bar), "r"(c0), "r"(c1), "r"(c2) : "memory");
}
__device__ __forceinline__ void tma4d(uint32_t dst, const CUtensorMap* m, int c0, int c3, uint32_t bar) {
    asm volatile("cp.async.bulk.tensor.4d.shared::cluster.global.mbarrier::complete_tx::bytes [%0], [%1, {%3, %5, %5, %4}], [%2];"
                 :: "r"(dst), "l"(m), "r"(bar), "r"(c0), "r"(c3), "r"(0) : "memory");
}
__device__ __forceinline__ void tma5d(uint32_t dst, const CUtensorMap* m, int c3, int c4, uint32_t bar) {
    asm volatile("cp.async.bulk.tensor.5d.shared::cluster.global.mbarrier::complete_tx::bytes [%0], [%1, {%5, %5, %5, %3, %4}], [%2];"
                 :: "r"(dst), "l"(m), "r"(bar), "r"(c3), "r"(c4), "r"(0) : "memory");
}
__device__ __forceinline__ uint32_t mapa(uint32_t addr, uint32_t rank) {
    uint32_t r;
    asm("mapa.shared::cluster.u32 %0, %1, %2;" : "=r"(r) : "r"(addr), "r"(rank));
    return r;
}
__device__ __forceinline__ void st_async_b32(uint32_t addr, uint32_t v, uint32_t bar) {
    asm volatile("st.async.weak.shared::cluster.mbarrier::complete_tx::bytes.b32 [%0], %1, [%2];" :: "r"(addr), "r"(v), "r"(bar) : "memory");
}
__device__ __forceinline__ void st_async_v2(uint32_t addr, float a, float b, uint32_t bar) {
    asm volatile("st.async.weak.shared::cluster.mbarrier::complete_tx::bytes.v2.f32 [%0], {%1, %2}, [%3];" :: "r"(addr), "f"(a), "f"(b), "r"(bar) : "memory");
}
__device__ __forceinline__ void st_async_v4(uint32_t addr, uint32_t a, uint32_t b, uint32_t c, uint32_t d, uint32_t bar) {
    asm volatile("st.async.weak.shared::cluster.mbarrier::complete_tx::bytes.v4.b32 [%0], {%1, %2, %3, %4}, [%5];"
                 :: "r"(addr), "r"(a), "r"(b), "r"(c), "r"(d), "r"(bar) : "memory");
}
template <int ID> __device__ __forceinline__ void bar_sync() { asm volatile("bar.sync %0, 288;" :: "n"(ID) : "memory"); }
template <int ID> __device__ __forceinline__ void bar_arrive() { asm volatile("bar.arrive %0, 288;" :: "n"(ID) : "memory"); }
__device__ __forceinline__ void cbar() { asm volatile("bar.sync 1, 256;" ::: "memory"); }

__device__ __forceinline__ uint4 ldg128(const void* p) {
    uint4 v;
    asm volatile("ld.global.nc.v4.u32 {%0,%1,%2,%3}, [%4];" : "=r"(v.x), "=r"(v.y), "=r"(v.z), "=r"(v.w) : "l"(p));
    return v;
}
__device__ __forceinline__ uint32_t ldg16(const void* p) {
    uint16_t v;
    asm volatile("ld.global.nc.u16 %0, [%1];" : "=h"(v) : "l"(p));
    return v;
}
__device__ __forceinline__ uint4 ld_strong128(unsigned long long p) {
    uint4 v;
    asm volatile("ld.relaxed.gpu.global.v4.b32 {%0,%1,%2,%3}, [%4];" : "=r"(v.x), "=r"(v.y), "=r"(v.z), "=r"(v.w) : "l"(p) : "memory");
    return v;
}
__device__ __forceinline__ uint2 ld_strong64(unsigned long long p) {
    uint2 v;
    asm volatile("ld.relaxed.gpu.global.v2.b32 {%0,%1}, [%2];" : "=r"(v.x), "=r"(v.y) : "l"(p) : "memory");
    return v;
}
__device__ __forceinline__ uint32_t ldg32(const void* p) {
    uint32_t v;
    asm volatile("ld.global.nc.u32 %0, [%1];" : "=r"(v) : "l"(p));
    return v;
}
struct Pkt2 { u64 a, b; };
__device__ __forceinline__ uint32_t lo32(u64 v) { return (uint32_t)v; }
__device__ __forceinline__ uint32_t hi32(u64 v) { return (uint32_t)(v >> 32); }
__device__ __forceinline__ Pkt2 ld_pkt2(const void* p) {
    Pkt2 r;
    asm volatile("ld.relaxed.gpu.global.v2.b64 {%0,%1}, [%2];" : "=l"(r.a), "=l"(r.b) : "l"(p) : "memory");
    return r;
}
__device__ __forceinline__ bool pkt_ok(const Pkt2& r, uint32_t tag) { return hi32(r.a) == tag && hi32(r.b) == tag; }
__device__ __forceinline__ void st_pkt(u64 p, uint32_t data, uint32_t tag) {
    asm volatile("{\n.reg .b64 v;\nmov.b64 v, {%1, %2};\nst.relaxed.gpu.global.b64 [%0], v;\n}" :: "l"(p), "r"(data), "r"(tag) : "memory");
}
__device__ __forceinline__ uint4 lds128(uint32_t a) {
    uint4 v;
    asm volatile("ld.shared.v4.u32 {%0,%1,%2,%3}, [%4];" : "=r"(v.x), "=r"(v.y), "=r"(v.z), "=r"(v.w) : "r"(a) : "memory");
    return v;
}
__device__ __forceinline__ float4 lds128f(uint32_t a) {
    float4 v;
    asm volatile("ld.shared.v4.f32 {%0,%1,%2,%3}, [%4];" : "=f"(v.x), "=f"(v.y), "=f"(v.z), "=f"(v.w) : "r"(a) : "memory");
    return v;
}
__device__ __forceinline__ uint2 lds64(uint32_t a) {
    uint2 v;
    asm volatile("ld.shared.v2.u32 {%0,%1}, [%2];" : "=r"(v.x), "=r"(v.y) : "r"(a) : "memory");
    return v;
}
__device__ __forceinline__ float2 lds64f(uint32_t a) {
    float2 v;
    asm volatile("ld.shared.v2.f32 {%0,%1}, [%2];" : "=f"(v.x), "=f"(v.y) : "r"(a) : "memory");
    return v;
}
__device__ __forceinline__ float lds32f(uint32_t a) {
    float v;
    asm volatile("ld.shared.f32 %0, [%1];" : "=f"(v) : "r"(a) : "memory");
    return v;
}
__device__ __forceinline__ void sts64f(uint32_t a, float x, float y) {
    asm volatile("st.shared.v2.f32 [%0], {%1,%2};" :: "r"(a), "f"(x), "f"(y) : "memory");
}
__device__ __forceinline__ void sts128f(uint32_t a, float x, float y, float z, float w) {
    asm volatile("st.shared.v4.f32 [%0], {%1,%2,%3,%4};" :: "r"(a), "f"(x), "f"(y), "f"(z), "f"(w) : "memory");
}
__device__ __forceinline__ void sts32f(uint32_t a, float x) {
    asm volatile("st.shared.f32 [%0], %1;" :: "r"(a), "f"(x) : "memory");
}
__device__ __forceinline__ void sts128(uint32_t a, uint32_t x, uint32_t y, uint32_t z, uint32_t w) {
    asm volatile("st.shared.v4.u32 [%0], {%1,%2,%3,%4};" :: "r"(a), "r"(x), "r"(y), "r"(z), "r"(w) : "memory");
}
__device__ __forceinline__ void settle(uint32_t tag, uint32_t a, uint32_t x, uint32_t y, uint32_t z, uint32_t w) {
    asm volatile("{\n.reg .pred p;\nsetp.eq.u32 p, %0, 0;\n@p st.shared.v4.u32 [%1], {%2,%3,%4,%5};\n}" :: "r"(tag), "r"(a), "r"(x), "r"(y), "r"(z), "r"(w) : "memory");
}
__device__ __forceinline__ void settle(uint32_t tag, uint32_t a, const float4& v) {
    settle(tag, a, __float_as_uint(v.x), __float_as_uint(v.y), __float_as_uint(v.z), __float_as_uint(v.w));
}
__device__ __forceinline__ void sts16(uint32_t a, uint32_t x) {
    asm volatile("st.shared.u16 [%0], %1;" :: "r"(a), "h"((uint16_t)x) : "memory");
}
__device__ __forceinline__ void ldsm4t(uint32_t a, uint32_t (&r)[4]) {
    asm volatile("ldmatrix.sync.aligned.m8n8.x4.trans.shared.b16 {%0,%1,%2,%3}, [%4];"
                 : "=r"(r[0]), "=r"(r[1]), "=r"(r[2]), "=r"(r[3]) : "r"(a) : "memory");
}
__device__ __forceinline__ void mma(float (&c)[4], uint32_t a0, uint32_t a1, uint32_t a2, uint32_t a3, uint32_t b0, uint32_t b1) {
    asm volatile("mma.sync.aligned.m16n8k16.row.col.f32.bf16.bf16.f32 {%0,%1,%2,%3}, {%4,%5,%6,%7}, {%8,%9}, {%0,%1,%2,%3};"
                 : "+f"(c[0]), "+f"(c[1]), "+f"(c[2]), "+f"(c[3]) : "r"(a0), "r"(a1), "r"(a2), "r"(a3), "r"(b0), "r"(b1));
}
__device__ __forceinline__ void mma4(float (&c)[4], const uint32_t (&a)[4], uint32_t b0, uint32_t b1) { mma(c, a[0], a[1], a[2], a[3], b0, b1); }
__device__ __forceinline__ float sel(uint32_t c, float a, float b) {
    float r;
    asm("{\n.reg .pred p;\nsetp.ne.u32 p, %3, 0;\nselp.f32 %0, %1, %2, p;\n}" : "=f"(r) : "f"(a), "f"(b), "r"(c));
    return r;
}
__device__ __forceinline__ float bf_lo(uint32_t v) { return __uint_as_float(v << 16); }
__device__ __forceinline__ float bf_hi(uint32_t v) { return __uint_as_float(v & 0xffff0000u); }
__device__ __forceinline__ uint32_t pack2(float lo, float hi) {
    uint32_t r;
    asm("cvt.rn.bf16x2.f32 %0, %1, %2;" : "=r"(r) : "f"(hi), "f"(lo));
    return r;
}
__device__ __forceinline__ float rbf(float x) { return __uint_as_float(pack2(0.f, x)); }
__device__ __forceinline__ uint32_t hadd2(uint32_t a, uint32_t b) { uint32_t r; asm("add.rn.bf16x2 %0, %1, %2;" : "=r"(r) : "r"(a), "r"(b)); return r; }
__device__ __forceinline__ uint32_t hsub2(uint32_t a, uint32_t b) { uint32_t r; asm("sub.rn.bf16x2 %0, %1, %2;" : "=r"(r) : "r"(a), "r"(b)); return r; }
__device__ __forceinline__ uint32_t hmul2(uint32_t a, uint32_t b) { uint32_t r; asm("mul.rn.bf16x2 %0, %1, %2;" : "=r"(r) : "r"(a), "r"(b)); return r; }
__device__ __forceinline__ uint32_t hfma2(uint32_t a, uint32_t b, uint32_t c) { uint32_t r; asm("fma.rn.bf16x2 %0, %1, %2, %3;" : "=r"(r) : "r"(a), "r"(b), "r"(c)); return r; }
__device__ __forceinline__ uint32_t selu(uint32_t c, uint32_t a, uint32_t b) { return __float_as_uint(sel(c, __uint_as_float(a), __uint_as_float(b))); }
constexpr uint32_t ONE2 = 0x3f803f80u;
__device__ __forceinline__ float silu_f(float x) {
    float e, r;
    asm("ex2.approx.ftz.f32 %0, %1;" : "=f"(e) : "f"(x * -1.4426950408889634f));
    asm("rcp.approx.ftz.f32 %0, %1;" : "=f"(r) : "f"(1.0f + e));
    return x * r;
}
__device__ __forceinline__ float rcp_sd(float m2) {
    float s, r;
    asm("sqrt.approx.ftz.f32 %0, %1;" : "=f"(s) : "f"(rbf(rbf(m2 * (1.0f / D_)) + 1e-5f)));
    asm("rcp.approx.ftz.f32 %0, %1;" : "=f"(r) : "f"(rbf(s)));
    return r;
}
__device__ __forceinline__ uint32_t ln_mod2(uint32_t x, uint32_t mean2, float rsd, uint32_t c1, uint32_t sh) {
    const uint32_t d = hsub2(x, mean2);
    return hadd2(hmul2(pack2(bf_lo(d) * rsd, bf_hi(d) * rsd), c1), sh);
}
__device__ __forceinline__ int pair_pos(int j) { return 2 * (j & 3) + (j >> 2); }

__global__ void __cluster_dims__(2, 1, 1) __launch_bounds__(THREADS, 1)
fused_decode_kernel(const __grid_constant__ Ptrs q_, const __grid_constant__ Params p) {
    extern __shared__ __align__(1024) unsigned char smem[];
    unsigned t_top;
    asm volatile("mov.u32 %0, %%globaltimer_lo;" : "=r"(t_top));
    const int tid = threadIdx.x;
    uint32_t z0;
    asm("and.b32 %0, %1, 1024;" : "=r"(z0) : "r"(tid));
    const char* kw = *(const char* const*)((const char*)&q_.kwin + z0);
    const uint32_t sb = (uint32_t)__cvta_generic_to_shared(smem);
    auto place = [](int cl) { return cl < 4 ? 8 * cl + 39 : cl - 4 + max((cl * 37 - 36 * 37) >> 8, 0); };
    uint32_t z2;
    asm("and.b32 %0, %1, 2048;" : "=r"(z2) : "r"(tid));
    const int cv = blockIdx.x + z2, pw = place(cv >> 1);
    static_assert(SK * DH * 2 == 1 << 22 && TILE_BYTES == 1 << 14, "koff");
    const char* kp;
    auto set_kp = [&](uint32_t off) {
        asm volatile("{\n.reg .u32 lo, hi;\nmov.b64 {lo, hi}, %1;\nadd.cc.u32 lo, lo, %2;\naddc.u32 hi, hi, 0;\nmov.b64 %0, {lo, hi};\n}"
                     : "=l"(kp) : "l"(kw), "r"(off));
    };
    uint64_t pol;
    asm("createpolicy.fractional.L2::evict_first.b64 %0, 1.0;" : "=l"(pol));
    auto fill_k = [&](int n) {
        mbar_expect_tx(sb + full_bar(n), TILE_BYTES);
        bulk_load(sb + slot_addr(n), kp + (n - N_K) * 2 * TILE_BYTES, TILE_BYTES, sb + full_bar(n), pol);
    };
    static_assert(K_FIRST >= 1, "head block starts with K tile 0");
    if (tid + (sb >> 28) == HEAD_TID) {
        mbar_init(sb + full_bar(N_K), 1);
        set_kp(((pw & 7) << 22) | ((pw & 8) << 24) | ((pw & 48) << 21) | ((cv & 1) << 14));
        bulk_load(sb + slot_addr(N_K), kp, TILE_BYTES, sb + full_bar(N_K), pol);
        mbar_expect_tx(sb + full_bar(N_K), TILE_BYTES);
#pragma unroll
        for (int j = 1; j < K_FIRST; j++) { mbar_init(sb + full_bar(N_K + j), 1); fill_k(N_K + j); }
    }
    __syncwarp();
    const int cta = blockIdx.x, rank = cta & 1, pv = place(cta >> 1);
    const int b = (pv >> 3) & 1, h = (pv & 7) | ((pv >> 1) & 24), bh = 32 * b + h;
    const int mc = 2 * pv + rank;
    auto first_fill = [&](int j) {
        const int n = fill_tile(j);
        if (n >= N_K) {
            fill_k(n);
        } else if (n >= N_WQ) {
            mbar_expect_tx(sb + full_bar(n), TILE_BYTES);
            tma2d(sb + slot_addr(n), &p.m_wq, h * DH + 64 * rank, 128 * (n - N_WQ), sb + full_bar(n));
        } else if (mc < N_MOD_CTA) {
            mbar_expect_tx(sb + full_bar(n), TILE_BYTES);
            tma2d(sb + slot_addr(n), &p.m_wmod, 32 * mc, 256 * n, sb + full_bar(n));
        } else {
            mbar_arrive(sb + full_bar(n));
        }
    };
    if (tid == HEAD_TID) {
#pragma unroll
        for (int j = K_FIRST; j < FIRST_N; j++) mbar_init(sb + full_bar(fill_tile(j)), 1);
#pragma unroll
        for (int j = K_FIRST; j < FIRST_N; j++) first_fill(j);
        asm volatile("fence.mbarrier_init.release.cluster;" ::: "memory");
    }
    __syncwarp();
    const int role = cta / 3;
    const bool is_gu = cta == 3 * role, is_gb = cta == 3 * role + 1 && role < 32;
    if (tid >= 288) {
        const unsigned t_start = t_top;
        asm volatile("barrier.cluster.arrive.relaxed.aligned;" ::: "memory");
        unsigned tag;
        asm volatile("ld.relaxed.gpu.global.u32 %0, [%1];" : "=r"(tag) : "l"(&g_epoch) : "memory");
        tag += 1;
        if (cta == NCTA - 1) {
#pragma unroll 2
            for (int i = tid - 288; i < 128 * 8; i += 32) {
                uint4* q = reinterpret_cast<uint4*>(s_line(i >> 6, (i >> 3) & 7)) + (i & 7);
                const uint32_t v = (i & 48) == 48 ? ~0u : 0u;
                q[0] = make_uint4(v, v, v, v);
                q[8] = q[32] = q[40] = make_uint4(0u, 0u, 0u, 0u);
            }
            __syncwarp();
            asm volatile("fence.acq_rel.gpu;" ::: "memory");
            if (tid == 288) asm volatile("st.relaxed.gpu.global.u32 [%0], %1;" :: "l"(&g_clear), "r"(tag) : "memory");
        }
        asm volatile("barrier.cluster.wait.acquire.aligned;" ::: "memory");
        mbar_wait_cluster(sb + BAR_XQ, 0);
#pragma unroll 1
        for (uint32_t n = 0; n < SPIN_LIMIT; n++) {
            unsigned c;
            asm volatile("ld.relaxed.gpu.global.u32 %0, [%1];" : "=r"(c) : "l"(&g_clear) : "memory");
            if (c == tag) break;
        }
        asm volatile("fence.acq_rel.gpu;" ::: "memory");
        asm volatile("st.volatile.shared.u32 [%0], %1;" :: "r"(sb + SM_SIDE), "r"(0) : "memory");
        asm volatile("bar.sync 2, 288;" ::: "memory");
        if (elect_one()) {
            asm volatile("prefetch.tensormap [%0];" :: "l"(is_gu ? &p.m_w1 : &p.m_gb) : "memory");
            asm volatile("prefetch.tensormap [%0];" :: "l"(&p.m_w3) : "memory");
            asm volatile("prefetch.tensormap [%0];" :: "l"(&p.m_w2) : "memory");
            const int issue = ((4 * N_GATE - 11) * PACE >> 2) - LEAD_NS;
            unsigned now, c = 0, best[2] = {~0u, ~0u}, np = is_gu ? 0 : PROBES;
            auto probe = [&]() {
                const int k = np >> 1, i = (role >> 3) + 2 * k;
                const u64 a = (s_line(e1_blk(0, role & 7), i < 6 ? i : i - 6) + (k ? 512 * k - 384 : 0)) ^ ((np & 1) << 12);
                unsigned v, c0, c1 = 0;
                asm volatile("mov.u32 %0, %%clock;" : "=r"(c0));
                asm volatile("ld.relaxed.gpu.global.u32 %0, [%1];" : "=r"(v) : "l"(a) : "memory");
                asm volatile("{\n.reg .pred p;\nsetp.ne.u32 p, %1, 0xffffffff;\n@p mov.u32 %0, %%clock;\n}" : "+r"(c1) : "r"(v));
                if (np & 1) best[1] = min(best[1], c1 - c0); else best[0] = min(best[0], c1 - c0);
                np++;
                if (!(np & 1)) asm volatile("st.volatile.shared.u32 [%0], %1;" :: "r"(sb + SM_SIDE), "r"(best[0] <= best[1] ? 0 : 4096) : "memory");
            };
#pragma unroll 1
            while (np < PROBES) {
                now = time_ns();
                if ((int)(now - t_start) >= issue + EARLY_NS) break;
                probe();
            }
            mbar_wait(sb + full_bar(N_GATE), tile_phase(N_GATE));
            now = time_ns();
            const unsigned mine = (1u << 24) + min(now - t_start, 100000u);
            const u64 prog = s_line(0, 7) + S_PROG;
            asm volatile("red.relaxed.gpu.global.add.u32 [%0], %1;" :: "l"(prog), "r"(mine) : "memory");
            if (is_gu || is_gb) {
#pragma unroll
                for (int i = 0; i < 6; i++) mbar_wait(sb + empty_bar(N_FFN + i), tile_phase(N_FFN + i) ^ 1);
#pragma unroll
                for (int i = 0; i < NQ; i++) mbar_expect_tx(sb + BAR_FFN + 8 * i, is_gu ? 65536 / NQ : 8192);
#pragma unroll
                for (int i = 0; i < NW; i++) mbar_expect_tx(sb + BAR_W2 + 8 * i, 32768 / NW);
                unsigned due = 0, next = now;
                constexpr unsigned full = (unsigned)NCTA << 24;
                asm volatile("st.volatile.shared.u32 [%0], %1;" :: "r"(sb + SM_PROG), "r"(mine) : "memory");
#pragma unroll 1
                for (uint32_t n = 0; n < 4096; n++) {
                    unsigned v;
                    asm volatile("ld.volatile.shared.u32 %0, [%1];" : "=r"(v) : "r"(sb + SM_PROG) : "memory");
                    if (v > c) {
                        c = v;
                        const int arr = (int)__fdividef((float)(c & 0xffffffu), (float)(c >> 24));
                        due = arr - ((arr - issue) * ALPHA16 >> 4) + (is_gb ? W2_NS - GB_LEAD : GU_NS);
                    }
                    now = time_ns();
                    if (now - t_start + PROBE_NS >= due) np = PROBES;
                    if ((c >= full && np == PROBES) || now - t_start >= due) break;
                    if ((int)(now - next) >= 0 && c < full) {
                        asm volatile("cp.async.cg.shared.global [%0], [%1], 16;" :: "r"(sb + SM_PROG), "l"(prog) : "memory");
                        next = now + POLL_NS;
                    }
                    if (np < PROBES) probe();
                }
#pragma unroll 1
                for (uint32_t n = 0; n < 1024 && now - t_start < due; n++) now = time_ns();
                if (is_gu) {
#pragma unroll
                    for (int i = 0; i < 2 * NQ; i++) {
                        const int q = i >> 1, r0 = q * (512 / NQ);
                        tma4d(sb + slot_addr(N_FFN) + (r0 >> 8) * 2 * TILE_BYTES + (i & 1) * TILE_BYTES + (r0 & 255) * 64, (i & 1) ? &p.m_w3 : &p.m_w1, 32 * role, r0 / 16, sb + BAR_FFN + 8 * q);
                    }
#pragma unroll 1
                    for (uint32_t n = 0; n < 1024 && now - t_start < due + (W2_NS - GU_NS); n++) now = time_ns();
                    const int f = best[0] <= best[1] ? NW / 2 : 0;
#pragma unroll
                    for (int i = 0; i < NW; i++) tma5d(sb + slot_addr(N_FFN + 4) + (i ^ f) * (32768 / NW), &p.m_w2, 2 * role, (i ^ f) * (8 / NW), sb + BAR_W2 + 8 * (i ^ f));
                } else {
                    tma2d(sb + slot_addr(N_FFN), &p.m_gb, 5 * D_ + 16 * role, 0, sb + BAR_FFN);
                    tma2d(sb + slot_addr(N_FFN) + 8192, &p.m_gb, 5 * D_ + 16 * role, 256, sb + BAR_FFN + 8);
                }
                asm volatile("cp.async.wait_all;" ::: "memory");
            }
        }
        __syncwarp();
        if (is_gu) {
            const int lane = tid & 31;
            auto sum8 = [&](uint32_t a, int stride) {
                float4 u[8];
#pragma unroll
                for (int i = 0; i < 8; i++) u[i] = lds128f(a + i * stride);
                return make_float4(((u[0].x + u[1].x) + (u[2].x + u[3].x)) + ((u[4].x + u[5].x) + (u[6].x + u[7].x)),
                                   ((u[0].y + u[1].y) + (u[2].y + u[3].y)) + ((u[4].y + u[5].y) + (u[6].y + u[7].y)),
                                   ((u[0].z + u[1].z) + (u[2].z + u[3].z)) + ((u[4].z + u[5].z) + (u[6].z + u[7].z)),
                                   ((u[0].w + u[1].w) + (u[2].w + u[3].w)) + ((u[4].w + u[5].w) + (u[6].w + u[7].w)));
            };
            uint32_t h_st = sb + SM_Q + (((lane & 1) * 4 + ((lane >> 2) & 3)) * 4 + (lane & 2) + (lane >> 4)) * 4;
            bar_sync<3>();
            const float4 C = sum8(sb + SM_P + lane * 16, 1024), S = sum8(sb + SM_P + 512 + lane * 16, 1024);
            const uint32_t st_ld = sb + SM_RED + (lane & 1) * 64;
            settle(tag, sb + SM_OP, C); settle(tag, sb + SM_OP, S); settle(tag, sb + SM_OP, h_st, st_ld, 0, 0);
            bar_sync<4>();
            const float4 r0 = lds128f(st_ld), r1 = lds128f(st_ld + 16), r2 = lds128f(st_ld + 32), r3 = lds128f(st_ld + 48);
            const float4 Y = sum8(sb + SM_PART + lane * 16, 512);
            const float e1 = r0.z - r0.x, e2 = r1.x - r0.x, e3 = r1.z - r0.x, e4 = r2.x - r0.x, e5 = r2.z - r0.x, e6 = r3.x - r0.x, e7 = r3.z - r0.x;
            const float se = ((e1 + e2) + (e3 + e4)) + ((e5 + e6) + e7);
            const float ee = (fmaf(e1, e1, e2 * e2) + fmaf(e3, e3, e4 * e4)) + fmaf(e5, e5, fmaf(e6, e6, e7 * e7));
            const float sq = ((r0.y + r0.w) + (r1.y + r1.w)) + ((r2.y + r2.w) + (r3.y + r3.w));
            const float rsd = rcp_sd(fmaf(se * (-1.0f / D_), se, fmaf(ee, 1.0f / 64, sq))), mu = -rbf(fmaf(r0.x, 8.0f, se) * (1.0f / D_));
            const uint32_t gr = pack2(fmaf(rsd, fmaf(mu, C.x, Y.x), S.x), fmaf(rsd, fmaf(mu, C.z, Y.z), S.z));
            const uint32_t ur = pack2(fmaf(rsd, fmaf(mu, C.y, Y.y), S.y), fmaf(rsd, fmaf(mu, C.w, Y.w), S.w));
            const uint32_t hv = hmul2(pack2(silu_f(bf_lo(gr)), silu_f(bf_hi(gr))), ur);
            sts32f(h_st, __uint_as_float(hv));
            bar_arrive<5>();
            if (role == 0 && lane == 0) g_epoch = tag;
        }
        return;
    }
    if (tid >= 256) {
        set_kp(bh * (SK * DH * 2) + rank * TILE_BYTES);
        const unsigned t_start = t_top;
        auto pace = [&](int q4) {
            const int due = (q4 * PACE >> 2) - LEAD_NS;
            unsigned now, n = 0;
            do { now = time_ns(); } while ((int)(now - t_start) < due && ++n < 256);
        };
        if (tid == 256) {
#pragma unroll
            for (int j = FIRST_N; j < STAGES; j++) mbar_init(sb + full_bar(fill_tile(j)), 1);
#pragma unroll
            for (int s = 0; s < STAGES; s++) mbar_init(sb + BAR_EMPTY + 8 * s, 8);
            mbar_init(sb + BAR_XQ, 1); mbar_init(sb + BAR_XML, 1); mbar_init(sb + BAR_XP, 1); mbar_init(sb + BAR_XO, 1);
#pragma unroll
            for (int i = 0; i < NQ + NW; i++) mbar_init(sb + BAR_FFN + 8 * i, 1);
            mbar_expect_tx(sb + BAR_XQ, 256); mbar_expect_tx(sb + BAR_XML, 8); mbar_expect_tx(sb + BAR_XP, WIN); mbar_expect_tx(sb + BAR_XO, 1024);
            asm volatile("fence.mbarrier_init.release.cluster;" ::: "memory");
            asm volatile("fence.proxy.async.shared::cta;" ::: "memory");
        }
        __syncwarp();
        asm volatile("barrier.cluster.arrive.relaxed.aligned;" ::: "memory");
        if (elect_one()) {
#pragma unroll
            for (int j = FIRST_N; j < STAGES; j++) {
                pace(j <= K_FIRST ? 4 * j : j <= K_FIRST + 2 ? 4 * K_FIRST + 5 * (j - K_FIRST) / 2 :
                     j <= K_FIRST + 6 ? 4 * K_FIRST + 5 + 2 * (j - K_FIRST - 2) : 4 * j - 11);
                first_fill(j);
            }
        }
        __syncwarp();
        asm volatile("barrier.cluster.wait.acquire.aligned;" ::: "memory");
        if (elect_one()) {
            asm volatile("prefetch.tensormap [%0];" :: "l"(&p.m_v) : "memory");
            asm volatile("prefetch.tensormap [%0];" :: "l"(&p.m_wo) : "memory");
            int s = 0, ph = 0;
#pragma unroll 1
            for (int n = STAGES; n < N_FFN; n++) {
                const uint32_t dst = sb + SM_RING + s * TILE_BYTES, bar = sb + BAR_FULL + 8 * s;
                mbar_wait(sb + BAR_EMPTY + 8 * s, ph);
                mbar_expect_tx(bar, TILE_BYTES);
                pace(n < N_WO ? 4 * n - 11 : 2 * (N_WO + n) - 11);
                if (n < N_V) bulk_load(dst, kp + (n - N_K) * 2 * TILE_BYTES, TILE_BYTES, bar, pol);
                else if (n < N_WO) tma2d_hint(dst, &p.m_v, 64 * rank, bh * SK + (SK - WIN) + 128 * (n - N_V), bar, pol);
                else tma3d(dst, &p.m_wo, 0, h * DH + 32 * (n - N_WO), 4 * rank, bar);
                if (++s == STAGES) { s = 0; ph ^= 1; }
            }
        }
        return;
    }

    const unsigned t_c = t_top;
    const int lane = tid & 31, w = tid >> 5, g = lane >> 2, t = lane & 3;
    const int hgrp = 4 * w + (g & 3);
    const int vb = g >> 2;
    const uint32_t cv0 = ldg32(q_.c + vb * D_ + 16 * hgrp + 2 * t), cv1 = ldg32(q_.c + vb * D_ + 16 * hgrp + 8 + 2 * t);
    unsigned tag;
    asm volatile("ld.relaxed.gpu.global.u32 %0, [%1];" : "=r"(tag) : "l"(&g_epoch) : "memory");
    const uint4 xa = ldg128(q_.x + b * D_ + 16 * lane), xb = ldg128(q_.x + b * D_ + 16 * lane + 8);
    const uint32_t xh0 = ldg32(q_.x + b * D_ + 16 * hgrp + 2 * t), xh1 = ldg32(q_.x + b * D_ + 16 * hgrp + 8 + 2 * t);
    asm volatile("barrier.cluster.arrive.relaxed.aligned;" ::: "memory");
#pragma unroll 1
    for (uint32_t n = t_c; n < 2; n++) asm volatile("nanosleep.u32 1;" ::: "memory");
    const int grp = w >> 2, sub = w & 3;
    const int lrow = (lane & 7) + 8 * (lane >> 4);
    const int lch = (lane >> 3) & 1;
    const int ob = lane >> 4;
    const uint32_t t1 = t & 1, t2 = t & 2;
    const int gsrc = 16 * (g & 1) + t;
    const uint32_t sw128 = lrow * 128 + ((lch ^ (lrow & 7)) << 4);
    uint32_t A[16][4];

    const uint32_t sc0 = pack2(silu_f(bf_lo(cv0)), silu_f(bf_hi(cv0))), sc1 = pack2(silu_f(bf_lo(cv1)), silu_f(bf_hi(cv1)));
    tag += 1;
    asm volatile("barrier.cluster.wait.acquire.aligned;" ::: "memory");
    mbar_wait(sb + BAR_FULL + 8 * (N_WMOD + grp), 0);
    if (mc < N_MOD_CTA) {
        const uint32_t tb = sb + SM_RING + (N_WMOD + grp) * TILE_BYTES + (64 * sub + lrow) * 64;
#pragma unroll
        for (int i = 0; i < 8; i++)
            ldsm4t(tb + (i >> 1) * 1024 + (((2 * (i & 1) + lch) ^ ((lrow >> 1) & 3)) << 4), A[i]);
        float acc[2][4] = {{0.f, 0.f, 0.f, 0.f}, {0.f, 0.f, 0.f, 0.f}};
#pragma unroll
        for (int s = 0; s < 4; s++) {
            const uint32_t b0 = __shfl_sync(~0u, sc0, 4 * s + gsrc), b1 = __shfl_sync(~0u, sc1, 4 * s + gsrc);
            mma4(acc[0], A[2 * s], b0, b1);
            mma4(acc[1], A[2 * s + 1], b0, b1);
        }
        sts32f(sb + SM_P + (w * 64 + 8 * t + g) * 4, sel(t2, sel(t1, acc[1][2], acc[1][0]), sel(t1, acc[0][2], acc[0][0])));
        sts32f(sb + SM_P + (w * 64 + 32 + 8 * t + g) * 4, sel(t2, sel(t1, acc[1][3], acc[1][1]), sel(t1, acc[0][3], acc[0][1])));
        cbar();
        if (w == 0) {
            const bool adj = mc < 32;
            const uint32_t a0 = sb + SM_P + (adj ? 2 * lane : ob * 32 + (lane & 1) * 16 + ((lane >> 1) & 7)) * 4, a1 = a0 + (adj ? 4 : 32);
            float2 sum = make_float2(0.f, 0.f);
#pragma unroll
            for (int i = 0; i < 8; i++) { sum.x += lds32f(a0 + i * 256); sum.y += lds32f(a1 + i * 256); }
            st_pkt((u64)&g_mod[ob][16 * mc + (adj ? (lane & 8) + pair_pos(lane & 7) : lane & 15)], pack2(sum.x, sum.y), tag);
        }
    }
    __syncwarp();
    if (lane == 0) mbar_arrive_n(sb + BAR_EMPTY + 8 * (N_WMOD + grp), 2);

    {
        const uint2* mp = &g_mod[b][vb * 256 + 8 * hgrp + 2 * t];
        const uint32_t ms = sb + SM_PART + tid * 16;
        auto fetch_mod = [&](uint32_t k) {
            asm volatile("cp.async.cg.shared.global [%0], [%1], 16;\ncp.async.commit_group;" :: "r"(ms + k), "l"(mp) : "memory");
        };
        fetch_mod(0);
        float xs[16] = {bf_lo(xa.x), bf_hi(xa.x), bf_lo(xa.y), bf_hi(xa.y), bf_lo(xa.z), bf_hi(xa.z), bf_lo(xa.w), bf_hi(xa.w),
                        bf_lo(xb.x), bf_hi(xb.x), bf_lo(xb.y), bf_hi(xb.y), bf_lo(xb.z), bf_hi(xb.z), bf_lo(xb.w), bf_hi(xb.w)};
        float s = 0.f;
#pragma unroll
        for (int i = 0; i < 16; i++) s += xs[i];
#pragma unroll
        for (int m = 1; m < 32; m <<= 1) s += __shfl_xor_sync(~0u, s, m);
        const float mean = s * (1.0f / D_);
        float q = 0.f;
#pragma unroll
        for (int i = 0; i < 16; i++) q += (xs[i] - mean) * (xs[i] - mean);
#pragma unroll
        for (int m = 1; m < 32; m <<= 1) q += __shfl_xor_sync(~0u, q, m);
        const uint32_t mean2 = pack2(mean, mean);
        const float rsd = rcp_sd(q);

        mbar_wait(sb + BAR_FULL + 8 * (N_WQ + (w >> 1)), 0);
        const uint32_t tb = sb + SM_RING + (N_WQ + (w >> 1)) * TILE_BYTES + (w & 1) * 8192;
#pragma unroll
        for (int i = 0; i < 16; i++) ldsm4t(tb + (i >> 2) * 2048 + (sw128 ^ ((i & 3) * 32)), A[i]);
        __syncwarp();
        if (lane == 0) mbar_arrive_n(sb + BAR_EMPTY + 8 * (N_WQ + (w >> 1)), 4);

        Pkt2 m;
        for (uint32_t n = 0, k = 0; n < SPIN_LIMIT; n++) {
            fetch_mod(k ^ 4096);
            asm volatile("cp.async.wait_group 1;" ::: "memory");
            const uint4 u = lds128(ms + k);
            m.a = u.x | (u64)u.y << 32; m.b = u.z | (u64)u.w << 32;
            if (__all_sync(~0u, pkt_ok(m, tag))) break;
            k ^= 4096;
        }
        const uint32_t ca0 = __shfl_xor_sync(~0u, lo32(m.a), 16), ca1 = __shfl_xor_sync(~0u, lo32(m.b), 16);
        const uint32_t v0 = ln_mod2(xh0, mean2, rsd, hadd2(ONE2, ca0), lo32(m.a));
        const uint32_t v1 = ln_mod2(xh1, mean2, rsd, hadd2(ONE2, ca1), lo32(m.b));
        float acc[4][4];
#pragma unroll
        for (int i = 0; i < 4; i++) { acc[i][0] = acc[i][1] = acc[i][2] = acc[i][3] = 0.f; }
#pragma unroll
        for (int s4 = 0; s4 < 4; s4++) {
            const uint32_t b0 = __shfl_sync(~0u, v0, 4 * s4 + t), b1 = __shfl_sync(~0u, v1, 4 * s4 + t);
#pragma unroll
            for (int i = 0; i < 4; i++) mma4(acc[i], A[4 * s4 + i], b0, b1);
        }
        sts32f(sb + SM_OP + (w * 64 + 16 * t + g) * 4, sel(t2, sel(t1, acc[3][0], acc[2][0]), sel(t1, acc[1][0], acc[0][0])));
        sts32f(sb + SM_OP + (w * 64 + 16 * t + 8 + g) * 4, sel(t2, sel(t1, acc[3][2], acc[2][2]), sel(t1, acc[1][2], acc[0][2])));
        cbar();
        if (w == 0) {
            float2 sum = make_float2(0.f, 0.f);
#pragma unroll
            for (int i = 0; i < 8; i++) { const float2 u = lds64f(sb + SM_OP + (i * 64 + 2 * lane) * 4); sum.x += u.x; sum.y += u.y; }
            const uint32_t v = pack2(sum.x, sum.y), a = sb + SM_Q + rank * 128 + lane * 4;
            st_async_b32(mapa(a, rank ^ 1), v, mapa(sb + BAR_XQ, rank ^ 1));
            st_async_b32(mapa(a, rank), v, mapa(sb + BAR_XQ, rank));
        }
        mbar_wait_cluster(sb + BAR_XQ, 0);
    }

    Pkt2 mga, msb, mcb;
    uint32_t tx0, tx1;
    const uint2* tmp = &g_mod[ob][32 * w + 2 * (lane & 15)];
    {
        uint4 Q[4];
        uint32_t koff[4];
#pragma unroll
        for (int i = 0; i < 4; i++) {
            const int ch = t + 4 * (i ^ (g & 1));
            Q[i] = lds128(sb + SM_Q + ch * 16);
            koff[i] = (sub * 16 + g) * 256 + ch * 16;
        }
        float mx = -INFINITY;
        int stage = N_K + grp, phase = 0;
#pragma unroll 1
        for (int it = 0; it < NT / 2; it++) {
            const uint32_t tb = sb + SM_RING + stage * TILE_BYTES;
            mbar_wait(sb + BAR_FULL + 8 * stage, phase);
            uint4 Ka[4], Kb[4];
#pragma unroll
            for (int i = 0; i < 4; i++) { Ka[i] = lds128(tb + koff[i]); Kb[i] = lds128(tb + koff[i] + 2048); }
            float c0[4] = {0.f, 0.f, 0.f, 0.f}, c1[4] = {0.f, 0.f, 0.f, 0.f};
#pragma unroll
            for (int i = 0; i < 4; i++) {
                mma(c0, Ka[i].x, Kb[i].x, Ka[i].y, Kb[i].y, Q[i].x, Q[i].y);
                mma(c1, Ka[i].z, Kb[i].z, Ka[i].w, Kb[i].w, Q[i].z, Q[i].w);
            }
            __syncwarp();
            if (lane == 0) mbar_arrive_n(sb + BAR_EMPTY + 8 * stage, 2);
            const float lo = (g & 1) ? c0[1] + c1[1] : c0[0] + c1[0];
            const float hi = (g & 1) ? c0[3] + c1[3] : c0[2] + c1[2];
            const float sc = rbf(rbf(t1 ? hi : lo) * 0.08838834764831845f);
            mx = fmaxf(mx, sc);
            if (t < 2) sts16(sb + SM_P + ((2 * it + grp) * 128 + rank * 64 + sub * 16 + 4 * (g >> 1) + 2 * t + (g & 1)) * 2, __float_as_uint(sc) >> 16);
            stage += 2;
            if (stage >= STAGES) { stage -= STAGES; phase ^= 1; }
        }

        mga = ld_pkt2(tmp + 2 * 256); msb = ld_pkt2(tmp + 3 * 256); mcb = ld_pkt2(tmp + 4 * 256);
        const __nv_bfloat16* xp = q_.x + ob * D_ + 64 * w + 4 * (lane & 8) + (lane & 7);
        tx0 = ldg16(xp) | ldg16(xp + 8) << 16;
        tx1 = ldg16(xp + 16) | ldg16(xp + 24) << 16;

        asm volatile("cp.async.wait_all;" ::: "memory");

#pragma unroll
        for (int m = 1; m < 32; m <<= 1) mx = fmaxf(mx, __shfl_xor_sync(~0u, mx, m));
        if (lane == 0) sts32f(sb + SM_RED + w * 4, mx);
        cbar();
        {
            const float4 u = lds128f(sb + SM_RED), v = lds128f(sb + SM_RED + 16);
            mx = fmaxf(fmaxf(fmaxf(u.x, u.y), fmaxf(u.z, u.w)), fmaxf(fmaxf(v.x, v.y), fmaxf(v.z, v.w)));
        }
        const uint32_t pa = sb + SM_P + (tid >> 3) * 256 + rank * 128 + (tid & 7) * 16;
        const uint4 s0 = lds128(pa);
        const float sc[8] = {bf_lo(s0.x), bf_hi(s0.x), bf_lo(s0.y), bf_hi(s0.y), bf_lo(s0.z), bf_hi(s0.z), bf_lo(s0.w), bf_hi(s0.w)};
        float l = 0.f;
#pragma unroll
        for (int i = 0; i < 8; i++) l += __expf(sc[i] - mx);
#pragma unroll
        for (int m = 1; m < 32; m <<= 1) l += __shfl_xor_sync(~0u, l, m);
        if (lane == 0) sts32f(sb + SM_RED + 32 + w * 4, l);
        cbar();
        {
            const float4 u = lds128f(sb + SM_RED + 32), v = lds128f(sb + SM_RED + 48);
            l = ((u.x + u.y) + (u.z + u.w)) + ((v.x + v.y) + (v.z + v.w));
        }
        if (tid == 0) st_async_v2(mapa(sb + SM_ML, rank ^ 1), mx, l, mapa(sb + BAR_XML, rank ^ 1));
        mbar_wait_cluster(sb + BAR_XML, 0);
        const float2 o = lds64f(sb + SM_ML);
        const float m = fmaxf(mx, o.x);
        const float inv = __fdividef(1.0f, l * __expf(mx - m) + o.y * __expf(o.x - m));
        const uint32_t p0 = pack2(__expf(sc[0] - m) * inv, __expf(sc[1] - m) * inv), p1 = pack2(__expf(sc[2] - m) * inv, __expf(sc[3] - m) * inv);
        const uint32_t p2 = pack2(__expf(sc[4] - m) * inv, __expf(sc[5] - m) * inv), p3 = pack2(__expf(sc[6] - m) * inv, __expf(sc[7] - m) * inv);
        st_async_v4(mapa(pa, rank ^ 1), p0, p1, p2, p3, mapa(sb + BAR_XP, rank ^ 1));
        sts128(pa, p0, p1, p2, p3);
        cbar();
        mbar_wait_cluster(sb + BAR_XP, 0);
    }

#pragma unroll 1
    for (uint32_t n = 0; n < SPIN_LIMIT && !__all_sync(~0u, pkt_ok(mga, tag) && pkt_ok(msb, tag) && pkt_ok(mcb, tag)); n++) {
        mga = ld_pkt2(tmp + 2 * 256); msb = ld_pkt2(tmp + 3 * 256); mcb = ld_pkt2(tmp + 4 * 256);
    }
    const uint32_t ga0 = lo32(mga.a), ga1 = lo32(mga.b), sb0 = lo32(msb.a), sb1 = lo32(msb.b);
    const uint32_t cb0 = hadd2(ONE2, lo32(mcb.a)), cb1 = hadd2(ONE2, lo32(mcb.b));
    const int wb = 4 * rank + sub;
    u64 red_p = s_line(e1_blk(1, wb), 2 * b) + lane * 4, red2_p = s_line(e1_blk(1, wb), 4 + b) + lane * 4;

    PIN64(red_p); PIN64(red2_p);
    float oa[4][4];
#pragma unroll
    for (int i = 0; i < 4; i++) { oa[i][0] = oa[i][1] = oa[i][2] = oa[i][3] = 0.f; }
    {
        int stage = N_V % STAGES, phase = tile_phase(N_V);
        auto v_tiles = [&](int v0, int v1) {
#pragma unroll 1
            for (int v = v0; v < v1; v++) {
                const uint32_t tb = sb + SM_RING + stage * TILE_BYTES + grp * 8192 + (sw128 ^ (sub * 32));
                uint2 P[4];
#pragma unroll
                for (int i = 0; i < 4; i++) P[i] = lds64(sb + SM_P + v * 256 + grp * 128 + i * 32 + t * 8);
                mbar_wait(sb + BAR_FULL + 8 * stage, phase);
                uint32_t a[4][4];
#pragma unroll
                for (int i = 0; i < 4; i++) ldsm4t(tb + i * 2048, a[i]);
#pragma unroll
                for (int i = 0; i < 4; i++) mma4(oa[i], a[i], P[i].x, P[i].y);
                __syncwarp();
                if (lane == 0) mbar_arrive(sb + BAR_EMPTY + 8 * stage);
                if (++stage == STAGES) { stage = 0; phase ^= 1; }
            }
        };
        v_tiles(0, MEET_AT);
        asm volatile("bar.sync 2, 288;" ::: "memory");
        v_tiles(MEET_AT, NT);
    }

    if (t < 2) {
        const uint32_t a = sb + SM_OP + rank * 512 + w * 64 + (g >> 1) * 16 + (g & 1) * 4 + t * 8;
        const uint32_t v = __float_as_uint(sel(t1, (oa[0][2] + oa[1][2]) + (oa[2][2] + oa[3][2]), (oa[0][0] + oa[1][0]) + (oa[2][0] + oa[3][0])));
        st_async_b32(mapa(a, rank ^ 1), v, mapa(sb + BAR_XO, rank ^ 1));
        st_async_b32(mapa(a, rank), v, mapa(sb + BAR_XO, rank));
    }
    __syncwarp();
    mbar_wait_cluster(sb + BAR_XO, 0);

    {
        float acc[4][4];
        const uint32_t o_ld = sb + SM_OP + grp * 512 + (lane & 15) * 16 + vb * 8, x_st = sb + SM_PART + 4096 + sub * 1024 + lane * 16;
        const float2 u = lds64f(o_ld), v = lds64f(o_ld + 256);
        const uint32_t o2 = pack2(u.x + v.x, u.y + v.y);
        uint32_t bo[8];
#pragma unroll
        for (int i = 0; i < 8; i++) bo[i] = __shfl_sync(~0u, o2, 16 * (i & 1) + 4 * (i >> 1) + t);
        float4 x0 = make_float4(0.f, 0.f, 0.f, 0.f), x1 = x0;
#pragma unroll
        for (int i = 0; i < 4; i++) { acc[i][0] = acc[i][1] = acc[i][2] = acc[i][3] = 0.f; }
        static_assert(N_WO % STAGES + 4 <= STAGES, "wo tiles occupy consecutive slots");
        const uint32_t wa = sb + slot_addr(N_WO) + grp * 2 * TILE_BYTES + sub * 4096, wbar = sb + full_bar(N_WO) + grp * 16;
#pragma unroll
        for (int j = 0; j < 2; j++) {
            if (j == 1 && grp) { asm volatile("bar.sync 8, 256;" ::: "memory"); x0 = lds128f(x_st); x1 = lds128f(x_st + 512); }
            mbar_wait(wbar + 8 * j, tile_phase(N_WO));
            if (j == 1) { }
#pragma unroll
            for (int i = 0; i < 8; i++) ldsm4t(wa + j * TILE_BYTES + (i >> 2) * 2048 + (sw128 ^ ((i & 3) * 32)), A[8 * j + i]);
#pragma unroll
            for (int i = 0; i < 8; i++) mma4(acc[i & 3], A[8 * j + i], bo[4 * j + 2 * (i >> 2)], bo[4 * j + 2 * (i >> 2) + 1]);
        }
        if (!grp) {
            sts128f(x_st, acc[0][0], acc[1][0], acc[2][0], acc[3][0]); sts128f(x_st + 512, acc[0][2], acc[1][2], acc[2][2], acc[3][2]);
            asm volatile("bar.arrive 8, 256;" ::: "memory");
        } else {
            acc[0][0] += x0.x; acc[1][0] += x0.y; acc[2][0] += x0.z; acc[3][0] += x0.w; acc[0][2] += x1.x; acc[1][2] += x1.y; acc[2][2] += x1.z; acc[3][2] += x1.w;
            const float r0 = sel(t2, sel(t1, 1.0f, acc[1][0]), sel(t1, acc[0][2], acc[0][0]));
            const float r1 = sel(t2, sel(t1, 1.0f, acc[3][0]), sel(t1, acc[2][2], acc[2][0]));
            const float r2 = sel(t2, 1.0f, sel(t1, acc[3][2], acc[1][2]));
            asm volatile("red.relaxed.gpu.global.add.f32 [%0], %2;\nred.relaxed.gpu.global.add.f32 [%0 + 256], %3;\nred.relaxed.gpu.global.add.f32 [%1], %4;"
                         :: "l"(red_p), "l"(red2_p), "f"(r0), "f"(r1), "f"(r2) : "memory");
            asm volatile("red.relaxed.gpu.global.add.f32 [%0], %2;\nred.relaxed.gpu.global.add.f32 [%0 + 256], %3;\nred.relaxed.gpu.global.add.f32 [%1], %4;"
                         :: "l"(red_p ^ 4096), "l"(red2_p ^ 4096), "f"(r0), "f"(r1), "f"(r2) : "memory");
        }
    }

    constexpr uint32_t CNT = 0x42000000u;
    if (is_gu) {
        uint32_t side;
        asm volatile("ld.volatile.shared.u32 %0, [%1];" : "=r"(side) : "r"(sb + SM_SIDE) : "memory");
        u64 acc_p = (s_line(e1_blk(0, w), lane >> 3) + (lane & 7) * 16) ^ side, acc2_p = (s_line(e1_blk(0, w), 4 + ob) + (lane & 7) * 16) ^ side;
        const int eb = e1_blk(w >> 2, w & 3);
        const uint32_t near = (w >> 2) * 4096 == side;
        u64 out_p = s_line(eb, lane >> 3) + S_OUT + (lane & 7) * 16, out2_p = s_line(eb, 4 + ob) + S_OUT + (lane & 15) * 8;
        u64 gb_p = (s_line(e1_blk(0, w), 6 + ob) + (lane & 15) * 8) ^ side, y_p = (u64)(q_.out + t1 * D_ + 64 * w + 4 * t2 + g);
        PIN64(acc_p); PIN64(acc2_p); PIN64(out_p); PIN64(out2_p); PIN64(gb_p); PIN64(y_p);
        auto keep = [&](uint32_t x) { return __shfl_sync(~0u, x, lane); };
        const int src = keep(8 * (g & 2) + t), src1 = keep(src + 4), src2 = keep(src + 8), src3 = keep(src + 12);
        const uint32_t p_st = keep(sb + SM_PART + w * 512 + lane * 16), r_st = keep(sb + SM_RED + (vb * 8 + w) * 8);
        tx0 = keep(tx0); tx1 = keep(tx1);
        const uint32_t g1 = g & 1;
        uint32_t cp[8], cn[8];
        float acc[4][4];
#pragma unroll
        for (int i = 0; i < 8; i++) {
            cp[i] = __shfl_sync(~0u, (i & 1) ? cb1 : cb0, 4 * (i >> 1) + src);
            cn[i] = selu(g1, __shfl_sync(~0u, (i & 1) ? sb1 : sb0, 4 * (i >> 1) + src), cp[i]);
        }
        const int frow = (lane & 7) + (lane & 16);
        const uint32_t fa = sb + slot_addr(N_FFN) + grp * 2 * TILE_BYTES + (64 * sub + frow) * 64 + ((lch ^ ((frow >> 1) & 3)) << 4);
        mbar_wait(sb + BAR_FFN + 8 * (w * NQ >> 3), 0);
        uint4 u = ld_strong128(acc_p), v = ld_strong128(acc2_p);
#pragma unroll
        for (int i = 0; i < 16; i++) ldsm4t((fa ^ ((i & 1) * 32)) + (i >> 3) * 2048 + ((i >> 2) & 1) * 512 + ((i >> 1) & 1) * TILE_BYTES, A[i]);
#pragma unroll
        for (int i = 0; i < 4; i++) { acc[i][0] = acc[i][1] = acc[i][2] = acc[i][3] = 0.f; }
#pragma unroll
        for (int i = 0; i < 16; i++) mma4(acc[i & 3], A[i], cn[2 * (i >> 2)], cn[2 * (i >> 2) + 1]);
        sts128f(sb + SM_P + w * 1024 + lane * 16, sel(t2, acc[1][0], acc[0][0]), sel(t2, acc[3][0], acc[2][0]), sel(t2, acc[1][2], acc[0][2]), sel(t2, acc[3][2], acc[2][2]));
        sts128f(sb + SM_P + w * 1024 + 512 + lane * 16, sel(t2, acc[1][1], acc[0][1]), sel(t2, acc[3][1], acc[2][1]), sel(t2, acc[1][3], acc[0][3]), sel(t2, acc[3][3], acc[2][3]));
        bar_arrive<3>();
#pragma unroll
        for (int i = 0; i < 8; i++) cn[i] = selu(g1, cp[i] ^ 0x80008000u, 0u);
        settle(tag, sb + SM_OP, cn[0], cn[1], cn[2], cn[3]); settle(tag, sb + SM_OP, cn[4], cn[5], cn[6], cn[7]);
        for (uint32_t n = 0; !__all_sync(~0u, u.w == CNT && v.w == CNT) && n < SPIN_LIMIT; n++) { u = ld_strong128(acc_p); v = ld_strong128(acc2_p); }
        const uint32_t x0 = hadd2(tx0, hmul2(ga0, pack2(__uint_as_float(u.x), __uint_as_float(u.y))));
        const uint32_t x1 = hadd2(tx1, hmul2(ga1, pack2(__uint_as_float(u.z), __uint_as_float(selu(lane & 8, v.y, v.x)))));
        float c[4] = {0.f, 0.f, 0.f, 0.f};
        mma(c, x0, ONE2, x1, ONE2, x0, x1);
#pragma unroll
        for (int i = 0; i < 4; i++) { acc[i][0] = acc[i][1] = acc[i][2] = acc[i][3] = 0.f; }
        float q, s;
#pragma unroll
        for (int s4 = 0; s4 < 4; s4++) {
            const int from = s4 == 0 ? src : s4 == 1 ? src1 : s4 == 2 ? src2 : src3;
            uint32_t b0 = __shfl_sync(~0u, x0, from), b1 = __shfl_sync(~0u, x1, from);
            b0 = hfma2(b0, cp[2 * s4], hmul2(b0, cn[2 * s4]));
            b1 = hfma2(b1, cp[2 * s4 + 1], hmul2(b1, cn[2 * s4 + 1]));
#pragma unroll
            for (int i = 0; i < 4; i++) mma4(acc[i], A[4 * s4 + i], b0, b1);
            if (s4 == 0) { q = sel(g1, c[1], c[0]); s = c[2] + c[3]; q += __shfl_xor_sync(~0u, q, 4); s += __shfl_xor_sync(~0u, s, 9); }
            if (s4 == 1) q += __shfl_xor_sync(~0u, q, 9);
            if (s4 == 2) { if (lane == 0 || lane == 18) sts64f(r_st, s, fmaxf(fmaf(s * (-1.0f / 64), s, q), 0.f)); }
        }
        sts128f(p_st, sel(t2, acc[1][0] + acc[1][1], acc[0][0] + acc[0][1]), sel(t2, acc[3][0] + acc[3][1], acc[2][0] + acc[2][1]),
                sel(t2, acc[1][2] + acc[1][3], acc[0][2] + acc[0][3]), sel(t2, acc[3][2] + acc[3][3], acc[2][2] + acc[2][3]));
        bar_arrive<4>();
        uint32_t xo[2];
#pragma unroll
        for (int j = 0; j < 2; j++) {
            const uint32_t e0 = __shfl_sync(~0u, x0, 16 * t1 + 8 * j + g), e1 = __shfl_sync(~0u, x1, 16 * t1 + 8 * j + g);
            xo[j] = __byte_perm(e0, e1, t2 ? 0x7632 : 0x5410);
        }
        mbar_wait(sb + BAR_W2 + 8 * (w * NW >> 3), 0);
        asm volatile("{\n.reg .pred p;\nsetp.ne.u32 p, %0, 0;\n@p bar.sync 6, 256;\n}" :: "r"(near) : "memory");
#pragma unroll
        for (int i = 0; i < 8; i++)
            ldsm4t(sb + slot_addr(N_FFN + 4) + w * 4096 + (i >> 2) * 2048 + (sw128 ^ ((i & 3) * 32)), A[i]);
        asm volatile("{\n.reg .pred p;\nsetp.eq.u32 p, %0, 0;\n@p bar.arrive 6, 256;\n}" :: "r"(near) : "memory");
#pragma unroll
        for (int i = 0; i < 4; i++) { acc[i][0] = acc[i][1] = acc[i][2] = acc[i][3] = 0.f; }
        bar_sync<5>();
        asm volatile("{\n.reg .pred p;\nsetp.ne.u32 p, %0, 0;\n@p bar.sync 7, 256;\n}" :: "r"(near) : "memory");
        const uint4 hv = lds128(sb + SM_Q + ((g & 2) * 2 + t) * 16);
#pragma unroll
        for (int i = 0; i < 4; i++) mma4(acc[i], A[i], hv.x, hv.y);
#pragma unroll
        for (int i = 0; i < 4; i++) mma4(acc[i], A[4 + i], hv.z, hv.w);
        float r[4], o[6];
#pragma unroll
        for (int i = 0; i < 4; i++) r[i] = sel(t2, acc[i][2], acc[i][0]);
        asm volatile("atom.relaxed.gpu.global.add.v4.f32 {%0, %1, %2, %3}, [%4], {%5, %6, %7, %8};"
                     : "=f"(o[0]), "=f"(o[1]), "=f"(o[2]), "=f"(o[4]) : "l"(out_p), "f"(r[0]), "f"(r[1]), "f"(r[2]), "f"(1.0f) : "memory");
        asm volatile("atom.relaxed.gpu.global.add.v2.f32 {%0, %1}, [%2], {%3, %4};"
                     : "=f"(o[3]), "=f"(o[5]) : "l"(out2_p), "f"(r[3]), "f"(1.0f) : "memory");
        asm volatile("{\n.reg .pred p;\nsetp.eq.u32 p, %0, 0;\n@p bar.arrive 7, 256;\n}" :: "r"(near) : "memory");
        uint2 gb = ld_strong64(gb_p);
        const uint32_t f0 = pack2(o[0] + r[0], o[1] + r[1]), f1 = pack2(o[2] + r[2], o[3] + r[3]);
#pragma unroll 1
        for (uint32_t n = 0; n < SPIN_LIMIT; n++) {
            const uint32_t y0 = hadd2(xo[0], hmul2(gb.x, f0)), y1 = hadd2(xo[1], hmul2(gb.y, f1));
            uint32_t late;
            asm volatile("{\n.reg .pred p, q, m;\n.reg .b16 a, b, c, d;\n"
                         "mov.b32 {a, b}, %6;\nmov.b32 {c, d}, %7;\nsetp.ne.b16 m, a, 0xffff;\nsetp.ne.and.b16 m, b, 0xffff, m;\nsetp.ne.and.b16 m, c, 0xffff, m;\nsetp.ne.and.b16 m, d, 0xffff, m;\n"
                         "setp.eq.and.f32 p, %4, 0f42280000, m;\nsetp.eq.and.f32 q, %5, 0f42280000, m;\n"
                         "mov.b32 {a, b}, %2;\nmov.b32 {c, d}, %3;\n"
                         "@p st.global.u16 [%1], a;\n@p st.global.u16 [%1 + 32], b;\n@p st.global.u16 [%1 + 64], c;\n@q st.global.u16 [%1 + 96], d;\n"
                         "vote.sync.all.pred m, m, 0xffffffff;\nselp.u32 %0, 0, 1, m;\n}"
                         : "=r"(late) : "l"(y_p), "r"(y0), "r"(y1), "f"(o[4]), "f"(o[5]), "r"(gb.x), "r"(gb.y) : "memory");
            if (!late) break;
            gb = ld_strong64(gb_p);
        }
    } else if (is_gb) {
        const uint32_t fa = sb + slot_addr(N_FFN) + grp * 8192 + (64 * sub + lrow) * 32 + ((lch ^ ((lrow >> 2) & 1)) << 4);
        const int dl = (lane & 7) * 4 + ((lane >> 3) & 1) * 2 + ob;
        u64 gb_p = s_line(2 * (role >> 2), 6 + (dl >> 4)) + (dl & 15) * 8 + (role & 3) * 2;
        PIN64(gb_p);
        uint32_t bs[8];
#pragma unroll
        for (int i = 0; i < 8; i++) bs[i] = __shfl_sync(~0u, (i & 1) ? sc1 : sc0, 4 * (i >> 1) + 16 * ((g >> 1) & 1) + t);
        const uint32_t c_st = sb + SM_PART + (w * 32 + t1 * 16 + (t >> 1) * 8 + g) * 4;
        settle(tag, sb + SM_OP, bs[0], bs[1], bs[2], bs[3]); settle(tag, sb + SM_OP, bs[4], bs[5], bs[6], bs[7]); settle(tag, sb + SM_OP, c_st, fa, 0, 0);
        mbar_wait(sb + BAR_FFN + 8 * grp, 0);
        float c[4][4];
#pragma unroll
        for (int s4 = 0; s4 < 4; s4++) ldsm4t(fa + s4 * 512, A[s4]);
#pragma unroll
        for (int s4 = 0; s4 < 4; s4++) { c[s4][0] = c[s4][1] = c[s4][2] = c[s4][3] = 0.f; mma4(c[s4], A[s4], bs[2 * s4], bs[2 * s4 + 1]); }
        sts32f(c_st, sel(t2, (c[0][2] + c[1][2]) + (c[2][2] + c[3][2]), (c[0][0] + c[1][0]) + (c[2][0] + c[3][0])));
        cbar();
        if (w == 0) {
            float u[8];
#pragma unroll
            for (int i = 0; i < 8; i++) u[i] = lds32f(sb + SM_PART + i * 128 + lane * 4);
            const uint16_t v = (uint16_t)pack2(((u[0] + u[1]) + (u[2] + u[3])) + ((u[4] + u[5]) + (u[6] + u[7])), 0.f);
            asm volatile("st.relaxed.gpu.global.u16 [%0], %1;\nst.relaxed.gpu.global.u16 [%0 + 4096], %1;" :: "l"(gb_p), "h"(v) : "memory");
        }
    }
}

typedef CUresult (*EncodeFn)(CUtensorMap*, CUtensorMapDataType, cuuint32_t, void*, const cuuint64_t*, const cuuint64_t*,
                             const cuuint32_t*, const cuuint32_t*, CUtensorMapInterleave, CUtensorMapSwizzle,
                             CUtensorMapL2promotion, CUtensorMapFloatOOBfill);

void make_map(EncodeFn enc, CUtensorMap* m, void* ptr, int cols, int rows, int box_cols, int box_rows, CUtensorMapSwizzle sw) {
    cuuint64_t gd[2] = {(cuuint64_t)cols, (cuuint64_t)rows}, gs[1] = {(cuuint64_t)cols * 2};
    cuuint32_t bd[2] = {(cuuint32_t)box_cols, (cuuint32_t)box_rows}, es[2] = {1, 1};
    enc(m, CU_TENSOR_MAP_DATA_TYPE_BFLOAT16, 2, ptr, gd, gs, bd, es, CU_TENSOR_MAP_INTERLEAVE_NONE, sw,
        CU_TENSOR_MAP_L2_PROMOTION_NONE, CU_TENSOR_MAP_FLOAT_OOB_FILL_NONE);
}

}

extern "C" void kernel_launch(void* const* d_in, const int* in_sizes, int n_in, void* d_out, int out_size) {
    (void)in_sizes; (void)n_in; (void)out_size;
    static EncodeFn enc = nullptr;
    if (!enc) {
        void* fn = nullptr;
        cudaDriverEntryPointQueryResult qr;
        cudaGetDriverEntryPoint("cuTensorMapEncodeTiled", &fn, cudaEnableDefault, &qr);
        enc = (EncodeFn)fn;
        cudaFuncSetAttribute(fused_decode_kernel, cudaFuncAttributeMaxDynamicSharedMemorySize, SMEM_BYTES);
    }
    Params p;
    Ptrs q;
    make_map(enc, &p.m_wmod, d_in[10], MODW, D_, 32, 256, CU_TENSOR_MAP_SWIZZLE_64B);
    make_map(enc, &p.m_wq, d_in[3], QD, D_, 64, 128, CU_TENSOR_MAP_SWIZZLE_128B);
    make_map(enc, &p.m_v, d_in[2], DH, 64 * SK, 64, 128, CU_TENSOR_MAP_SWIZZLE_128B);
    {
        cuuint64_t gd[3] = {64, QD, 8}, gs[2] = {D_ * 2, 128};
        cuuint32_t bd[3] = {64, 32, 4}, es[3] = {1, 1, 1};
        enc(&p.m_wo, CU_TENSOR_MAP_DATA_TYPE_BFLOAT16, 3, d_in[4], gd, gs, bd, es, CU_TENSOR_MAP_INTERLEAVE_NONE,
            CU_TENSOR_MAP_SWIZZLE_128B, CU_TENSOR_MAP_L2_PROMOTION_NONE, CU_TENSOR_MAP_FLOAT_OOB_FILL_NONE);
    }
    for (int i = 0; i < 2; i++) {
        cuuint64_t gd[4] = {FF, 2, 8, D_ / 16}, gs[3] = {8 * FF * 2, FF * 2, 16 * FF * 2};
        cuuint32_t bd[4] = {32, 2, 8, 32 / NQ}, es[4] = {1, 1, 1, 1};
        enc(i ? &p.m_w3 : &p.m_w1, CU_TENSOR_MAP_DATA_TYPE_BFLOAT16, 4, d_in[6 + i], gd, gs, bd, es, CU_TENSOR_MAP_INTERLEAVE_NONE,
            CU_TENSOR_MAP_SWIZZLE_64B, CU_TENSOR_MAP_L2_PROMOTION_NONE, CU_TENSOR_MAP_FLOAT_OOB_FILL_NONE);
    }
    {
        cuuint64_t gd[5] = {64, 2, 8, FF / 16, 8}, gs[4] = {8 * D_ * 2, D_ * 2, 16 * D_ * 2, 128};
        cuuint32_t bd[5] = {64, 2, 8, 2, 8 / NW}, es[5] = {1, 1, 1, 1, 1};
        enc(&p.m_w2, CU_TENSOR_MAP_DATA_TYPE_BFLOAT16, 5, d_in[8], gd, gs, bd, es, CU_TENSOR_MAP_INTERLEAVE_NONE,
            CU_TENSOR_MAP_SWIZZLE_128B, CU_TENSOR_MAP_L2_PROMOTION_NONE, CU_TENSOR_MAP_FLOAT_OOB_FILL_NONE);
    }
    make_map(enc, &p.m_gb, d_in[10], MODW, D_, 16, 256, CU_TENSOR_MAP_SWIZZLE_32B);
    q.x = (const __nv_bfloat16*)d_in[0];
    q.kwin = (const __nv_bfloat16*)d_in[1] + (size_t)(SK - WIN) * DH;
    q.c = (const __nv_bfloat16*)d_in[9];
    q.out = (__nv_bfloat16*)d_out;
    fused_decode_kernel<<<NCTA, THREADS, SMEM_BYTES, cudaStreamPerThread>>>(q, p);
}
```

```cpp
#include <cuda_runtime.h>
#include <cuda.h>
#include <cuda_bf16.h>
#include <stdint.h>

namespace {

constexpr int D_ = 512, DH = 128, SK = 16384, WIN = 4096, FF = 1376, QD = 4096, MODW = 3072;
constexpr int NCTA = 128;
constexpr int TILE_BYTES = 16384;
constexpr int NT = 32;
constexpr int STAGES = 13;
constexpr int K_FIRST = 2;
constexpr int FIRST_N = 5;
constexpr int MEET_AT = 16;
constexpr int PACE = 656;
constexpr int LEAD_NS = 1290;
constexpr int GATE_X = 25;
constexpr int POLL_NS = 300;
constexpr int ALPHA16 = 4;
constexpr int GU_NS = 4630;
constexpr int W2_NS = 5860;
constexpr int GB_LEAD = 370;
constexpr int NQ = 8;
constexpr int PROBES = 6;
constexpr int PROBE_NS = 1000;
constexpr int EARLY_NS = 800;
constexpr int NW = 4;
constexpr int HEAD_TID = 256;
constexpr int N_WMOD = 0, N_WQ = 2, N_K = 6, N_V = N_K + NT, N_WO = N_V + NT, N_FFN = N_WO + 4;
constexpr int N_GATE = N_V + GATE_X;
constexpr int THREADS = 320;
constexpr int N_MOD_CTA = 80;
#define SPIN_LIMIT_S "4194304"
constexpr unsigned SPIN_LIMIT = 1u << 22;

constexpr int SM_RING = 0;
constexpr int SM_P = STAGES * TILE_BYTES;
constexpr int SM_PART = SM_P + WIN * 2;
constexpr int SM_OP = SM_PART + 8192;
constexpr int SM_Q = SM_OP + 2048;
constexpr int SM_RED = SM_Q + 256;
constexpr int SM_ML = SM_RED + 128;
constexpr int SM_PROG = SM_ML + 16;
constexpr int SM_SIDE = SM_PROG + 16;
constexpr int SM_BAR = SM_SIDE + 16;
constexpr int BAR_FULL = SM_BAR, BAR_EMPTY = SM_BAR + 8 * STAGES, BAR_XQ = SM_BAR + 16 * STAGES,
              BAR_XML = BAR_XQ + 8, BAR_XP = BAR_XQ + 16, BAR_XO = BAR_XQ + 24, BAR_FFN = BAR_XQ + 32;
constexpr int BAR_W2 = BAR_FFN + 8 * NQ;
constexpr int SMEM_BYTES = BAR_W2 + 8 * NW;
static_assert(SMEM_BYTES <= 232448, "shared memory");
__host__ __device__ constexpr uint32_t slot_addr(int n) { return SM_RING + (n % STAGES) * TILE_BYTES; }
__host__ __device__ constexpr uint32_t full_bar(int n) { return BAR_FULL + 8 * (n % STAGES); }
__host__ __device__ constexpr uint32_t empty_bar(int n) { return BAR_EMPTY + 8 * (n % STAGES); }
__host__ __device__ constexpr uint32_t tile_phase(int n) { return (n / STAGES) & 1; }
static_assert((N_FFN + 4) % STAGES + 2 <= STAGES && N_FFN % STAGES + 4 <= STAGES, "w1/w3 tiles and w2 tiles occupy consecutive slots");
static_assert(GATE_X >= MEET_AT && N_GATE - STAGES < N_V + MEET_AT && N_FFN + 5 - 2 * STAGES < N_V + MEET_AT && N_FFN + 5 - STAGES < N_WO,
              "barrier parities the helper warp waits on are unambiguous after the rendezvous; the wo tiles are not replaced");
__host__ __device__ constexpr int fill_tile(int j) { return j < K_FIRST ? N_K + j : j < K_FIRST + N_K ? j - K_FIRST : j; }

struct Ptrs {
    const __nv_bfloat16 *kwin, *x, *c;
    __nv_bfloat16* out;
};
struct Params {
    CUtensorMap m_wmod, m_wq, m_v, m_wo, m_w1, m_w3, m_w2, m_gb;
};

__device__ unsigned g_epoch;
__device__ __align__(128) uint2 g_mod[2][5 * D_ / 2];
__device__ __align__(256) unsigned char g_s[131072];
__device__ __forceinline__ unsigned long long s_line(int blk, int i) {
    return (((unsigned long long)g_s + 65535) & ~65535ull) + blk * 4096 + (i >> 1) * 1024 + (i & 1) * 256;
}
__device__ __forceinline__ int e1_blk(int r, int w) { return 2 * w + (r ^ (w & 1)); }
constexpr int S_OUT = 512, S_PROG = 128;
__device__ __align__(128) unsigned g_clear;

typedef unsigned long long u64;
__device__ __forceinline__ unsigned time_ns() {
    unsigned r;
    asm volatile("mov.u32 %0, %%globaltimer_lo;" : "=r"(r));
    return r;
}
__device__ __forceinline__ bool elect_one() {
    uint32_t r;
    asm volatile("{\n.reg .pred p;\nelect.sync _|p, 0xffffffff;\nselp.u32 %0, 1, 0, p;\n}" : "=r"(r));
    return r != 0;
}
#define PIN64(v) asm volatile("" : "+l"(v))

__device__ __forceinline__ void mbar_init(uint32_t bar, uint32_t cnt) {
    asm volatile("mbarrier.init.shared::cta.b64 [%0], %1;" :: "r"(bar), "r"(cnt) : "memory");
}
__device__ __forceinline__ void mbar_expect_tx(uint32_t bar, uint32_t bytes) {
    asm volatile("mbarrier.arrive.expect_tx.shared::cta.b64 _, [%0], %1;" :: "r"(bar), "r"(bytes) : "memory");
}
__device__ __forceinline__ void mbar_arrive(uint32_t bar) {
    asm volatile("mbarrier.arrive.shared::cta.b64 _, [%0];" :: "r"(bar) : "memory");
}
__device__ __forceinline__ void mbar_arrive_n(uint32_t bar, uint32_t n) {
    asm volatile("mbarrier.arrive.shared::cta.b64 _, [%0], %1;" :: "r"(bar), "r"(n) : "memory");
}
__device__ __forceinline__ void mbar_wait(uint32_t bar, uint32_t parity) {
    asm volatile("{\n.reg .pred p;\n.reg .u32 n;\nmov.u32 n, 0;\nW0:\n"
                 "mbarrier.try_wait.parity.shared::cta.b64 p, [%0], %1;\n@p bra W1;\n"
                 "add.u32 n, n, 1;\nsetp.lt.u32 p, n, " SPIN_LIMIT_S ";\n@p bra W0;\nW1:\n}"
                 :: "r"(bar), "r"(parity) : "memory");
}
__device__ __forceinline__ void mbar_wait_cluster(uint32_t bar, uint32_t parity) {
    asm volatile("{\n.reg .pred p;\n.reg .u32 n;\nmov.u32 n, 0;\nW0:\n"
                 "mbarrier.try_wait.parity.acquire.cluster.shared::cta.b64 p, [%0], %1;\n@p bra W1;\n"
                 "add.u32 n, n, 1;\nsetp.lt.u32 p, n, " SPIN_LIMIT_S ";\n@p bra W0;\nW1:\n}"
                 :: "r"(bar), "r"(parity) : "memory");
}
__device__ __forceinline__ void bulk_load(uint32_t dst, const void* src, uint32_t bytes, uint32_t bar, uint64_t pol) {
    asm volatile("cp.async.bulk.shared::cluster.global.mbarrier::complete_tx::bytes.L2::cache_hint [%0], [%1], %2, [%3], %4;"
                 :: "r"(dst), "l"(src), "r"(bytes), "r"(bar), "l"(pol) : "memory");
}
__device__ __forceinline__ void tma2d(uint32_t dst, const CUtensorMap* m, int c0, int c1, uint32_t bar) {
    asm volatile("cp.async.bulk.tensor.2d.shared::cluster.global.mbarrier::complete_tx::bytes [%0], [%1, {%3, %4}], [%2];"
                 :: "r"(dst), "l"(m), "r"(bar), "r"(c0), "r"(c1) : "memory");
}
__device__ __forceinline__ void tma2d_hint(uint32_t dst, const CUtensorMap* m, int c0, int c1, uint32_t bar, uint64_t pol) {
    asm volatile("cp.async.bulk.tensor.2d.shared::cluster.global.mbarrier::complete_tx::bytes.L2::cache_hint [%0], [%1, {%3, %4}], [%2], %5;"
                 :: "r"(dst), "l"(m), "r"(bar), "r"(c0), "r"(c1), "l"(pol) : "memory");
}
__device__ __forceinline__ void tma3d(uint32_t dst, const CUtensorMap* m, int c0, int c1, int c2, uint32_t bar) {
    asm volatile("cp.async.bulk.tensor.3d.shared::cluster.global.mbarrier::complete_tx::bytes [%0], [%1, {%3, %4, %5}], [%2];"
                 :: "r"(dst), "l"(m), "r"(bar), "r"(c0), "r"(c1), "r"(c2) : "memory");
}
__device__ __forceinline__ void tma4d(uint32_t dst, const CUtensorMap* m, int c0, int c3, uint32_t bar) {
    asm volatile("cp.async.bulk.tensor.4d.shared::cluster.global.mbarrier::complete_tx::bytes [%0], [%1, {%3, %5, %5, %4}], [%2];"
                 :: "r"(dst), "l"(m), "r"(bar), "r"(c0), "r"(c3), "r"(0) : "memory");
}
__device__ __forceinline__ void tma5d(uint32_t dst, const CUtensorMap* m, int c3, int c4, uint32_t bar) {
    asm volatile("cp.async.bulk.tensor.5d.shared::cluster.global.mbarrier::complete_tx::bytes [%0], [%1, {%5, %5, %5, %3, %4}], [%2];"
                 :: "r"(dst), "l"(m), "r"(bar), "r"(c3), "r"(c4), "r"(0) : "memory");
}
__device__ __forceinline__ uint32_t mapa(uint32_t addr, uint32_t rank) {
    uint32_t r;
    asm("mapa.shared::cluster.u32 %0, %1, %2;" : "=r"(r) : "r"(addr), "r"(rank));
    return r;
}
__device__ __forceinline__ void st_async_b32(uint32_t addr, uint32_t v, uint32_t bar) {
    asm volatile("st.async.weak.shared::cluster.mbarrier::complete_tx::bytes.b32 [%0], %1, [%2];" :: "r"(addr), "r"(v), "r"(bar) : "memory");
}
__device__ __forceinline__ void st_async_v2(uint32_t addr, float a, float b, uint32_t bar) {
    asm volatile("st.async.weak.shared::cluster.mbarrier::complete_tx::bytes.v2.f32 [%0], {%1, %2}, [%3];" :: "r"(addr), "f"(a), "f"(b), "r"(bar) : "memory");
}
__device__ __forceinline__ void st_async_v4(uint32_t addr, uint32_t a, uint32_t b, uint32_t c, uint32_t d, uint32_t bar) {
    asm volatile("st.async.weak.shared::cluster.mbarrier::complete_tx::bytes.v4.b32 [%0], {%1, %2, %3, %4}, [%5];"
                 :: "r"(addr), "r"(a), "r"(b), "r"(c), "r"(d), "r"(bar) : "memory");
}
template <int ID> __device__ __forceinline__ void bar_sync() { asm volatile("bar.sync %0, 288;" :: "n"(ID) : "memory"); }
template <int ID> __device__ __forceinline__ void bar_arrive() { asm volatile("bar.arrive %0, 288;" :: "n"(ID) : "memory"); }
__device__ __forceinline__ void cbar() { asm volatile("bar.sync 1, 256;" ::: "memory"); }

__device__ __forceinline__ uint4 ldg128(const void* p) {
    uint4 v;
    asm volatile("ld.global.nc.v4.u32 {%0,%1,%2,%3}, [%4];" : "=r"(v.x), "=r"(v.y), "=r"(v.z), "=r"(v.w) : "l"(p));
    return v;
}
__device__ __forceinline__ uint32_t ldg16(const void* p) {
    uint16_t v;
    asm volatile("ld.global.nc.u16 %0, [%1];" : "=h"(v) : "l"(p));
    return v;
}
__device__ __forceinline__ uint4 ld_strong128(unsigned long long p) {
    uint4 v;
    asm volatile("ld.relaxed.gpu.global.v4.b32 {%0,%1,%2,%3}, [%4];" : "=r"(v.x), "=r"(v.y), "=r"(v.z), "=r"(v.w) : "l"(p) : "memory");
    return v;
}
__device__ __forceinline__ uint2 ld_strong64(unsigned long long p) {
    uint2 v;
    asm volatile("ld.relaxed.gpu.global.v2.b32 {%0,%1}, [%2];" : "=r"(v.x), "=r"(v.y) : "l"(p) : "memory");
    return v;
}
__device__ __forceinline__ uint32_t ldg32(const void* p) {
    uint32_t v;
    asm volatile("ld.global.nc.u32 %0, [%1];" : "=r"(v) : "l"(p));
    return v;
}
struct Pkt2 { u64 a, b; };
__device__ __forceinline__ uint32_t lo32(u64 v) { return (uint32_t)v; }
__device__ __forceinline__ uint32_t hi32(u64 v) { return (uint32_t)(v >> 32); }
__device__ __forceinline__ Pkt2 ld_pkt2(const void* p) {
    Pkt2 r;
    asm volatile("ld.relaxed.gpu.global.v2.b64 {%0,%1}, [%2];" : "=l"(r.a), "=l"(r.b) : "l"(p) : "memory");
    return r;
}
__device__ __forceinline__ bool pkt_ok(const Pkt2& r, uint32_t tag) { return hi32(r.a) == tag && hi32(r.b) == tag; }
__device__ __forceinline__ void st_pkt(u64 p, uint32_t data, uint32_t tag) {
    asm volatile("{\n.reg .b64 v;\nmov.b64 v, {%1, %2};\nst.relaxed.gpu.global.b64 [%0], v;\n}" :: "l"(p), "r"(data), "r"(tag) : "memory");
}
__device__ __forceinline__ uint4 lds128(uint32_t a) {
    uint4 v;
    asm volatile("ld.shared.v4.u32 {%0,%1,%2,%3}, [%4];" : "=r"(v.x), "=r"(v.y), "=r"(v.z), "=r"(v.w) : "r"(a) : "memory");
    return v;
}
__device__ __forceinline__ float4 lds128f(uint32_t a) {
    float4 v;
    asm volatile("ld.shared.v4.f32 {%0,%1,%2,%3}, [%4];" : "=f"(v.x), "=f"(v.y), "=f"(v.z), "=f"(v.w) : "r"(a) : "memory");
    return v;
}
__device__ __forceinline__ uint2 lds64(uint32_t a) {
    uint2 v;
    asm volatile("ld.shared.v2.u32 {%0,%1}, [%2];" : "=r"(v.x), "=r"(v.y) : "r"(a) : "memory");
    return v;
}
__device__ __forceinline__ float2 lds64f(uint32_t a) {
    float2 v;
    asm volatile("ld.shared.v2.f32 {%0,%1}, [%2];" : "=f"(v.x), "=f"(v.y) : "r"(a) : "memory");
    return v;
}
__device__ __forceinline__ float lds32f(uint32_t a) {
    float v;
    asm volatile("ld.shared.f32 %0, [%1];" : "=f"(v) : "r"(a) : "memory");
    return v;
}
__device__ __forceinline__ void sts64f(uint32_t a, float x, float y) {
    asm volatile("st.shared.v2.f32 [%0], {%1,%2};" :: "r"(a), "f"(x), "f"(y) : "memory");
}
__device__ __forceinline__ void sts128f(uint32_t a, float x, float y, float z, float w) {
    asm volatile("st.shared.v4.f32 [%0], {%1,%2,%3,%4};" :: "r"(a), "f"(x), "f"(y), "f"(z), "f"(w) : "memory");
}
__device__ __forceinline__ void sts32f(uint32_t a, float x) {
    asm volatile("st.shared.f32 [%0], %1;" :: "r"(a), "f"(x) : "memory");
}
__device__ __forceinline__ void sts128(uint32_t a, uint32_t x, uint32_t y, uint32_t z, uint32_t w) {
    asm volatile("st.shared.v4.u32 [%0], {%1,%2,%3,%4};" :: "r"(a), "r"(x), "r"(y), "r"(z), "r"(w) : "memory");
}
__device__ __forceinline__ void settle(uint32_t tag, uint32_t a, uint32_t x, uint32_t y, uint32_t z, uint32_t w) {
    asm volatile("{\n.reg .pred p;\nsetp.eq.u32 p, %0, 0;\n@p st.shared.v4.u32 [%1], {%2,%3,%4,%5};\n}" :: "r"(tag), "r"(a), "r"(x), "r"(y), "r"(z), "r"(w) : "memory");
}
__device__ __forceinline__ void settle(uint32_t tag, uint32_t a, const float4& v) {
    settle(tag, a, __float_as_uint(v.x), __float_as_uint(v.y), __float_as_uint(v.z), __float_as_uint(v.w));
}
__device__ __forceinline__ void sts16(uint32_t a, uint32_t x) {
    asm volatile("st.shared.u16 [%0], %1;" :: "r"(a), "h"((uint16_t)x) : "memory");
}
__device__ __forceinline__ void ldsm4t(uint32_t a, uint32_t (&r)[4]) {
    asm volatile("ldmatrix.sync.aligned.m8n8.x4.trans.shared.b16 {%0,%1,%2,%3}, [%4];"
                 : "=r"(r[0]), "=r"(r[1]), "=r"(r[2]), "=r"(r[3]) : "r"(a) : "memory");
}
__device__ __forceinline__ void mma(float (&c)[4], uint32_t a0, uint32_t a1, uint32_t a2, uint32_t a3, uint32_t b0, uint32_t b1) {
    asm volatile("mma.sync.aligned.m16n8k16.row.col.f32.bf16.bf16.f32 {%0,%1,%2,%3}, {%4,%5,%6,%7}, {%8,%9}, {%0,%1,%2,%3};"
                 : "+f"(c[0]), "+f"(c[1]), "+f"(c[2]), "+f"(c[3]) : "r"(a0), "r"(a1), "r"(a2), "r"(a3), "r"(b0), "r"(b1));
}
__device__ __forceinline__ void mma4(float (&c)[4], const uint32_t (&a)[4], uint32_t b0, uint32_t b1) { mma(c, a[0], a[1], a[2], a[3], b0, b1); }
__device__ __forceinline__ float sel(uint32_t c, float a, float b) {
    float r;
    asm("{\n.reg .pred p;\nsetp.ne.u32 p, %3, 0;\nselp.f32 %0, %1, %2, p;\n}" : "=f"(r) : "f"(a), "f"(b), "r"(c));
    return r;
}
__device__ __forceinline__ float bf_lo(uint32_t v) { return __uint_as_float(v << 16); }
__device__ __forceinline__ float bf_hi(uint32_t v) { return __uint_as_float(v & 0xffff0000u); }
__device__ __forceinline__ uint32_t pack2(float lo, float hi) {
    uint32_t r;
    asm("cvt.rn.bf16x2.f32 %0, %1, %2;" : "=r"(r) : "f"(hi), "f"(lo));
    return r;
}
__device__ __forceinline__ float rbf(float x) { return __uint_as_float(pack2(0.f, x)); }
__device__ __forceinline__ uint32_t hadd2(uint32_t a, uint32_t b) { uint32_t r; asm("add.rn.bf16x2 %0, %1, %2;" : "=r"(r) : "r"(a), "r"(b)); return r; }
__device__ __forceinline__ uint32_t hsub2(uint32_t a, uint32_t b) { uint32_t r; asm("sub.rn.bf16x2 %0, %1, %2;" : "=r"(r) : "r"(a), "r"(b)); return r; }
__device__ __forceinline__ uint32_t hmul2(uint32_t a, uint32_t b) { uint32_t r; asm("mul.rn.bf16x2 %0, %1, %2;" : "=r"(r) : "r"(a), "r"(b)); return r; }
__device__ __forceinline__ uint32_t hfma2(uint32_t a, uint32_t b, uint32_t c) { uint32_t r; asm("fma.rn.bf16x2 %0, %1, %2, %3;" : "=r"(r) : "r"(a), "r"(b), "r"(c)); return r; }
__device__ __forceinline__ uint32_t selu(uint32_t c, uint32_t a, uint32_t b) { return __float_as_uint(sel(c, __uint_as_float(a), __uint_as_float(b))); }
constexpr uint32_t ONE2 = 0x3f803f80u;
__device__ __forceinline__ float silu_f(float x) {
    float e, r;
    asm("ex2.approx.ftz.f32 %0, %1;" : "=f"(e) : "f"(x * -1.4426950408889634f));
    asm("rcp.approx.ftz.f32 %0, %1;" : "=f"(r) : "f"(1.0f + e));
    return x * r;
}
__device__ __forceinline__ float rcp_sd(float m2) {
    float s, r;
    asm("sqrt.approx.ftz.f32 %0, %1;" : "=f"(s) : "f"(rbf(rbf(m2 * (1.0f / D_)) + 1e-5f)));
    asm("rcp.approx.ftz.f32 %0, %1;" : "=f"(r) : "f"(rbf(s)));
    return r;
}
__device__ __forceinline__ uint32_t ln_mod2(uint32_t x, uint32_t mean2, float rsd, uint32_t c1, uint32_t sh) {
    const uint32_t d = hsub2(x, mean2);
    return hadd2(hmul2(pack2(bf_lo(d) * rsd, bf_hi(d) * rsd), c1), sh);
}
__device__ __forceinline__ int pair_pos(int j) { return 2 * (j & 3) + (j >> 2); }

__global__ void __cluster_dims__(2, 1, 1) __launch_bounds__(THREADS, 1)
fused_decode_kernel(const __grid_constant__ Ptrs q_, const __grid_constant__ Params p) {
    extern __shared__ __align__(1024) unsigned char smem[];
    unsigned t_top;
    asm volatile("mov.u32 %0, %%globaltimer_lo;" : "=r"(t_top));
    const int tid = threadIdx.x;
    uint32_t z0;
    asm("and.b32 %0, %1, 1024;" : "=r"(z0) : "r"(tid));
    const char* kw = *(const char* const*)((const char*)&q_.kwin + z0);
    const uint32_t sb = (uint32_t)__cvta_generic_to_shared(smem);
    auto place = [](int cl) { return cl < 4 ? 8 * cl + 39 : cl - 4 + max((cl * 37 - 36 * 37) >> 8, 0); };
    uint32_t z2;
    asm("and.b32 %0, %1, 2048;" : "=r"(z2) : "r"(tid));
    const int cv = blockIdx.x + z2, pw = place(cv >> 1);
    static_assert(SK * DH * 2 == 1 << 22 && TILE_BYTES == 1 << 14, "koff");
    const char* kp;
    auto set_kp = [&](uint32_t off) {
        asm volatile("{\n.reg .u32 lo, hi;\nmov.b64 {lo, hi}, %1;\nadd.cc.u32 lo, lo, %2;\naddc.u32 hi, hi, 0;\nmov.b64 %0, {lo, hi};\n}"
                     : "=l"(kp) : "l"(kw), "r"(off));
    };
    uint64_t pol;
    asm("createpolicy.fractional.L2::evict_first.b64 %0, 1.0;" : "=l"(pol));
    auto fill_k = [&](int n) {
        mbar_expect_tx(sb + full_bar(n), TILE_BYTES);
        bulk_load(sb + slot_addr(n), kp + (n - N_K) * 2 * TILE_BYTES, TILE_BYTES, sb + full_bar(n), pol);
    };
    static_assert(K_FIRST >= 1, "head block starts with K tile 0");
    if (tid + (sb >> 28) == HEAD_TID) {
        mbar_init(sb + full_bar(N_K), 1);
        set_kp(((pw & 7) << 22) | ((pw & 8) << 24) | ((pw & 48) << 21) | ((cv & 1) << 14));
        bulk_load(sb + slot_addr(N_K), kp, TILE_BYTES, sb + full_bar(N_K), pol);
        mbar_expect_tx(sb + full_bar(N_K), TILE_BYTES);
#pragma unroll
        for (int j = 1; j < K_FIRST; j++) { mbar_init(sb + full_bar(N_K + j), 1); fill_k(N_K + j); }
    }
    __syncwarp();
    const int cta = blockIdx.x, rank = cta & 1, pv = place(cta >> 1);
    const int b = (pv >> 3) & 1, h = (pv & 7) | ((pv >> 1) & 24), bh = 32 * b + h;
    const int mc = 2 * pv + rank;
    auto first_fill = [&](int j) {
        const int n = fill_tile(j);
        if (n >= N_K) {
            fill_k(n);
        } else if (n >= N_WQ) {
            mbar_expect_tx(sb + full_bar(n), TILE_BYTES);
            tma2d(sb + slot_addr(n), &p.m_wq, h * DH + 64 * rank, 128 * (n - N_WQ), sb + full_bar(n));
        } else if (mc < N_MOD_CTA) {
            mbar_expect_tx(sb + full_bar(n), TILE_BYTES);
            tma2d(sb + slot_addr(n), &p.m_wmod, 32 * mc, 256 * n, sb + full_bar(n));
        } else {
            mbar_arrive(sb + full_bar(n));
        }
    };
    if (tid == HEAD_TID) {
#pragma unroll
        for (int j = K_FIRST; j < FIRST_N; j++) mbar_init(sb + full_bar(fill_tile(j)), 1);
#pragma unroll
        for (int j = K_FIRST; j < FIRST_N; j++) first_fill(j);
        asm volatile("fence.mbarrier_init.release.cluster;" ::: "memory");
    }
    __syncwarp();
    const int role = cta / 3;
    const bool is_gu = cta == 3 * role, is_gb = cta == 3 * role + 1 && role < 32;
    if (tid >= 288) {
        const unsigned t_start = t_top;
        asm volatile("barrier.cluster.arrive.relaxed.aligned;" ::: "memory");
        unsigned tag;
        asm volatile("ld.relaxed.gpu.global.u32 %0, [%1];" : "=r"(tag) : "l"(&g_epoch) : "memory");
        tag += 1;
        if (cta == NCTA - 1) {
#pragma unroll 2
            for (int i = tid - 288; i < 128 * 8; i += 32) {
                uint4* q = reinterpret_cast<uint4*>(s_line(i >> 6, (i >> 3) & 7)) + (i & 7);
                const uint32_t v = (i & 48) == 48 ? ~0u : 0u;
                q[0] = make_uint4(v, v, v, v);
                q[8] = q[32] = q[40] = make_uint4(0u, 0u, 0u, 0u);
            }
            __syncwarp();
            asm volatile("fence.acq_rel.gpu;" ::: "memory");
            if (tid == 288) asm volatile("st.relaxed.gpu.global.u32 [%0], %1;" :: "l"(&g_clear), "r"(tag) : "memory");
        }
        asm volatile("barrier.cluster.wait.acquire.aligned;" ::: "memory");
        mbar_wait_cluster(sb + BAR_XQ, 0);
#pragma unroll 1
        for (uint32_t n = 0; n < SPIN_LIMIT; n++) {
            unsigned c;
            asm volatile("ld.relaxed.gpu.global.u32 %0, [%1];" : "=r"(c) : "l"(&g_clear) : "memory");
            if (c == tag) break;
        }
        asm volatile("fence.acq_rel.gpu;" ::: "memory");
        asm volatile("st.volatile.shared.u32 [%0], %1;" :: "r"(sb + SM_SIDE), "r"(0) : "memory");
        asm volatile("bar.sync 2, 288;" ::: "memory");
        if (elect_one()) {
            asm volatile("prefetch.tensormap [%0];" :: "l"(is_gu ? &p.m_w1 : &p.m_gb) : "memory");
            asm volatile("prefetch.tensormap [%0];" :: "l"(&p.m_w3) : "memory");
            asm volatile("prefetch.tensormap [%0];" :: "l"(&p.m_w2) : "memory");
            const int issue = ((4 * N_GATE - 11) * PACE >> 2) - LEAD_NS;
            unsigned now, c = 0, best[2] = {~0u, ~0u}, np = is_gu ? 0 : PROBES;
            auto probe = [&]() {
                const int k = np >> 1, i = (role >> 3) + 2 * k;
                const u64 a = (s_line(e1_blk(0, role & 7), i < 6 ? i : i - 6) + (k ? 512 * k - 384 : 0)) ^ ((np & 1) << 12);
                unsigned v, c0, c1 = 0;
                asm volatile("mov.u32 %0, %%clock;" : "=r"(c0));
                asm volatile("ld.relaxed.gpu.global.u32 %0, [%1];" : "=r"(v) : "l"(a) : "memory");
                asm volatile("{\n.reg .pred p;\nsetp.ne.u32 p, %1, 0xffffffff;\n@p mov.u32 %0, %%clock;\n}" : "+r"(c1) : "r"(v));
                if (np & 1) best[1] = min(best[1], c1 - c0); else best[0] = min(best[0], c1 - c0);
                np++;
                if (!(np & 1)) asm volatile("st.volatile.shared.u32 [%0], %1;" :: "r"(sb + SM_SIDE), "r"(best[0] <= best[1] ? 0 : 4096) : "memory");
            };
#pragma unroll 1
            while (np < PROBES) {
                now = time_ns();
                if ((int)(now - t_start) >= issue + EARLY_NS) break;
                probe();
            }
            mbar_wait(sb + full_bar(N_GATE), tile_phase(N_GATE));
            now = time_ns();
            const unsigned mine = (1u << 24) + min(now - t_start, 100000u);
            const u64 prog = s_line(0, 7) + S_PROG;
            asm volatile("red.relaxed.gpu.global.add.u32 [%0], %1;" :: "l"(prog), "r"(mine) : "memory");
            if (is_gu || is_gb) {
#pragma unroll
                for (int i = 0; i < 6; i++) mbar_wait(sb + empty_bar(N_FFN + i), tile_phase(N_FFN + i) ^ 1);
#pragma unroll
                for (int i = 0; i < NQ; i++) mbar_expect_tx(sb + BAR_FFN + 8 * i, is_gu ? 65536 / NQ : 8192);
#pragma unroll
                for (int i = 0; i < NW; i++) mbar_expect_tx(sb + BAR_W2 + 8 * i, 32768 / NW);
                unsigned due = 0, next = now;
                constexpr unsigned full = (unsigned)NCTA << 24;
                asm volatile("st.volatile.shared.u32 [%0], %1;" :: "r"(sb + SM_PROG), "r"(mine) : "memory");
#pragma unroll 1
                for (uint32_t n = 0; n < 4096; n++) {
                    unsigned v;
                    asm volatile("ld.volatile.shared.u32 %0, [%1];" : "=r"(v) : "r"(sb + SM_PROG) : "memory");
                    if (v > c) {
                        c = v;
                        const int arr = (int)__fdividef((float)(c & 0xffffffu), (float)(c >> 24));
                        due = arr - ((arr - issue) * ALPHA16 >> 4) + (is_gb ? W2_NS - GB_LEAD : GU_NS);
                    }
                    now = time_ns();
                    if (now - t_start + PROBE_NS >= due) np = PROBES;
                    if ((c >= full && np == PROBES) || now - t_start >= due) break;
                    if ((int)(now - next) >= 0 && c < full) {
                        asm volatile("cp.async.cg.shared.global [%0], [%1], 16;" :: "r"(sb + SM_PROG), "l"(prog) : "memory");
                        next = now + POLL_NS;
                    }
                    if (np < PROBES) probe();
                }
#pragma unroll 1
                for (uint32_t n = 0; n < 1024 && now - t_start < due; n++) now = time_ns();
                if (is_gu) {
#pragma unroll
                    for (int i = 0; i < 2 * NQ; i++) {
                        const int q = i >> 1, r0 = q * (512 / NQ);
                        tma4d(sb + slot_addr(N_FFN) + (r0 >> 8) * 2 * TILE_BYTES + (i & 1) * TILE_BYTES + (r0 & 255) * 64, (i & 1) ? &p.m_w3 : &p.m_w1, 32 * role, r0 / 16, sb + BAR_FFN + 8 * q);
                    }
#pragma unroll 1
                    for (uint32_t n = 0; n < 1024 && now - t_start < due + (W2_NS - GU_NS); n++) now = time_ns();
                    const int f = best[0] <= best[1] ? NW / 2 : 0;
#pragma unroll
                    for (int i = 0; i < NW; i++) tma5d(sb + slot_addr(N_FFN + 4) + (i ^ f) * (32768 / NW), &p.m_w2, 2 * role, (i ^ f) * (8 / NW), sb + BAR_W2 + 8 * (i ^ f));
                } else {
                    tma2d(sb + slot_addr(N_FFN), &p.m_gb, 5 * D_ + 16 * role, 0, sb + BAR_FFN);
                    tma2d(sb + slot_addr(N_FFN) + 8192, &p.m_gb, 5 * D_ + 16 * role, 256, sb + BAR_FFN + 8);
                }
                asm volatile("cp.async.wait_all;" ::: "memory");
            }
        }
        __syncwarp();
        if (is_gu) {
            const int lane = tid & 31;
            auto sum8 = [&](uint32_t a, int stride) {
                float4 u[8];
#pragma unroll
                for (int i = 0; i < 8; i++) u[i] = lds128f(a + i * stride);
                return make_float4(((u[0].x + u[1].x) + (u[2].x + u[3].x)) + ((u[4].x + u[5].x) + (u[6].x + u[7].x)),
                                   ((u[0].y + u[1].y) + (u[2].y + u[3].y)) + ((u[4].y + u[5].y) + (u[6].y + u[7].y)),
                                   ((u[0].z + u[1].z) + (u[2].z + u[3].z)) + ((u[4].z + u[5].z) + (u[6].z + u[7].z)),
                                   ((u[0].w + u[1].w) + (u[2].w + u[3].w)) + ((u[4].w + u[5].w) + (u[6].w + u[7].w)));
            };
            uint32_t h_st = sb + SM_Q + (((lane & 1) * 4 + ((lane >> 2) & 3)) * 4 + (lane & 2) + (lane >> 4)) * 4;
            bar_sync<3>();
            const float4 C = sum8(sb + SM_P + lane * 16, 1024), S = sum8(sb + SM_P + 512 + lane * 16, 1024);
            const uint32_t st_ld = sb + SM_RED + (lane & 1) * 64;
            settle(tag, sb + SM_OP, C); settle(tag, sb + SM_OP, S); settle(tag, sb + SM_OP, h_st, st_ld, 0, 0);
            bar_sync<4>();
            const float4 r0 = lds128f(st_ld), r1 = lds128f(st_ld + 16), r2 = lds128f(st_ld + 32), r3 = lds128f(st_ld + 48);
            const float4 Y = sum8(sb + SM_PART + lane * 16, 512);
            const float e1 = r0.z - r0.x, e2 = r1.x - r0.x, e3 = r1.z - r0.x, e4 = r2.x - r0.x, e5 = r2.z - r0.x, e6 = r3.x - r0.x, e7 = r3.z - r0.x;
            const float se = ((e1 + e2) + (e3 + e4)) + ((e5 + e6) + e7);
            const float ee = (fmaf(e1, e1, e2 * e2) + fmaf(e3, e3, e4 * e4)) + fmaf(e5, e5, fmaf(e6, e6, e7 * e7));
            const float sq = ((r0.y + r0.w) + (r1.y + r1.w)) + ((r2.y + r2.w) + (r3.y + r3.w));
            const float rsd = rcp_sd(fmaf(se * (-1.0f / D_), se, fmaf(ee, 1.0f / 64, sq))), mu = -rbf(fmaf(r0.x, 8.0f, se) * (1.0f / D_));
            const uint32_t gr = pack2(fmaf(rsd, fmaf(mu, C.x, Y.x), S.x), fmaf(rsd, fmaf(mu, C.z, Y.z), S.z));
            const uint32_t ur = pack2(fmaf(rsd, fmaf(mu, C.y, Y.y), S.y), fmaf(rsd, fmaf(mu, C.w, Y.w), S.w));
            const uint32_t hv = hmul2(pack2(silu_f(bf_lo(gr)), silu_f(bf_hi(gr))), ur);
            sts32f(h_st, __uint_as_float(hv));
            bar_arrive<5>();
            if (role == 0 && lane == 0) g_epoch = tag;
        }
        return;
    }
    if (tid >= 256) {
        set_kp(bh * (SK * DH * 2) + rank * TILE_BYTES);
        const unsigned t_start = t_top;
        auto pace = [&](int q4) {
            const int due = (q4 * PACE >> 2) - LEAD_NS;
            unsigned now, n = 0;
            do { now = time_ns(); } while ((int)(now - t_start) < due && ++n < 256);
        };
        if (tid == 256) {
#pragma unroll
            for (int j = FIRST_N; j < STAGES; j++) mbar_init(sb + full_bar(fill_tile(j)), 1);
#pragma unroll
            for (int s = 0; s < STAGES; s++) mbar_init(sb + BAR_EMPTY + 8 * s, 8);
            mbar_init(sb + BAR_XQ, 1); mbar_init(sb + BAR_XML, 1); mbar_init(sb + BAR_XP, 1); mbar_init(sb + BAR_XO, 1);
#pragma unroll
            for (int i = 0; i < NQ + NW; i++) mbar_init(sb + BAR_FFN + 8 * i, 1);
            mbar_expect_tx(sb + BAR_XQ, 256); mbar_expect_tx(sb + BAR_XML, 8); mbar_expect_tx(sb + BAR_XP, WIN); mbar_expect_tx(sb + BAR_XO, 1024);
            asm volatile("fence.mbarrier_init.release.cluster;" ::: "memory");
            asm volatile("fence.proxy.async.shared::cta;" ::: "memory");
        }
        __syncwarp();
        asm volatile("barrier.cluster.arrive.relaxed.aligned;" ::: "memory");
        if (elect_one()) {
#pragma unroll
            for (int j = FIRST_N; j < STAGES; j++) {
                pace(j <= K_FIRST ? 4 * j : j <= K_FIRST + 2 ? 4 * K_FIRST + 5 * (j - K_FIRST) / 2 :
                     j <= K_FIRST + 6 ? 4 * K_FIRST + 5 + 2 * (j - K_FIRST - 2) : 4 * j - 11);
                first_fill(j);
            }
        }
        __syncwarp();
        asm volatile("barrier.cluster.wait.acquire.aligned;" ::: "memory");
        if (elect_one()) {
            asm volatile("prefetch.tensormap [%0];" :: "l"(&p.m_v) : "memory");
            asm volatile("prefetch.tensormap [%0];" :: "l"(&p.m_wo) : "memory");
            int s = 0, ph = 0;
#pragma unroll 1
            for (int n = STAGES; n < N_FFN; n++) {
                const uint32_t dst = sb + SM_RING + s * TILE_BYTES, bar = sb + BAR_FULL + 8 * s;
                mbar_wait(sb + BAR_EMPTY + 8 * s, ph);
                mbar_expect_tx(bar, TILE_BYTES);
                pace(n < N_WO ? 4 * n - 11 : 2 * (N_WO + n) - 11);
                if (n < N_V) bulk_load(dst, kp + (n - N_K) * 2 * TILE_BYTES, TILE_BYTES, bar, pol);
                else if (n < N_WO) tma2d_hint(dst, &p.m_v, 64 * rank, bh * SK + (SK - WIN) + 128 * (n - N_V), bar, pol);
                else tma3d(dst, &p.m_wo, 0, h * DH + 32 * (n - N_WO), 4 * rank, bar);
                if (++s == STAGES) { s = 0; ph ^= 1; }
            }
        }
        return;
    }

    const unsigned t_c = t_top;
    const int lane = tid & 31, w = tid >> 5, g = lane >> 2, t = lane & 3;
    const int hgrp = 4 * w + (g & 3);
    const int vb = g >> 2;
    const uint32_t cv0 = ldg32(q_.c + vb * D_ + 16 * hgrp + 2 * t), cv1 = ldg32(q_.c + vb * D_ + 16 * hgrp + 8 + 2 * t);
    unsigned tag;
    asm volatile("ld.relaxed.gpu.global.u32 %0, [%1];" : "=r"(tag) : "l"(&g_epoch) : "memory");
    const uint4 xa = ldg128(q_.x + b * D_ + 16 * lane), xb = ldg128(q_.x + b * D_ + 16 * lane + 8);
    const uint32_t xh0 = ldg32(q_.x + b * D_ + 16 * hgrp + 2 * t), xh1 = ldg32(q_.x + b * D_ + 16 * hgrp + 8 + 2 * t);
    asm volatile("barrier.cluster.arrive.relaxed.aligned;" ::: "memory");
#pragma unroll 1
    for (uint32_t n = t_c; n < 2; n++) asm volatile("nanosleep.u32 1;" ::: "memory");
    const int grp = w >> 2, sub = w & 3;
    const int lrow = (lane & 7) + 8 * (lane >> 4);
    const int lch = (lane >> 3) & 1;
    const int ob = lane >> 4;
    const uint32_t t1 = t & 1, t2 = t & 2;
    const int gsrc = 16 * (g & 1) + t;
    const uint32_t sw128 = lrow * 128 + ((lch ^ (lrow & 7)) << 4);
    uint32_t A[16][4];

    const uint32_t sc0 = pack2(silu_f(bf_lo(cv0)), silu_f(bf_hi(cv0))), sc1 = pack2(silu_f(bf_lo(cv1)), silu_f(bf_hi(cv1)));
    tag += 1;
    asm volatile("barrier.cluster.wait.acquire.aligned;" ::: "memory");
    mbar_wait(sb + BAR_FULL + 8 * (N_WMOD + grp), 0);
    if (mc < N_MOD_CTA) {
        const uint32_t tb = sb + SM_RING + (N_WMOD + grp) * TILE_BYTES + (64 * sub + lrow) * 64;
#pragma unroll
        for (int i = 0; i < 8; i++)
            ldsm4t(tb + (i >> 1) * 1024 + (((2 * (i & 1) + lch) ^ ((lrow >> 1) & 3)) << 4), A[i]);
        float acc[2][4] = {{0.f, 0.f, 0.f, 0.f}, {0.f, 0.f, 0.f, 0.f}};
#pragma unroll
        for (int s = 0; s < 4; s++) {
            const uint32_t b0 = __shfl_sync(~0u, sc0, 4 * s + gsrc), b1 = __shfl_sync(~0u, sc1, 4 * s + gsrc);
            mma4(acc[0], A[2 * s], b0, b1);
            mma4(acc[1], A[2 * s + 1], b0, b1);
        }
        sts32f(sb + SM_P + (w * 64 + 8 * t + g) * 4, sel(t2, sel(t1, acc[1][2], acc[1][0]), sel(t1, acc[0][2], acc[0][0])));
        sts32f(sb + SM_P + (w * 64 + 32 + 8 * t + g) * 4, sel(t2, sel(t1, acc[1][3], acc[1][1]), sel(t1, acc[0][3], acc[0][1])));
        cbar();
        if (w == 0) {
            const bool adj = mc < 32;
            const uint32_t a0 = sb + SM_P + (adj ? 2 * lane : ob * 32 + (lane & 1) * 16 + ((lane >> 1) & 7)) * 4, a1 = a0 + (adj ? 4 : 32);
            float2 sum = make_float2(0.f, 0.f);
#pragma unroll
            for (int i = 0; i < 8; i++) { sum.x += lds32f(a0 + i * 256); sum.y += lds32f(a1 + i * 256); }
            st_pkt((u64)&g_mod[ob][16 * mc + (adj ? (lane & 8) + pair_pos(lane & 7) : lane & 15)], pack2(sum.x, sum.y), tag);
        }
    }
    __syncwarp();
    if (lane == 0) mbar_arrive_n(sb + BAR_EMPTY + 8 * (N_WMOD + grp), 2);

    {
        const uint2* mp = &g_mod[b][vb * 256 + 8 * hgrp + 2 * t];
        const uint32_t ms = sb + SM_PART + tid * 16;
        auto fetch_mod = [&](uint32_t k) {
            asm volatile("cp.async.cg.shared.global [%0], [%1], 16;\ncp.async.commit_group;" :: "r"(ms + k), "l"(mp) : "memory");
        };
        fetch_mod(0);
        float xs[16] = {bf_lo(xa.x), bf_hi(xa.x), bf_lo(xa.y), bf_hi(xa.y), bf_lo(xa.z), bf_hi(xa.z), bf_lo(xa.w), bf_hi(xa.w),
                        bf_lo(xb.x), bf_hi(xb.x), bf_lo(xb.y), bf_hi(xb.y), bf_lo(xb.z), bf_hi(xb.z), bf_lo(xb.w), bf_hi(xb.w)};
        float s = 0.f;
#pragma unroll
        for (int i = 0; i < 16; i++) s += xs[i];
#pragma unroll
        for (int m = 1; m < 32; m <<= 1) s += __shfl_xor_sync(~0u, s, m);
        const float mean = s * (1.0f / D_);
        float q = 0.f;
#pragma unroll
        for (int i = 0; i < 16; i++) q += (xs[i] - mean) * (xs[i] - mean);
#pragma unroll
        for (int m = 1; m < 32; m <<= 1) q += __shfl_xor_sync(~0u, q, m);
        const uint32_t mean2 = pack2(mean, mean);
        const float rsd = rcp_sd(q);

        mbar_wait(sb + BAR_FULL + 8 * (N_WQ + (w >> 1)), 0);
        const uint32_t tb = sb + SM_RING + (N_WQ + (w >> 1)) * TILE_BYTES + (w & 1) * 8192;
#pragma unroll
        for (int i = 0; i < 16; i++) ldsm4t(tb + (i >> 2) * 2048 + (sw128 ^ ((i & 3) * 32)), A[i]);
        __syncwarp();
        if (lane == 0) mbar_arrive_n(sb + BAR_EMPTY + 8 * (N_WQ + (w >> 1)), 4);

        Pkt2 m;
        for (uint32_t n = 0, k = 0; n < SPIN_LIMIT; n++) {
            fetch_mod(k ^ 4096);
            asm volatile("cp.async.wait_group 1;" ::: "memory");
            const uint4 u = lds128(ms + k);
            m.a = u.x | (u64)u.y << 32; m.b = u.z | (u64)u.w << 32;
            if (__all_sync(~0u, pkt_ok(m, tag))) break;
            k ^= 4096;
        }
        const uint32_t ca0 = __shfl_xor_sync(~0u, lo32(m.a), 16), ca1 = __shfl_xor_sync(~0u, lo32(m.b), 16);
        const uint32_t v0 = ln_mod2(xh0, mean2, rsd, hadd2(ONE2, ca0), lo32(m.a));
        const uint32_t v1 = ln_mod2(xh1, mean2, rsd, hadd2(ONE2, ca1), lo32(m.b));
        float acc[4][4];
#pragma unroll
        for (int i = 0; i < 4; i++) { acc[i][0] = acc[i][1] = acc[i][2] = acc[i][3] = 0.f; }
#pragma unroll
        for (int s4 = 0; s4 < 4; s4++) {
            const uint32_t b0 = __shfl_sync(~0u, v0, 4 * s4 + t), b1 = __shfl_sync(~0u, v1, 4 * s4 + t);
#pragma unroll
            for (int i = 0; i < 4; i++) mma4(acc[i], A[4 * s4 + i], b0, b1);
        }
        sts32f(sb + SM_OP + (w * 64 + 16 * t + g) * 4, sel(t2, sel(t1, acc[3][0], acc[2][0]), sel(t1, acc[1][0], acc[0][0])));
        sts32f(sb + SM_OP + (w * 64 + 16 * t + 8 + g) * 4, sel(t2, sel(t1, acc[3][2], acc[2][2]), sel(t1, acc[1][2], acc[0][2])));
        cbar();
        if (w == 0) {
            float2 sum = make_float2(0.f, 0.f);
#pragma unroll
            for (int i = 0; i < 8; i++) { const float2 u = lds64f(sb + SM_OP + (i * 64 + 2 * lane) * 4); sum.x += u.x; sum.y += u.y; }
            const uint32_t v = pack2(sum.x, sum.y), a = sb + SM_Q + rank * 128 + lane * 4;
            st_async_b32(mapa(a, rank ^ 1), v, mapa(sb + BAR_XQ, rank ^ 1));
            st_async_b32(mapa(a, rank), v, mapa(sb + BAR_XQ, rank));
        }
        mbar_wait_cluster(sb + BAR_XQ, 0);
    }

    Pkt2 mga, msb, mcb;
    uint32_t tx0, tx1;
    const uint2* tmp = &g_mod[ob][32 * w + 2 * (lane & 15)];
    {
        uint4 Q[4];
        uint32_t koff[4];
#pragma unroll
        for (int i = 0; i < 4; i++) {
            const int ch = t + 4 * (i ^ (g & 1));
            Q[i] = lds128(sb + SM_Q + ch * 16);
            koff[i] = (sub * 16 + g) * 256 + ch * 16;
        }
        float mx = -INFINITY;
        int stage = N_K + grp, phase = 0;
#pragma unroll 1
        for (int it = 0; it < NT / 2; it++) {
            const uint32_t tb = sb + SM_RING + stage * TILE_BYTES;
            mbar_wait(sb + BAR_FULL + 8 * stage, phase);
            uint4 Ka[4], Kb[4];
#pragma unroll
            for (int i = 0; i < 4; i++) { Ka[i] = lds128(tb + koff[i]); Kb[i] = lds128(tb + koff[i] + 2048); }
            float c0[4] = {0.f, 0.f, 0.f, 0.f}, c1[4] = {0.f, 0.f, 0.f, 0.f};
#pragma unroll
            for (int i = 0; i < 4; i++) {
                mma(c0, Ka[i].x, Kb[i].x, Ka[i].y, Kb[i].y, Q[i].x, Q[i].y);
                mma(c1, Ka[i].z, Kb[i].z, Ka[i].w, Kb[i].w, Q[i].z, Q[i].w);
            }
            __syncwarp();
            if (lane == 0) mbar_arrive_n(sb + BAR_EMPTY + 8 * stage, 2);
            const float lo = (g & 1) ? c0[1] + c1[1] : c0[0] + c1[0];
            const float hi = (g & 1) ? c0[3] + c1[3] : c0[2] + c1[2];
            const float sc = rbf(rbf(t1 ? hi : lo) * 0.08838834764831845f);
            mx = fmaxf(mx, sc);
            if (t < 2) sts16(sb + SM_P + ((2 * it + grp) * 128 + rank * 64 + sub * 16 + 4 * (g >> 1) + 2 * t + (g & 1)) * 2, __float_as_uint(sc) >> 16);
            stage += 2;
            if (stage >= STAGES) { stage -= STAGES; phase ^= 1; }
        }

        mga = ld_pkt2(tmp + 2 * 256); msb = ld_pkt2(tmp + 3 * 256); mcb = ld_pkt2(tmp + 4 * 256);
        const __nv_bfloat16* xp = q_.x + ob * D_ + 64 * w + 4 * (lane & 8) + (lane & 7);
        tx0 = ldg16(xp) | ldg16(xp + 8) << 16;
        tx1 = ldg16(xp + 16) | ldg16(xp + 24) << 16;

        asm volatile("cp.async.wait_all;" ::: "memory");

#pragma unroll
        for (int m = 1; m < 32; m <<= 1) mx = fmaxf(mx, __shfl_xor_sync(~0u, mx, m));
        if (lane == 0) sts32f(sb + SM_RED + w * 4, mx);
        cbar();
        {
            const float4 u = lds128f(sb + SM_RED), v = lds128f(sb + SM_RED + 16);
            mx = fmaxf(fmaxf(fmaxf(u.x, u.y), fmaxf(u.z, u.w)), fmaxf(fmaxf(v.x, v.y), fmaxf(v.z, v.w)));
        }
        const uint32_t pa = sb + SM_P + (tid >> 3) * 256 + rank * 128 + (tid & 7) * 16;
        const uint4 s0 = lds128(pa);
        const float sc[8] = {bf_lo(s0.x), bf_hi(s0.x), bf_lo(s0.y), bf_hi(s0.y), bf_lo(s0.z), bf_hi(s0.z), bf_lo(s0.w), bf_hi(s0.w)};
        float l = 0.f;
#pragma unroll
        for (int i = 0; i < 8; i++) l += __expf(sc[i] - mx);
#pragma unroll
        for (int m = 1; m < 32; m <<= 1) l += __shfl_xor_sync(~0u, l, m);
        if (lane == 0) sts32f(sb + SM_RED + 32 + w * 4, l);
        cbar();
        {
            const float4 u = lds128f(sb + SM_RED + 32), v = lds128f(sb + SM_RED + 48);
            l = ((u.x + u.y) + (u.z + u.w)) + ((v.x + v.y) + (v.z + v.w));
        }
        if (tid == 0) st_async_v2(mapa(sb + SM_ML, rank ^ 1), mx, l, mapa(sb + BAR_XML, rank ^ 1));
        mbar_wait_cluster(sb + BAR_XML, 0);
        const float2 o = lds64f(sb + SM_ML);
        const float m = fmaxf(mx, o.x);
        const float inv = __fdividef(1.0f, l * __expf(mx - m) + o.y * __expf(o.x - m));
        const uint32_t p0 = pack2(__expf(sc[0] - m) * inv, __expf(sc[1] - m) * inv), p1 = pack2(__expf(sc[2] - m) * inv, __expf(sc[3] - m) * inv);
        const uint32_t p2 = pack2(__expf(sc[4] - m) * inv, __expf(sc[5] - m) * inv), p3 = pack2(__expf(sc[6] - m) * inv, __expf(sc[7] - m) * inv);
        st_async_v4(mapa(pa, rank ^ 1), p0, p1, p2, p3, mapa(sb + BAR_XP, rank ^ 1));
        sts128(pa, p0, p1, p2, p3);
        cbar();
        mbar_wait_cluster(sb + BAR_XP, 0);
    }

#pragma unroll 1
    for (uint32_t n = 0; n < SPIN_LIMIT && !__all_sync(~0u, pkt_ok(mga, tag) && pkt_ok(msb, tag) && pkt_ok(mcb, tag)); n++) {
        mga = ld_pkt2(tmp + 2 * 256); msb = ld_pkt2(tmp + 3 * 256); mcb = ld_pkt2(tmp + 4 * 256);
    }
    const uint32_t ga0 = lo32(mga.a), ga1 = lo32(mga.b), sb0 = lo32(msb.a), sb1 = lo32(msb.b);
    const uint32_t cb0 = hadd2(ONE2, lo32(mcb.a)), cb1 = hadd2(ONE2, lo32(mcb.b));
    const int wb = 4 * rank + sub;
    u64 red_p = s_line(e1_blk(1, wb), 2 * b) + lane * 4, red2_p = s_line(e1_blk(1, wb), 4 + b) + lane * 4;

    PIN64(red_p); PIN64(red2_p);
    float oa[4][4];
#pragma unroll
    for (int i = 0; i < 4; i++) { oa[i][0] = oa[i][1] = oa[i][2] = oa[i][3] = 0.f; }
    {
        int stage = N_V % STAGES, phase = tile_phase(N_V);
        auto v_tiles = [&](int v0, int v1) {
#pragma unroll 1
            for (int v = v0; v < v1; v++) {
                const uint32_t tb = sb + SM_RING + stage * TILE_BYTES + grp * 8192 + (sw128 ^ (sub * 32));
                uint2 P[4];
#pragma unroll
                for (int i = 0; i < 4; i++) P[i] = lds64(sb + SM_P + v * 256 + grp * 128 + i * 32 + t * 8);
                mbar_wait(sb + BAR_FULL + 8 * stage, phase);
                uint32_t a[4][4];
#pragma unroll
                for (int i = 0; i < 4; i++) ldsm4t(tb + i * 2048, a[i]);
#pragma unroll
                for (int i = 0; i < 4; i++) mma4(oa[i], a[i], P[i].x, P[i].y);
                __syncwarp();
                if (lane == 0) mbar_arrive(sb + BAR_EMPTY + 8 * stage);
                if (++stage == STAGES) { stage = 0; phase ^= 1; }
            }
        };
        v_tiles(0, MEET_AT);
        asm volatile("bar.sync 2, 288;" ::: "memory");
        v_tiles(MEET_AT, NT);
    }

    if (t < 2) {
        const uint32_t a = sb + SM_OP + rank * 512 + w * 64 + (g >> 1) * 16 + (g & 1) * 4 + t * 8;
        const uint32_t v = __float_as_uint(sel(t1, (oa[0][2] + oa[1][2]) + (oa[2][2] + oa[3][2]), (oa[0][0] + oa[1][0]) + (oa[2][0] + oa[3][0])));
        st_async_b32(mapa(a, rank ^ 1), v, mapa(sb + BAR_XO, rank ^ 1));
        st_async_b32(mapa(a, rank), v, mapa(sb + BAR_XO, rank));
    }
    __syncwarp();
    mbar_wait_cluster(sb + BAR_XO, 0);

    {
        float acc[4][4];
        const uint32_t o_ld = sb + SM_OP + grp * 512 + (lane & 15) * 16 + vb * 8, x_st = sb + SM_PART + 4096 + sub * 1024 + lane * 16;
        const float2 u = lds64f(o_ld), v = lds64f(o_ld + 256);
        const uint32_t o2 = pack2(u.x + v.x, u.y + v.y);
        uint32_t bo[8];
#pragma unroll
        for (int i = 0; i < 8; i++) bo[i] = __shfl_sync(~0u, o2, 16 * (i & 1) + 4 * (i >> 1) + t);
        float4 x0 = make_float4(0.f, 0.f, 0.f, 0.f), x1 = x0;
#pragma unroll
        for (int i = 0; i < 4; i++) { acc[i][0] = acc[i][1] = acc[i][2] = acc[i][3] = 0.f; }
        static_assert(N_WO % STAGES + 4 <= STAGES, "wo tiles occupy consecutive slots");
        const uint32_t wa = sb + slot_addr(N_WO) + grp * 2 * TILE_BYTES + sub * 4096, wbar = sb + full_bar(N_WO) + grp * 16;
#pragma unroll
        for (int j = 0; j < 2; j++) {
            if (j == 1 && grp) { asm volatile("bar.sync 8, 256;" ::: "memory"); x0 = lds128f(x_st); x1 = lds128f(x_st + 512); }
            mbar_wait(wbar + 8 * j, tile_phase(N_WO));
            if (j == 1) { }
#pragma unroll
            for (int i = 0; i < 8; i++) ldsm4t(wa + j * TILE_BYTES + (i >> 2) * 2048 + (sw128 ^ ((i & 3) * 32)), A[8 * j + i]);
#pragma unroll
            for (int i = 0; i < 8; i++) mma4(acc[i & 3], A[8 * j + i], bo[4 * j + 2 * (i >> 2)], bo[4 * j + 2 * (i >> 2) + 1]);
        }
        if (!grp) {
            sts128f(x_st, acc[0][0], acc[1][0], acc[2][0], acc[3][0]); sts128f(x_st + 512, acc[0][2], acc[1][2], acc[2][2], acc[3][2]);
            asm volatile("bar.arrive 8, 256;" ::: "memory");
        } else {
            acc[0][0] += x0.x; acc[1][0] += x0.y; acc[2][0] += x0.z; acc[3][0] += x0.w; acc[0][2] += x1.x; acc[1][2] += x1.y; acc[2][2] += x1.z; acc[3][2] += x1.w;
            const float r0 = sel(t2, sel(t1, 1.0f, acc[1][0]), sel(t1, acc[0][2], acc[0][0]));
            const float r1 = sel(t2, sel(t1, 1.0f, acc[3][0]), sel(t1, acc[2][2], acc[2][0]));
            const float r2 = sel(t2, 1.0f, sel(t1, acc[3][2], acc[1][2]));
            asm volatile("red.relaxed.gpu.global.add.f32 [%0], %2;\nred.relaxed.gpu.global.add.f32 [%0 + 256], %3;\nred.relaxed.gpu.global.add.f32 [%1], %4;"
                         :: "l"(red_p), "l"(red2_p), "f"(r0), "f"(r1), "f"(r2) : "memory");
            asm volatile("red.relaxed.gpu.global.add.f32 [%0], %2;\nred.relaxed.gpu.global.add.f32 [%0 + 256], %3;\nred.relaxed.gpu.global.add.f32 [%1], %4;"
                         :: "l"(red_p ^ 4096), "l"(red2_p ^ 4096), "f"(r0), "f"(r1), "f"(r2) : "memory");
        }
    }

    constexpr uint32_t CNT = 0x42000000u;
    if (is_gu) {
        uint32_t side;
        asm volatile("ld.volatile.shared.u32 %0, [%1];" : "=r"(side) : "r"(sb + SM_SIDE) : "memory");
        u64 acc_p = (s_line(e1_blk(0, w), lane >> 3) + (lane & 7) * 16) ^ side, acc2_p = (s_line(e1_blk(0, w), 4 + ob) + (lane & 7) * 16) ^ side;
        const int eb = e1_blk(w >> 2, w & 3);
        const bool near = __all_sync(~0u, (w >> 2) * 4096 == side);
        u64 out_p = s_line(eb, lane >> 3) + S_OUT + (lane & 7) * 16, out2_p = s_line(eb, 4 + ob) + S_OUT + (lane & 15) * 8;
        u64 gb_p = (s_line(e1_blk(0, w), 6 + ob) + (lane & 15) * 8) ^ side, y_p = (u64)(q_.out + t1 * D_ + 64 * w + 4 * t2 + g);
        PIN64(acc_p); PIN64(acc2_p); PIN64(out_p); PIN64(out2_p); PIN64(gb_p); PIN64(y_p);
        auto keep = [&](uint32_t x) { return __shfl_sync(~0u, x, lane); };
        const int src = keep(8 * (g & 2) + t), src1 = keep(src + 4), src2 = keep(src + 8), src3 = keep(src + 12);
        const uint32_t p_st = keep(sb + SM_PART + w * 512 + lane * 16), r_st = keep(sb + SM_RED + (vb * 8 + w) * 8);
        tx0 = keep(tx0); tx1 = keep(tx1);
        uint32_t w2a[4];
#pragma unroll
        for (int i = 0; i < 4; i++) w2a[i] = keep(sb + slot_addr(N_FFN + 4) + w * 4096 + (sw128 ^ (i * 32)));
        const uint32_t hva = keep(sb + SM_Q + ((g & 2) * 2 + t) * 16), w2b = keep(sb + BAR_W2 + 8 * (w * NW >> 3)), t2k = keep(t2);
        const uint32_t g1 = g & 1;
        uint32_t cp[8], cn[8];
        float acc[4][4];
#pragma unroll
        for (int i = 0; i < 8; i++) {
            cp[i] = __shfl_sync(~0u, (i & 1) ? cb1 : cb0, 4 * (i >> 1) + src);
            cn[i] = selu(g1, __shfl_sync(~0u, (i & 1) ? sb1 : sb0, 4 * (i >> 1) + src), cp[i]);
        }
        const int frow = (lane & 7) + (lane & 16);
        const uint32_t fa = sb + slot_addr(N_FFN) + grp * 2 * TILE_BYTES + (64 * sub + frow) * 64 + ((lch ^ ((frow >> 1) & 3)) << 4);
        mbar_wait(sb + BAR_FFN + 8 * (w * NQ >> 3), 0);
        uint4 u = ld_strong128(acc_p), v = ld_strong128(acc2_p);
#pragma unroll
        for (int i = 0; i < 16; i++) ldsm4t((fa ^ ((i & 1) * 32)) + (i >> 3) * 2048 + ((i >> 2) & 1) * 512 + ((i >> 1) & 1) * TILE_BYTES, A[i]);
#pragma unroll
        for (int i = 0; i < 4; i++) { acc[i][0] = acc[i][1] = acc[i][2] = acc[i][3] = 0.f; }
#pragma unroll
        for (int i = 0; i < 16; i++)
            mma4(acc[i & 3], A[i], cn[2 * (i >> 2)], cn[2 * (i >> 2) + 1]);
        sts128f(sb + SM_P + w * 1024 + lane * 16, sel(t2, acc[1][0], acc[0][0]), sel(t2, acc[3][0], acc[2][0]), sel(t2, acc[1][2], acc[0][2]), sel(t2, acc[3][2], acc[2][2]));
        sts128f(sb + SM_P + w * 1024 + 512 + lane * 16, sel(t2, acc[1][1], acc[0][1]), sel(t2, acc[3][1], acc[2][1]), sel(t2, acc[1][3], acc[0][3]), sel(t2, acc[3][3], acc[2][3]));
        bar_arrive<3>();
#pragma unroll
        for (int i = 0; i < 8; i++) cn[i] = selu(g1, cp[i] ^ 0x80008000u, 0u);
        settle(tag, sb + SM_OP, cn[0], cn[1], cn[2], cn[3]); settle(tag, sb + SM_OP, cn[4], cn[5], cn[6], cn[7]);
        for (uint32_t n = 0; !__all_sync(~0u, u.w == CNT && v.w == CNT) && n < SPIN_LIMIT; n++) { u = ld_strong128(acc_p); v = ld_strong128(acc2_p); }
        const uint32_t x0 = hadd2(tx0, hmul2(ga0, pack2(__uint_as_float(u.x), __uint_as_float(u.y))));
        const uint32_t x1 = hadd2(tx1, hmul2(ga1, pack2(__uint_as_float(u.z), __uint_as_float(selu(lane & 8, v.y, v.x)))));
        float c[4] = {0.f, 0.f, 0.f, 0.f};
        mma(c, x0, ONE2, x1, ONE2, x0, x1);
#pragma unroll
        for (int i = 0; i < 4; i++) { acc[i][0] = acc[i][1] = acc[i][2] = acc[i][3] = 0.f; }
        float q, s;
#pragma unroll
        for (int s4 = 0; s4 < 4; s4++) {
            const int from = s4 == 0 ? src : s4 == 1 ? src1 : s4 == 2 ? src2 : src3;
            uint32_t b0 = __shfl_sync(~0u, x0, from), b1 = __shfl_sync(~0u, x1, from);
            b0 = hfma2(b0, cp[2 * s4], hmul2(b0, cn[2 * s4]));
            b1 = hfma2(b1, cp[2 * s4 + 1], hmul2(b1, cn[2 * s4 + 1]));
#pragma unroll
            for (int i = 0; i < 4; i++) mma4(acc[i], A[4 * s4 + i], b0, b1);
            if (s4 == 0) { q = sel(g1, c[1], c[0]); s = c[2] + c[3]; q += __shfl_xor_sync(~0u, q, 4); s += __shfl_xor_sync(~0u, s, 9); }
            if (s4 == 1) q += __shfl_xor_sync(~0u, q, 9);
            if (s4 == 2) { if (lane == 0 || lane == 18) sts64f(r_st, s, fmaxf(fmaf(s * (-1.0f / 64), s, q), 0.f)); }
        }
        sts128f(p_st, sel(t2, acc[1][0] + acc[1][1], acc[0][0] + acc[0][1]), sel(t2, acc[3][0] + acc[3][1], acc[2][0] + acc[2][1]),
                sel(t2, acc[1][2] + acc[1][3], acc[0][2] + acc[0][3]), sel(t2, acc[3][2] + acc[3][3], acc[2][2] + acc[2][3]));
        bar_arrive<4>();
        uint32_t xo[2];
#pragma unroll
        for (int j = 0; j < 2; j++) {
            const uint32_t e0 = __shfl_sync(~0u, x0, 16 * t1 + 8 * j + g), e1 = __shfl_sync(~0u, x1, 16 * t1 + 8 * j + g);
            xo[j] = __byte_perm(e0, e1, t2 ? 0x7632 : 0x5410);
        }
        auto w2_frags = [&]() {
            mbar_wait(w2b, 0);
#pragma unroll
            for (int i = 0; i < 8; i++) ldsm4t(w2a[i & 3] + (i >> 2) * 2048, A[i]);
        };
        if (!near) w2_frags();
#pragma unroll
        for (int i = 0; i < 4; i++) { acc[i][0] = acc[i][1] = acc[i][2] = acc[i][3] = 0.f; }
        bar_sync<5>();
        const uint4 hv = lds128(hva);
        if (near) w2_frags();
#pragma unroll
        for (int i = 0; i < 4; i++) mma4(acc[i], A[i], hv.x, hv.y);
#pragma unroll
        for (int i = 0; i < 4; i++) mma4(acc[i], A[4 + i], hv.z, hv.w);
        float r[4], o[6];
#pragma unroll
        for (int i = 0; i < 4; i++) r[i] = sel(t2k, acc[i][2], acc[i][0]);
        asm volatile("atom.relaxed.gpu.global.add.v4.f32 {%0, %1, %2, %3}, [%4], {%5, %6, %7, %8};"
                     : "=f"(o[0]), "=f"(o[1]), "=f"(o[2]), "=f"(o[4]) : "l"(out_p), "f"(r[0]), "f"(r[1]), "f"(r[2]), "f"(1.0f) : "memory");
        asm volatile("atom.relaxed.gpu.global.add.v2.f32 {%0, %1}, [%2], {%3, %4};"
                     : "=f"(o[3]), "=f"(o[5]) : "l"(out2_p), "f"(r[3]), "f"(1.0f) : "memory");
        uint2 gb = ld_strong64(gb_p);
        const uint32_t f0 = pack2(o[0] + r[0], o[1] + r[1]), f1 = pack2(o[2] + r[2], o[3] + r[3]);
#pragma unroll 1
        for (uint32_t n = 0; n < SPIN_LIMIT; n++) {
            const uint32_t y0 = hadd2(xo[0], hmul2(gb.x, f0)), y1 = hadd2(xo[1], hmul2(gb.y, f1));
            uint32_t late;
            asm volatile("{\n.reg .pred p, q, m;\n.reg .b16 a, b, c, d;\n"
                         "mov.b32 {a, b}, %6;\nmov.b32 {c, d}, %7;\nsetp.ne.b16 m, a, 0xffff;\nsetp.ne.and.b16 m, b, 0xffff, m;\nsetp.ne.and.b16 m, c, 0xffff, m;\nsetp.ne.and.b16 m, d, 0xffff, m;\n"
                         "setp.eq.and.f32 p, %4, 0f42280000, m;\nsetp.eq.and.f32 q, %5, 0f42280000, m;\n"
                         "mov.b32 {a, b}, %2;\nmov.b32 {c, d}, %3;\n"
                         "@p st.global.u16 [%1], a;\n@p st.global.u16 [%1 + 32], b;\n@p st.global.u16 [%1 + 64], c;\n@q st.global.u16 [%1 + 96], d;\n"
                         "vote.sync.all.pred m, m, 0xffffffff;\nselp.u32 %0, 0, 1, m;\n}"
                         : "=r"(late) : "l"(y_p), "r"(y0), "r"(y1), "f"(o[4]), "f"(o[5]), "r"(gb.x), "r"(gb.y) : "memory");
            if (!late) break;
            gb = ld_strong64(gb_p);
        }
    } else if (is_gb) {
        const uint32_t fa = sb + slot_addr(N_FFN) + grp * 8192 + (64 * sub + lrow) * 32 + ((lch ^ ((lrow >> 2) & 1)) << 4);
        const int dl = (lane & 7) * 4 + ((lane >> 3) & 1) * 2 + ob;
        u64 gb_p = s_line(2 * (role >> 2), 6 + (dl >> 4)) + (dl & 15) * 8 + (role & 3) * 2;
        PIN64(gb_p);
        uint32_t bs[8];
#pragma unroll
        for (int i = 0; i < 8; i++) bs[i] = __shfl_sync(~0u, (i & 1) ? sc1 : sc0, 4 * (i >> 1) + 16 * ((g >> 1) & 1) + t);
        const uint32_t c_st = sb + SM_PART + (w * 32 + t1 * 16 + (t >> 1) * 8 + g) * 4;
        settle(tag, sb + SM_OP, bs[0], bs[1], bs[2], bs[3]); settle(tag, sb + SM_OP, bs[4], bs[5], bs[6], bs[7]); settle(tag, sb + SM_OP, c_st, fa, 0, 0);
        mbar_wait(sb + BAR_FFN + 8 * grp, 0);
        float c[4][4];
#pragma unroll
        for (int s4 = 0; s4 < 4; s4++) ldsm4t(fa + s4 * 512, A[s4]);
#pragma unroll
        for (int s4 = 0; s4 < 4; s4++) { c[s4][0] = c[s4][1] = c[s4][2] = c[s4][3] = 0.f; mma4(c[s4], A[s4], bs[2 * s4], bs[2 * s4 + 1]); }
        sts32f(c_st, sel(t2, (c[0][2] + c[1][2]) + (c[2][2] + c[3][2]), (c[0][0] + c[1][0]) + (c[2][0] + c[3][0])));
        cbar();
        if (w == 0) {
            float u[8];
#pragma unroll
            for (int i = 0; i < 8; i++) u[i] = lds32f(sb + SM_PART + i * 128 + lane * 4);
            const uint16_t v = (uint16_t)pack2(((u[0] + u[1]) + (u[2] + u[3])) + ((u[4] + u[5]) + (u[6] + u[7])), 0.f);
            asm volatile("st.relaxed.gpu.global.u16 [%0], %1;\nst.relaxed.gpu.global.u16 [%0 + 4096], %1;" :: "l"(gb_p), "h"(v) : "memory");
        }
    }
}

typedef CUresult (*EncodeFn)(CUtensorMap*, CUtensorMapDataType, cuuint32_t, void*, const cuuint64_t*, const cuuint64_t*,
                             const cuuint32_t*, const cuuint32_t*, CUtensorMapInterleave, CUtensorMapSwizzle,
                             CUtensorMapL2promotion, CUtensorMapFloatOOBfill);

void make_map(EncodeFn enc, CUtensorMap* m, void* ptr, int cols, int rows, int box_cols, int box_rows, CUtensorMapSwizzle sw) {
    cuuint64_t gd[2] = {(cuuint64_t)cols, (cuuint64_t)rows}, gs[1] = {(cuuint64_t)cols * 2};
    cuuint32_t bd[2] = {(cuuint32_t)box_cols, (cuuint32_t)box_rows}, es[2] = {1, 1};
    enc(m, CU_TENSOR_MAP_DATA_TYPE_BFLOAT16, 2, ptr, gd, gs, bd, es, CU_TENSOR_MAP_INTERLEAVE_NONE, sw,
        CU_TENSOR_MAP_L2_PROMOTION_NONE, CU_TENSOR_MAP_FLOAT_OOB_FILL_NONE);
}

}

extern "C" void kernel_launch(void* const* d_in, const int* in_sizes, int n_in, void* d_out, int out_size) {
    (void)in_sizes; (void)n_in; (void)out_size;
    static EncodeFn enc = nullptr;
    if (!enc) {
        void* fn = nullptr;
        cudaDriverEntryPointQueryResult qr;
        cudaGetDriverEntryPoint("cuTensorMapEncodeTiled", &fn, cudaEnableDefault, &qr);
        enc = (EncodeFn)fn;
        cudaFuncSetAttribute(fused_decode_kernel, cudaFuncAttributeMaxDynamicSharedMemorySize, SMEM_BYTES);
    }
    Params p;
    Ptrs q;
    make_map(enc, &p.m_wmod, d_in[10], MODW, D_, 32, 256, CU_TENSOR_MAP_SWIZZLE_64B);
    make_map(enc, &p.m_wq, d_in[3], QD, D_, 64, 128, CU_TENSOR_MAP_SWIZZLE_128B);
    make_map(enc, &p.m_v, d_in[2], DH, 64 * SK, 64, 128, CU_TENSOR_MAP_SWIZZLE_128B);
    {
        cuuint64_t gd[3] = {64, QD, 8}, gs[2] = {D_ * 2, 128};
        cuuint32_t bd[3] = {64, 32, 4}, es[3] = {1, 1, 1};
        enc(&p.m_wo, CU_TENSOR_MAP_DATA_TYPE_BFLOAT16, 3, d_in[4], gd, gs, bd, es, CU_TENSOR_MAP_INTERLEAVE_NONE,
            CU_TENSOR_MAP_SWIZZLE_128B, CU_TENSOR_MAP_L2_PROMOTION_NONE, CU_TENSOR_MAP_FLOAT_OOB_FILL_NONE);
    }
    for (int i = 0; i < 2; i++) {
        cuuint64_t gd[4] = {FF, 2, 8, D_ / 16}, gs[3] = {8 * FF * 2, FF * 2, 16 * FF * 2};
        cuuint32_t bd[4] = {32, 2, 8, 32 / NQ}, es[4] = {1, 1, 1, 1};
        enc(i ? &p.m_w3 : &p.m_w1, CU_TENSOR_MAP_DATA_TYPE_BFLOAT16, 4, d_in[6 + i], gd, gs, bd, es, CU_TENSOR_MAP_INTERLEAVE_NONE,
            CU_TENSOR_MAP_SWIZZLE_64B, CU_TENSOR_MAP_L2_PROMOTION_NONE, CU_TENSOR_MAP_FLOAT_OOB_FILL_NONE);
    }
    {
        cuuint64_t gd[5] = {64, 2, 8, FF / 16, 8}, gs[4] = {8 * D_ * 2, D_ * 2, 16 * D_ * 2, 128};
        cuuint32_t bd[5] = {64, 2, 8, 2, 8 / NW}, es[5] = {1, 1, 1, 1, 1};
        enc(&p.m_w2, CU_TENSOR_MAP_DATA_TYPE_BFLOAT16, 5, d_in[8], gd, gs, bd, es, CU_TENSOR_MAP_INTERLEAVE_NONE,
            CU_TENSOR_MAP_SWIZZLE_128B, CU_TENSOR_MAP_L2_PROMOTION_NONE, CU_TENSOR_MAP_FLOAT_OOB_FILL_NONE);
    }
    make_map(enc, &p.m_gb, d_in[10], MODW, D_, 16, 256, CU_TENSOR_MAP_SWIZZLE_32B);
    q.x = (const __nv_bfloat16*)d_in[0];
    q.kwin = (const __nv_bfloat16*)d_in[1] + (size_t)(SK - WIN) * DH;
    q.c = (const __nv_bfloat16*)d_in[9];
    q.out = (__nv_bfloat16*)d_out;
    fused_decode_kernel<<<NCTA, THREADS, SMEM_BYTES, cudaStreamPerThread>>>(q, p);
}
```

```cpp
#include <cuda_runtime.h>
#include <cuda.h>
#include <cuda_bf16.h>
#include <stdint.h>

namespace {

constexpr int D_ = 512, DH = 128, SK = 16384, WIN = 4096, FF = 1376, QD = 4096, MODW = 3072;
constexpr int NCTA = 128;
constexpr int TILE_BYTES = 16384;
constexpr int NT = 32;
constexpr int STAGES = 13;
constexpr int K_FIRST = 2;
constexpr int FIRST_N = 5;
constexpr int MEET_AT = 16;
constexpr int PACE = 656;
constexpr int LEAD_NS = 1290;
constexpr int GATE_X = 25;
constexpr int POLL_NS = 300;
constexpr int ALPHA16 = 4;
constexpr int GU_NS = 4630;
constexpr int W2_NS = 5860;
constexpr int GB_LEAD = 370;
constexpr int NQ = 8;
constexpr int PROBES = 6;
constexpr int PROBE_NS = 1000;
constexpr int EARLY_NS = 800;
constexpr int NW = 4;
constexpr int HEAD_TID = 256;
constexpr int N_WMOD = 0, N_WQ = 2, N_K = 6, N_V = N_K + NT, N_WO = N_V + NT, N_FFN = N_WO + 4;
constexpr int N_GATE = N_V + GATE_X;
constexpr int THREADS = 320;
constexpr int N_MOD_CTA = 80;
#define SPIN_LIMIT_S "4194304"
constexpr unsigned SPIN_LIMIT = 1u << 22;

constexpr int SM_RING = 0;
constexpr int SM_P = STAGES * TILE_BYTES;
constexpr int SM_PART = SM_P + WIN * 2;
constexpr int SM_OP = SM_PART + 8192;
constexpr int SM_Q = SM_OP + 2048;
constexpr int SM_RED = SM_Q + 256;
constexpr int SM_ML = SM_RED + 128;
constexpr int SM_PROG = SM_ML + 16;
constexpr int SM_SIDE = SM_PROG + 16;
constexpr int SM_BAR = SM_SIDE + 16;
constexpr int BAR_FULL = SM_BAR, BAR_EMPTY = SM_BAR + 8 * STAGES, BAR_XQ = SM_BAR + 16 * STAGES,
              BAR_XML = BAR_XQ + 8, BAR_XP = BAR_XQ + 16, BAR_XO = BAR_XQ + 24, BAR_FFN = BAR_XQ + 32;
constexpr int BAR_W2 = BAR_FFN + 8 * NQ;
constexpr int SMEM_BYTES = BAR_W2 + 8 * NW;
static_assert(SMEM_BYTES <= 232448, "shared memory");
__host__ __device__ constexpr uint32_t slot_addr(int n) { return SM_RING + (n % STAGES) * TILE_BYTES; }
__host__ __device__ constexpr uint32_t full_bar(int n) { return BAR_FULL + 8 * (n % STAGES); }
__host__ __device__ constexpr uint32_t empty_bar(int n) { return BAR_EMPTY + 8 * (n % STAGES); }
__host__ __device__ constexpr uint32_t tile_phase(int n) { return (n / STAGES) & 1; }
static_assert((N_FFN + 4) % STAGES + 2 <= STAGES && N_FFN % STAGES + 4 <= STAGES, "w1/w3 tiles and w2 tiles occupy consecutive slots");
static_assert(GATE_X >= MEET_AT && N_GATE - STAGES < N_V + MEET_AT && N_FFN + 5 - 2 * STAGES < N_V + MEET_AT && N_FFN + 5 - STAGES < N_WO,
              "barrier parities the helper warp waits on are unambiguous after the rendezvous; the wo tiles are not replaced");
__host__ __device__ constexpr int fill_tile(int j) { return j < K_FIRST ? N_K + j : j < K_FIRST + N_K ? j - K_FIRST : j; }

struct Ptrs {
    const __nv_bfloat16 *kwin, *x, *c;
    __nv_bfloat16* out;
};
struct Params {
    CUtensorMap m_wmod, m_wq, m_v, m_wo, m_w1, m_w3, m_w2, m_gb;
};

__device__ unsigned g_epoch;
__device__ __align__(128) uint2 g_mod[2][5 * D_ / 2];
__device__ __align__(256) unsigned char g_s[131072];
__device__ __forceinline__ unsigned long long s_line(int blk, int i) {
    return (((unsigned long long)g_s + 65535) & ~65535ull) + blk * 4096 + (i >> 1) * 1024 + (i & 1) * 256;
}
__device__ __forceinline__ int e1_blk(int r, int w) { return 2 * w + (r ^ (w & 1)); }
constexpr int S_OUT = 512, S_PROG = 128;
__device__ __align__(128) unsigned g_clear;

typedef unsigned long long u64;
__device__ __forceinline__ unsigned time_ns() {
    unsigned r;
    asm volatile("mov.u32 %0, %%globaltimer_lo;" : "=r"(r));
    return r;
}
__device__ __forceinline__ bool elect_one() {
    uint32_t r;
    asm volatile("{\n.reg .pred p;\nelect.sync _|p, 0xffffffff;\nselp.u32 %0, 1, 0, p;\n}" : "=r"(r));
    return r != 0;
}
#define PIN64(v) asm volatile("" : "+l"(v))

__device__ __forceinline__ void mbar_init(uint32_t bar, uint32_t cnt) {
    asm volatile("mbarrier.init.shared::cta.b64 [%0], %1;" :: "r"(bar), "r"(cnt) : "memory");
}
__device__ __forceinline__ void mbar_expect_tx(uint32_t bar, uint32_t bytes) {
    asm volatile("mbarrier.arrive.expect_tx.shared::cta.b64 _, [%0], %1;" :: "r"(bar), "r"(bytes) : "memory");
}
__device__ __forceinline__ void mbar_arrive(uint32_t bar) {
    asm volatile("mbarrier.arrive.shared::cta.b64 _, [%0];" :: "r"(bar) : "memory");
}
__device__ __forceinline__ void mbar_arrive_n(uint32_t bar, uint32_t n) {
    asm volatile("mbarrier.arrive.shared::cta.b64 _, [%0], %1;" :: "r"(bar), "r"(n) : "memory");
}
__device__ __forceinline__ void mbar_wait(uint32_t bar, uint32_t parity) {
    asm volatile("{\n.reg .pred p;\n.reg .u32 n;\nmov.u32 n, 0;\nW0:\n"
                 "mbarrier.try_wait.parity.shared::cta.b64 p, [%0], %1;\n@p bra W1;\n"
                 "add.u32 n, n, 1;\nsetp.lt.u32 p, n, " SPIN_LIMIT_S ";\n@p bra W0;\nW1:\n}"
                 :: "r"(bar), "r"(parity) : "memory");
}
__device__ __forceinline__ void mbar_wait_cluster(uint32_t bar, uint32_t parity) {
    asm volatile("{\n.reg .pred p;\n.reg .u32 n;\nmov.u32 n, 0;\nW0:\n"
                 "mbarrier.try_wait.parity.acquire.cluster.shared::cta.b64 p, [%0], %1;\n@p bra W1;\n"
                 "add.u32 n, n, 1;\nsetp.lt.u32 p, n, " SPIN_LIMIT_S ";\n@p bra W0;\nW1:\n}"
                 :: "r"(bar), "r"(parity) : "memory");
}
__device__ __forceinline__ void bulk_load(uint32_t dst, const void* src, uint32_t bytes, uint32_t bar, uint64_t pol) {
    asm volatile("cp.async.bulk.shared::cluster.global.mbarrier::complete_tx::bytes.L2::cache_hint [%0], [%1], %2, [%3], %4;"
                 :: "r"(dst), "l"(src), "r"(bytes), "r"(bar), "l"(pol) : "memory");
}
__device__ __forceinline__ void tma2d(uint32_t dst, const CUtensorMap* m, int c0, int c1, uint32_t bar) {
    asm volatile("cp.async.bulk.tensor.2d.shared::cluster.global.mbarrier::complete_tx::bytes [%0], [%1, {%3, %4}], [%2];"
                 :: "r"(dst), "l"(m), "r"(bar), "r"(c0), "r"(c1) : "memory");
}
__device__ __forceinline__ void tma2d_hint(uint32_t dst, const CUtensorMap* m, int c0, int c1, uint32_t bar, uint64_t pol) {
    asm volatile("cp.async.bulk.tensor.2d.shared::cluster.global.mbarrier::complete_tx::bytes.L2::cache_hint [%0], [%1, {%3, %4}], [%2], %5;"
                 :: "r"(dst), "l"(m), "r"(bar), "r"(c0), "r"(c1), "l"(pol) : "memory");
}
__device__ __forceinline__ void tma3d(uint32_t dst, const CUtensorMap* m, int c0, int c1, int c2, uint32_t bar) {
    asm volatile("cp.async.bulk.tensor.3d.shared::cluster.global.mbarrier::complete_tx::bytes [%0], [%1, {%3, %4, %5}], [%2];"
                 :: "r"(dst), "l"(m), "r"(bar), "r"(c0), "r"(c1), "r"(c2) : "memory");
}
__device__ __forceinline__ void tma4d(uint32_t dst, const CUtensorMap* m, int c0, int c3, uint32_t bar) {
    asm volatile("cp.async.bulk.tensor.4d.shared::cluster.global.mbarrier::complete_tx::bytes [%0], [%1, {%3, %5, %5, %4}], [%2];"
                 :: "r"(dst), "l"(m), "r"(bar), "r"(c0), "r"(c3), "r"(0) : "memory");
}
__device__ __forceinline__ void tma5d(uint32_t dst, const CUtensorMap* m, int c3, int c4, uint32_t bar) {
    asm volatile("cp.async.bulk.tensor.5d.shared::cluster.global.mbarrier::complete_tx::bytes [%0], [%1, {%5, %5, %5, %3, %4}], [%2];"
                 :: "r"(dst), "l"(m), "r"(bar), "r"(c3), "r"(c4), "r"(0) : "memory");
}
__device__ __forceinline__ uint32_t mapa(uint32_t addr, uint32_t rank) {
    uint32_t r;
    asm("mapa.shared::cluster.u32 %0, %1, %2;" : "=r"(r) : "r"(addr), "r"(rank));
    return r;
}
__device__ __forceinline__ void st_async_b32(uint32_t addr, uint32_t v, uint32_t bar) {
    asm volatile("st.async.weak.shared::cluster.mbarrier::complete_tx::bytes.b32 [%0], %1, [%2];" :: "r"(addr), "r"(v), "r"(bar) : "memory");
}
__device__ __forceinline__ void st_async_v2(uint32_t addr, float a, float b, uint32_t bar) {
    asm volatile("st.async.weak.shared::cluster.mbarrier::complete_tx::bytes.v2.f32 [%0], {%1, %2}, [%3];" :: "r"(addr), "f"(a), "f"(b), "r"(bar) : "memory");
}
__device__ __forceinline__ void st_async_v4(uint32_t addr, uint32_t a, uint32_t b, uint32_t c, uint32_t d, uint32_t bar) {
    asm volatile("st.async.weak.shared::cluster.mbarrier::complete_tx::bytes.v4.b32 [%0], {%1, %2, %3, %4}, [%5];"
                 :: "r"(addr), "r"(a), "r"(b), "r"(c), "r"(d), "r"(bar) : "memory");
}
template <int ID> __device__ __forceinline__ void bar_sync() { asm volatile("bar.sync %0, 288;" :: "n"(ID) : "memory"); }
template <int ID> __device__ __forceinline__ void bar_arrive() { asm volatile("bar.arrive %0, 288;" :: "n"(ID) : "memory"); }
__device__ __forceinline__ void cbar() { asm volatile("bar.sync 1, 256;" ::: "memory"); }

__device__ __forceinline__ uint4 ldg128(const void* p) {
    uint4 v;
    asm volatile("ld.global.nc.v4.u32 {%0,%1,%2,%3}, [%4];" : "=r"(v.x), "=r"(v.y), "=r"(v.z), "=r"(v.w) : "l"(p));
    return v;
}
__device__ __forceinline__ uint32_t ldg16(const void* p) {
    uint16_t v;
    asm volatile("ld.global.nc.u16 %0, [%1];" : "=h"(v) : "l"(p));
    return v;
}
__device__ __forceinline__ uint4 ld_strong128(unsigned long long p) {
    uint4 v;
    asm volatile("ld.relaxed.gpu.global.v4.b32 {%0,%1,%2,%3}, [%4];" : "=r"(v.x), "=r"(v.y), "=r"(v.z), "=r"(v.w) : "l"(p) : "memory");
    return v;
}
__device__ __forceinline__ uint2 ld_strong64(unsigned long long p) {
    uint2 v;
    asm volatile("ld.relaxed.gpu.global.v2.b32 {%0,%1}, [%2];" : "=r"(v.x), "=r"(v.y) : "l"(p) : "memory");
    return v;
}
__device__ __forceinline__ uint32_t ldg32(const void* p) {
    uint32_t v;
    asm volatile("ld.global.nc.u32 %0, [%1];" : "=r"(v) : "l"(p));
    return v;
}
struct Pkt2 { u64 a, b; };
__device__ __forceinline__ uint32_t lo32(u64 v) { return (uint32_t)v; }
__device__ __forceinline__ uint32_t hi32(u64 v) { return (uint32_t)(v >> 32); }
__device__ __forceinline__ Pkt2 ld_pkt2(const void* p) {
    Pkt2 r;
    asm volatile("ld.relaxed.gpu.global.v2.b64 {%0,%1}, [%2];" : "=l"(r.a), "=l"(r.b) : "l"(p) : "memory");
    return r;
}
__device__ __forceinline__ bool pkt_ok(const Pkt2& r, uint32_t tag) { return hi32(r.a) == tag && hi32(r.b) == tag; }
__device__ __forceinline__ void st_pkt(u64 p, uint32_t data, uint32_t tag) {
    asm volatile("{\n.reg .b64 v;\nmov.b64 v, {%1, %2};\nst.relaxed.gpu.global.b64 [%0], v;\n}" :: "l"(p), "r"(data), "r"(tag) : "memory");
}
__device__ __forceinline__ uint4 lds128(uint32_t a) {
    uint4 v;
    asm volatile("ld.shared.v4.u32 {%0,%1,%2,%3}, [%4];" : "=r"(v.x), "=r"(v.y), "=r"(v.z), "=r"(v.w) : "r"(a) : "memory");
    return v;
}
__device__ __forceinline__ float4 lds128f(uint32_t a) {
    float4 v;
    asm volatile("ld.shared.v4.f32 {%0,%1,%2,%3}, [%4];" : "=f"(v.x), "=f"(v.y), "=f"(v.z), "=f"(v.w) : "r"(a) : "memory");
    return v;
}
__device__ __forceinline__ uint2 lds64(uint32_t a) {
    uint2 v;
    asm volatile("ld.shared.v2.u32 {%0,%1}, [%2];" : "=r"(v.x), "=r"(v.y) : "r"(a) : "memory");
    return v;
}
__device__ __forceinline__ float2 lds64f(uint32_t a) {
    float2 v;
    asm volatile("ld.shared.v2.f32 {%0,%1}, [%2];" : "=f"(v.x), "=f"(v.y) : "r"(a) : "memory");
    return v;
}
__device__ __forceinline__ float lds32f(uint32_t a) {
    float v;
    asm volatile("ld.shared.f32 %0, [%1];" : "=f"(v) : "r"(a) : "memory");
    return v;
}
__device__ __forceinline__ void sts64f(uint32_t a, float x, float y) {
    asm volatile("st.shared.v2.f32 [%0], {%1,%2};" :: "r"(a), "f"(x), "f"(y) : "memory");
}
__device__ __forceinline__ void sts128f(uint32_t a, float x, float y, float z, float w) {
    asm volatile("st.shared.v4.f32 [%0], {%1,%2,%3,%4};" :: "r"(a), "f"(x), "f"(y), "f"(z), "f"(w) : "memory");
}
__device__ __forceinline__ void sts32f(uint32_t a, float x) {
    asm volatile("st.shared.f32 [%0], %1;" :: "r"(a), "f"(x) : "memory");
}
__device__ __forceinline__ void sts128(uint32_t a, uint32_t x, uint32_t y, uint32_t z, uint32_t w) {
    asm volatile("st.shared.v4.u32 [%0], {%1,%2,%3,%4};" :: "r"(a), "r"(x), "r"(y), "r"(z), "r"(w) : "memory");
}
__device__ __forceinline__ void settle(uint32_t tag, uint32_t a, uint32_t x, uint32_t y, uint32_t z, uint32_t w) {
    asm volatile("{\n.reg .pred p;\nsetp.eq.u32 p, %0, 0;\n@p st.shared.v4.u32 [%1], {%2,%3,%4,%5};\n}" :: "r"(tag), "r"(a), "r"(x), "r"(y), "r"(z), "r"(w) : "memory");
}
__device__ __forceinline__ void settle(uint32_t tag, uint32_t a, const float4& v) {
    settle(tag, a, __float_as_uint(v.x), __float_as_uint(v.y), __float_as_uint(v.z), __float_as_uint(v.w));
}
__device__ __forceinline__ void sts16(uint32_t a, uint32_t x) {
    asm volatile("st.shared.u16 [%0], %1;" :: "r"(a), "h"((uint16_t)x) : "memory");
}
__device__ __forceinline__ void ldsm4t(uint32_t a, uint32_t (&r)[4]) {
    asm volatile("ldmatrix.sync.aligned.m8n8.x4.trans.shared.b16 {%0,%1,%2,%3}, [%4];"
                 : "=r"(r[0]), "=r"(r[1]), "=r"(r[2]), "=r"(r[3]) : "r"(a) : "memory");
}
__device__ __forceinline__ void mma(float (&c)[4], uint32_t a0, uint32_t a1, uint32_t a2, uint32_t a3, uint32_t b0, uint32_t b1) {
    asm volatile("mma.sync.aligned.m16n8k16.row.col.f32.bf16.bf16.f32 {%0,%1,%2,%3}, {%4,%5,%6,%7}, {%8,%9}, {%0,%1,%2,%3};"
                 : "+f"(c[0]), "+f"(c[1]), "+f"(c[2]), "+f"(c[3]) : "r"(a0), "r"(a1), "r"(a2), "r"(a3), "r"(b0), "r"(b1));
}
__device__ __forceinline__ void mma4(float (&c)[4], const uint32_t (&a)[4], uint32_t b0, uint32_t b1) { mma(c, a[0], a[1], a[2], a[3], b0, b1); }
__device__ __forceinline__ float sel(uint32_t c, float a, float b) {
    float r;
    asm("{\n.reg .pred p;\nsetp.ne.u32 p, %3, 0;\nselp.f32 %0, %1, %2, p;\n}" : "=f"(r) : "f"(a), "f"(b), "r"(c));
    return r;
}
__device__ __forceinline__ float bf_lo(uint32_t v) { return __uint_as_float(v << 16); }
__device__ __forceinline__ float bf_hi(uint32_t v) { return __uint_as_float(v & 0xffff0000u); }
__device__ __forceinline__ uint32_t pack2(float lo, float hi) {
    uint32_t r;
    asm("cvt.rn.bf16x2.f32 %0, %1, %2;" : "=r"(r) : "f"(hi), "f"(lo));
    return r;
}
__device__ __forceinline__ float rbf(float x) { return __uint_as_float(pack2(0.f, x)); }
__device__ __forceinline__ uint32_t hadd2(uint32_t a, uint32_t b) { uint32_t r; asm("add.rn.bf16x2 %0, %1, %2;" : "=r"(r) : "r"(a), "r"(b)); return r; }
__device__ __forceinline__ uint32_t hsub2(uint32_t a, uint32_t b) { uint32_t r; asm("sub.rn.bf16x2 %0, %1, %2;" : "=r"(r) : "r"(a), "r"(b)); return r; }
__device__ __forceinline__ uint32_t hmul2(uint32_t a, uint32_t b) { uint32_t r; asm("mul.rn.bf16x2 %0, %1, %2;" : "=r"(r) : "r"(a), "r"(b)); return r; }
__device__ __forceinline__ uint32_t hfma2(uint32_t a, uint32_t b, uint32_t c) { uint32_t r; asm("fma.rn.bf16x2 %0, %1, %2, %3;" : "=r"(r) : "r"(a), "r"(b), "r"(c)); return r; }
__device__ __forceinline__ uint32_t selu(uint32_t c, uint32_t a, uint32_t b) { return __float_as_uint(sel(c, __uint_as_float(a), __uint_as_float(b))); }
constexpr uint32_t ONE2 = 0x3f803f80u;
__device__ __forceinline__ float sigmoid_f(float x) {
    float e, r;
    asm("ex2.approx.ftz.f32 %0, %1;" : "=f"(e) : "f"(x * -1.4426950408889634f));
    asm("rcp.approx.ftz.f32 %0, %1;" : "=f"(r) : "f"(1.0f + e));
    return r;
}
__device__ __forceinline__ float silu_f(float x) { return x * sigmoid_f(x); }
__device__ __forceinline__ float rcp_sd(float m2) {
    float s, r;
    asm("sqrt.approx.ftz.f32 %0, %1;" : "=f"(s) : "f"(rbf(rbf(m2 * (1.0f / D_)) + 1e-5f)));
    asm("rcp.approx.ftz.f32 %0, %1;" : "=f"(r) : "f"(rbf(s)));
    return r;
}
__device__ __forceinline__ uint32_t ln_mod2(uint32_t x, uint32_t mean2, float rsd, uint32_t c1, uint32_t sh) {
    const uint32_t d = hsub2(x, mean2);
    return hadd2(hmul2(pack2(bf_lo(d) * rsd, bf_hi(d) * rsd), c1), sh);
}
__device__ __forceinline__ int pair_pos(int j) { return 2 * (j & 3) + (j >> 2); }

__global__ void __cluster_dims__(2, 1, 1) __launch_bounds__(THREADS, 1)
fused_decode_kernel(const __grid_constant__ Ptrs q_, const __grid_constant__ Params p) {
    extern __shared__ __align__(1024) unsigned char smem[];
    unsigned t_top;
    asm volatile("mov.u32 %0, %%globaltimer_lo;" : "=r"(t_top));
    const int tid = threadIdx.x;
    uint32_t z0;
    asm("and.b32 %0, %1, 1024;" : "=r"(z0) : "r"(tid));
    const char* kw = *(const char* const*)((const char*)&q_.kwin + z0);
    const uint32_t sb = (uint32_t)__cvta_generic_to_shared(smem);
    auto place = [](int cl) { return cl < 4 ? 8 * cl + 39 : cl - 4 + max((cl * 37 - 36 * 37) >> 8, 0); };
    uint32_t z2;
    asm("and.b32 %0, %1, 2048;" : "=r"(z2) : "r"(tid));
    const int cv = blockIdx.x + z2, pw = place(cv >> 1);
    static_assert(SK * DH * 2 == 1 << 22 && TILE_BYTES == 1 << 14, "koff");
    const char* kp;
    auto set_kp = [&](uint32_t off) {
        asm volatile("{\n.reg .u32 lo, hi;\nmov.b64 {lo, hi}, %1;\nadd.cc.u32 lo, lo, %2;\naddc.u32 hi, hi, 0;\nmov.b64 %0, {lo, hi};\n}"
                     : "=l"(kp) : "l"(kw), "r"(off));
    };
    uint64_t pol;
    asm("createpolicy.fractional.L2::evict_first.b64 %0, 1.0;" : "=l"(pol));
    auto fill_k = [&](int n) {
        mbar_expect_tx(sb + full_bar(n), TILE_BYTES);
        bulk_load(sb + slot_addr(n), kp + (n - N_K) * 2 * TILE_BYTES, TILE_BYTES, sb + full_bar(n), pol);
    };
    static_assert(K_FIRST >= 1, "head block starts with K tile 0");
    if (tid + (sb >> 28) == HEAD_TID) {
        mbar_init(sb + full_bar(N_K), 1);
        set_kp(((pw & 7) << 22) | ((pw & 8) << 24) | ((pw & 48) << 21) | ((cv & 1) << 14));
        bulk_load(sb + slot_addr(N_K), kp, TILE_BYTES, sb + full_bar(N_K), pol);
        mbar_expect_tx(sb + full_bar(N_K), TILE_BYTES);
#pragma unroll
        for (int j = 1; j < K_FIRST; j++) { mbar_init(sb + full_bar(N_K + j), 1); fill_k(N_K + j); }
    }
    __syncwarp();
    const int cta = blockIdx.x, rank = cta & 1, pv = place(cta >> 1);
    const int b = (pv >> 3) & 1, h = (pv & 7) | ((pv >> 1) & 24), bh = 32 * b + h;
    const int mc = 2 * pv + rank;
    auto first_fill = [&](int j) {
        const int n = fill_tile(j);
        if (n >= N_K) {
            fill_k(n);
        } else if (n >= N_WQ) {
            mbar_expect_tx(sb + full_bar(n), TILE_BYTES);
            tma2d(sb + slot_addr(n), &p.m_wq, h * DH + 64 * rank, 128 * (n - N_WQ), sb + full_bar(n));
        } else if (mc < N_MOD_CTA) {
            mbar_expect_tx(sb + full_bar(n), TILE_BYTES);
            tma2d(sb + slot_addr(n), &p.m_wmod, 32 * mc, 256 * n, sb + full_bar(n));
        } else {
            mbar_arrive(sb + full_bar(n));
        }
    };
    if (tid == HEAD_TID) {
#pragma unroll
        for (int j = K_FIRST; j < FIRST_N; j++) mbar_init(sb + full_bar(fill_tile(j)), 1);
#pragma unroll
        for (int j = K_FIRST; j < FIRST_N; j++) first_fill(j);
        asm volatile("fence.mbarrier_init.release.cluster;" ::: "memory");
    }
    __syncwarp();
    const int role = cta / 3;
    const bool is_gu = cta == 3 * role, is_gb = cta == 3 * role + 1 && role < 32;
    if (tid >= 288) {
        const unsigned t_start = t_top;
        asm volatile("barrier.cluster.arrive.relaxed.aligned;" ::: "memory");
        unsigned tag;
        asm volatile("ld.relaxed.gpu.global.u32 %0, [%1];" : "=r"(tag) : "l"(&g_epoch) : "memory");
        tag += 1;
        if (cta == NCTA - 1) {
#pragma unroll 2
            for (int i = tid - 288; i < 128 * 8; i += 32) {
                uint4* q = reinterpret_cast<uint4*>(s_line(i >> 6, (i >> 3) & 7)) + (i & 7);
                const uint32_t v = (i & 48) == 48 ? ~0u : 0u;
                q[0] = make_uint4(v, v, v, v);
                q[8] = q[32] = q[40] = make_uint4(0u, 0u, 0u, 0u);
            }
            __syncwarp();
            asm volatile("fence.acq_rel.gpu;" ::: "memory");
            if (tid == 288) asm volatile("st.relaxed.gpu.global.u32 [%0], %1;" :: "l"(&g_clear), "r"(tag) : "memory");
        }
        asm volatile("barrier.cluster.wait.acquire.aligned;" ::: "memory");
        mbar_wait_cluster(sb + BAR_XQ, 0);
#pragma unroll 1
        for (uint32_t n = 0; n < SPIN_LIMIT; n++) {
            unsigned c;
            asm volatile("ld.relaxed.gpu.global.u32 %0, [%1];" : "=r"(c) : "l"(&g_clear) : "memory");
            if (c == tag) break;
        }
        asm volatile("fence.acq_rel.gpu;" ::: "memory");
        asm volatile("st.volatile.shared.u32 [%0], %1;" :: "r"(sb + SM_SIDE), "r"(0) : "memory");
        asm volatile("bar.sync 2, 288;" ::: "memory");
        if (elect_one()) {
            asm volatile("prefetch.tensormap [%0];" :: "l"(is_gu ? &p.m_w1 : &p.m_gb) : "memory");
            asm volatile("prefetch.tensormap [%0];" :: "l"(&p.m_w3) : "memory");
            asm volatile("prefetch.tensormap [%0];" :: "l"(&p.m_w2) : "memory");
            const int issue = ((4 * N_GATE - 11) * PACE >> 2) - LEAD_NS;
            unsigned now, c = 0, best[2] = {~0u, ~0u}, np = is_gu ? 0 : PROBES;
            auto probe = [&]() {
                const int k = np >> 1, i = (role >> 3) + 2 * k;
                const u64 a = (s_line(e1_blk(0, role & 7), i < 6 ? i : i - 6) + (k ? 512 * k - 384 : 0)) ^ ((np & 1) << 12);
                unsigned v, c0, c1 = 0;
                asm volatile("mov.u32 %0, %%clock;" : "=r"(c0));
                asm volatile("ld.relaxed.gpu.global.u32 %0, [%1];" : "=r"(v) : "l"(a) : "memory");
                asm volatile("{\n.reg .pred p;\nsetp.ne.u32 p, %1, 0xffffffff;\n@p mov.u32 %0, %%clock;\n}" : "+r"(c1) : "r"(v));
                if (np & 1) best[1] = min(best[1], c1 - c0); else best[0] = min(best[0], c1 - c0);
                np++;
                if (!(np & 1)) asm volatile("st.volatile.shared.u32 [%0], %1;" :: "r"(sb + SM_SIDE), "r"(best[0] <= best[1] ? 0 : 4096) : "memory");
            };
#pragma unroll 1
            while (np < PROBES) {
                now = time_ns();
                if ((int)(now - t_start) >= issue + EARLY_NS) break;
                probe();
            }
            mbar_wait(sb + full_bar(N_GATE), tile_phase(N_GATE));
            now = time_ns();
            const unsigned mine = (1u << 24) + min(now - t_start, 100000u);
            const u64 prog = s_line(0, 7) + S_PROG;
            asm volatile("red.relaxed.gpu.global.add.u32 [%0], %1;" :: "l"(prog), "r"(mine) : "memory");
            if (is_gu || is_gb) {
#pragma unroll
                for (int i = 0; i < 6; i++) mbar_wait(sb + empty_bar(N_FFN + i), tile_phase(N_FFN + i) ^ 1);
#pragma unroll
                for (int i = 0; i < NQ; i++) mbar_expect_tx(sb + BAR_FFN + 8 * i, is_gu ? 65536 / NQ : 8192);
#pragma unroll
                for (int i = 0; i < NW; i++) mbar_expect_tx(sb + BAR_W2 + 8 * i, 32768 / NW);
                unsigned due = 0, next = now;
                constexpr unsigned full = (unsigned)NCTA << 24;
                asm volatile("st.volatile.shared.u32 [%0], %1;" :: "r"(sb + SM_PROG), "r"(mine) : "memory");
#pragma unroll 1
                for (uint32_t n = 0; n < 4096; n++) {
                    unsigned v;
                    asm volatile("ld.volatile.shared.u32 %0, [%1];" : "=r"(v) : "r"(sb + SM_PROG) : "memory");
                    if (v > c) {
                        c = v;
                        const int arr = (int)__fdividef((float)(c & 0xffffffu), (float)(c >> 24));
                        due = arr - ((arr - issue) * ALPHA16 >> 4) + (is_gb ? W2_NS - GB_LEAD : GU_NS);
                    }
                    now = time_ns();
                    if (now - t_start + PROBE_NS >= due) np = PROBES;
                    if ((c >= full && np == PROBES) || now - t_start >= due) break;
                    if ((int)(now - next) >= 0 && c < full) {
                        asm volatile("cp.async.cg.shared.global [%0], [%1], 16;" :: "r"(sb + SM_PROG), "l"(prog) : "memory");
                        next = now + POLL_NS;
                    }
                    if (np < PROBES) probe();
                }
#pragma unroll 1
                for (uint32_t n = 0; n < 1024 && now - t_start < due; n++) now = time_ns();
                if (is_gu) {
#pragma unroll
                    for (int i = 0; i < 2 * NQ; i++) {
                        const int q = i >> 1, r0 = q * (512 / NQ);
                        tma4d(sb + slot_addr(N_FFN) + (r0 >> 8) * 2 * TILE_BYTES + (i & 1) * TILE_BYTES + (r0 & 255) * 64, (i & 1) ? &p.m_w3 : &p.m_w1, 32 * role, r0 / 16, sb + BAR_FFN + 8 * q);
                    }
#pragma unroll 1
                    for (uint32_t n = 0; n < 1024 && now - t_start < due + (W2_NS - GU_NS); n++) now = time_ns();
                    const int f = best[0] <= best[1] ? NW / 2 : 0;
#pragma unroll
                    for (int i = 0; i < NW; i++) tma5d(sb + slot_addr(N_FFN + 4) + (i ^ f) * (32768 / NW), &p.m_w2, 2 * role, (i ^ f) * (8 / NW), sb + BAR_W2 + 8 * (i ^ f));
                } else {
                    tma2d(sb + slot_addr(N_FFN), &p.m_gb, 5 * D_ + 16 * role, 0, sb + BAR_FFN);
                    tma2d(sb + slot_addr(N_FFN) + 8192, &p.m_gb, 5 * D_ + 16 * role, 256, sb + BAR_FFN + 8);
                }
                asm volatile("cp.async.wait_all;" ::: "memory");
            }
        }
        __syncwarp();
        if (is_gu) {
            const int lane = tid & 31;
            auto sum8 = [&](uint32_t a, int stride) {
                float4 u[8];
#pragma unroll
                for (int i = 0; i < 8; i++) u[i] = lds128f(a + i * stride);
                return make_float4(((u[0].x + u[1].x) + (u[2].x + u[3].x)) + ((u[4].x + u[5].x) + (u[6].x + u[7].x)),
                                   ((u[0].y + u[1].y) + (u[2].y + u[3].y)) + ((u[4].y + u[5].y) + (u[6].y + u[7].y)),
                                   ((u[0].z + u[1].z) + (u[2].z + u[3].z)) + ((u[4].z + u[5].z) + (u[6].z + u[7].z)),
                                   ((u[0].w + u[1].w) + (u[2].w + u[3].w)) + ((u[4].w + u[5].w) + (u[6].w + u[7].w)));
            };
            uint32_t h_st = sb + SM_Q + (((lane & 1) * 4 + ((lane >> 2) & 3)) * 4 + (lane & 2) + (lane >> 4)) * 4;
            bar_sync<3>();
            const float4 C = sum8(sb + SM_P + lane * 16, 1024), S = sum8(sb + SM_P + 512 + lane * 16, 1024);
            const uint32_t st_ld = sb + SM_RED + (lane & 1) * 64;
            settle(tag, sb + SM_OP, C); settle(tag, sb + SM_OP, S); settle(tag, sb + SM_OP, h_st, st_ld, 0, 0);
            bar_sync<4>();
            const float4 r0 = lds128f(st_ld), r1 = lds128f(st_ld + 16), r2 = lds128f(st_ld + 32), r3 = lds128f(st_ld + 48);
            const float4 Y = sum8(sb + SM_PART + lane * 16, 512);
            const float e1 = r0.z - r0.x, e2 = r1.x - r0.x, e3 = r1.z - r0.x, e4 = r2.x - r0.x, e5 = r2.z - r0.x, e6 = r3.x - r0.x, e7 = r3.z - r0.x;
            const float se = ((e1 + e2) + (e3 + e4)) + ((e5 + e6) + e7);
            const float ee = (fmaf(e1, e1, e2 * e2) + fmaf(e3, e3, e4 * e4)) + fmaf(e5, e5, fmaf(e6, e6, e7 * e7));
            const float sq = ((r0.y + r0.w) + (r1.y + r1.w)) + ((r2.y + r2.w) + (r3.y + r3.w));
            float rsd;
            asm("rsqrt.approx.ftz.f32 %0, %1;" : "=f"(rsd) : "f"(fmaf(fmaf(se * (-1.0f / D_), se, fmaf(ee, 1.0f / 64, sq)), 1.0f / D_, 1e-5f)));
            const float mu = -rbf(fmaf(r0.x, 8.0f, se) * (1.0f / D_));
            const float g0 = fmaf(rsd, fmaf(mu, C.x, Y.x), S.x), g1 = fmaf(rsd, fmaf(mu, C.z, Y.z), S.z);
            const float u0 = fmaf(rsd, fmaf(mu, C.y, Y.y), S.y), u1 = fmaf(rsd, fmaf(mu, C.w, Y.w), S.w);
            const uint32_t hv = pack2(silu_f(g0) * u0, silu_f(g1) * u1);
            sts32f(h_st, __uint_as_float(hv));
            bar_arrive<5>();
            if (role == 0 && lane == 0) g_epoch = tag;
        }
        return;
    }
    if (tid >= 256) {
        set_kp(bh * (SK * DH * 2) + rank * TILE_BYTES);
        const unsigned t_start = t_top;
        auto pace = [&](int q4) {
            const int due = (q4 * PACE >> 2) - LEAD_NS;
            unsigned now, n = 0;
            do { now = time_ns(); } while ((int)(now - t_start) < due && ++n < 256);
        };
        if (tid == 256) {
#pragma unroll
            for (int j = FIRST_N; j < STAGES; j++) mbar_init(sb + full_bar(fill_tile(j)), 1);
#pragma unroll
            for (int s = 0; s < STAGES; s++) mbar_init(sb + BAR_EMPTY + 8 * s, 8);
            mbar_init(sb + BAR_XQ, 1); mbar_init(sb + BAR_XML, 1); mbar_init(sb + BAR_XP, 1); mbar_init(sb + BAR_XO, 1);
#pragma unroll
            for (int i = 0; i < NQ + NW; i++) mbar_init(sb + BAR_FFN + 8 * i, 1);
            mbar_expect_tx(sb + BAR_XQ, 256); mbar_expect_tx(sb + BAR_XML, 8); mbar_expect_tx(sb + BAR_XP, WIN); mbar_expect_tx(sb + BAR_XO, 1024);
            asm volatile("fence.mbarrier_init.release.cluster;" ::: "memory");
            asm volatile("fence.proxy.async.shared::cta;" ::: "memory");
        }
        __syncwarp();
        asm volatile("barrier.cluster.arrive.relaxed.aligned;" ::: "memory");
        if (elect_one()) {
#pragma unroll
            for (int j = FIRST_N; j < STAGES; j++) {
                pace(j <= K_FIRST ? 4 * j : j <= K_FIRST + 2 ? 4 * K_FIRST + 5 * (j - K_FIRST) / 2 :
                     j <= K_FIRST + 6 ? 4 * K_FIRST + 5 + 2 * (j - K_FIRST - 2) : 4 * j - 11);
                first_fill(j);
            }
        }
        __syncwarp();
        asm volatile("barrier.cluster.wait.acquire.aligned;" ::: "memory");
        if (elect_one()) {
            asm volatile("prefetch.tensormap [%0];" :: "l"(&p.m_v) : "memory");
            asm volatile("prefetch.tensormap [%0];" :: "l"(&p.m_wo) : "memory");
            int s = 0, ph = 0;
#pragma unroll 1
            for (int n = STAGES; n < N_FFN; n++) {
                const uint32_t dst = sb + SM_RING + s * TILE_BYTES, bar = sb + BAR_FULL + 8 * s;
                mbar_wait(sb + BAR_EMPTY + 8 * s, ph);
                mbar_expect_tx(bar, TILE_BYTES);
                pace(n < N_WO ? 4 * n - 11 : 2 * (N_WO + n) - 11);
                if (n < N_V) bulk_load(dst, kp + (n - N_K) * 2 * TILE_BYTES, TILE_BYTES, bar, pol);
                else if (n < N_WO) tma2d_hint(dst, &p.m_v, 64 * rank, bh * SK + (SK - WIN) + 128 * (n - N_V), bar, pol);
                else tma3d(dst, &p.m_wo, 0, h * DH + 32 * (n - N_WO), 4 * rank, bar);
                if (++s == STAGES) { s = 0; ph ^= 1; }
            }
        }
        return;
    }

    const unsigned t_c = t_top;
    const int lane = tid & 31, w = tid >> 5, g = lane >> 2, t = lane & 3;
    const int hgrp = 4 * w + (g & 3);
    const int vb = g >> 2;
    const uint32_t cv0 = ldg32(q_.c + vb * D_ + 16 * hgrp + 2 * t), cv1 = ldg32(q_.c + vb * D_ + 16 * hgrp + 8 + 2 * t);
    unsigned tag;
    asm volatile("ld.relaxed.gpu.global.u32 %0, [%1];" : "=r"(tag) : "l"(&g_epoch) : "memory");
    const uint4 xa = ldg128(q_.x + b * D_ + 16 * lane), xb = ldg128(q_.x + b * D_ + 16 * lane + 8);
    const uint32_t xh0 = ldg32(q_.x + b * D_ + 16 * hgrp + 2 * t), xh1 = ldg32(q_.x + b * D_ + 16 * hgrp + 8 + 2 * t);
    asm volatile("barrier.cluster.arrive.relaxed.aligned;" ::: "memory");
#pragma unroll 1
    for (uint32_t n = t_c; n < 2; n++) asm volatile("nanosleep.u32 1;" ::: "memory");
    const int grp = w >> 2, sub = w & 3;
    const int lrow = (lane & 7) + 8 * (lane >> 4);
    const int lch = (lane >> 3) & 1;
    const int ob = lane >> 4;
    const uint32_t t1 = t & 1, t2 = t & 2;
    const int gsrc = 16 * (g & 1) + t;
    const uint32_t sw128 = lrow * 128 + ((lch ^ (lrow & 7)) << 4);
    uint32_t A[16][4];

    const uint32_t sc0 = pack2(silu_f(bf_lo(cv0)), silu_f(bf_hi(cv0))), sc1 = pack2(silu_f(bf_lo(cv1)), silu_f(bf_hi(cv1)));
    tag += 1;
    asm volatile("barrier.cluster.wait.acquire.aligned;" ::: "memory");
    mbar_wait(sb + BAR_FULL + 8 * (N_WMOD + grp), 0);
    if (mc < N_MOD_CTA) {
        const uint32_t tb = sb + SM_RING + (N_WMOD + grp) * TILE_BYTES + (64 * sub + lrow) * 64;
#pragma unroll
        for (int i = 0; i < 8; i++)
            ldsm4t(tb + (i >> 1) * 1024 + (((2 * (i & 1) + lch) ^ ((lrow >> 1) & 3)) << 4), A[i]);
        float acc[2][4] = {{0.f, 0.f, 0.f, 0.f}, {0.f, 0.f, 0.f, 0.f}};
#pragma unroll
        for (int s = 0; s < 4; s++) {
            const uint32_t b0 = __shfl_sync(~0u, sc0, 4 * s + gsrc), b1 = __shfl_sync(~0u, sc1, 4 * s + gsrc);
            mma4(acc[0], A[2 * s], b0, b1);
            mma4(acc[1], A[2 * s + 1], b0, b1);
        }
        sts32f(sb + SM_P + (w * 64 + 8 * t + g) * 4, sel(t2, sel(t1, acc[1][2], acc[1][0]), sel(t1, acc[0][2], acc[0][0])));
        sts32f(sb + SM_P + (w * 64 + 32 + 8 * t + g) * 4, sel(t2, sel(t1, acc[1][3], acc[1][1]), sel(t1, acc[0][3], acc[0][1])));
        cbar();
        if (w == 0) {
            const bool adj = mc < 32;
            const uint32_t a0 = sb + SM_P + (adj ? 2 * lane : ob * 32 + (lane & 1) * 16 + ((lane >> 1) & 7)) * 4, a1 = a0 + (adj ? 4 : 32);
            float2 sum = make_float2(0.f, 0.f);
#pragma unroll
            for (int i = 0; i < 8; i++) { sum.x += lds32f(a0 + i * 256); sum.y += lds32f(a1 + i * 256); }
            st_pkt((u64)&g_mod[ob][16 * mc + (adj ? (lane & 8) + pair_pos(lane & 7) : lane & 15)], pack2(sum.x, sum.y), tag);
        }
    }
    __syncwarp();
    if (lane == 0) mbar_arrive_n(sb + BAR_EMPTY + 8 * (N_WMOD + grp), 2);

    {
        const uint2* mp = &g_mod[b][vb * 256 + 8 * hgrp + 2 * t];
        const uint32_t ms = sb + SM_PART + tid * 16;
        auto fetch_mod = [&](uint32_t k) {
            asm volatile("cp.async.cg.shared.global [%0], [%1], 16;\ncp.async.commit_group;" :: "r"(ms + k), "l"(mp) : "memory");
        };
        fetch_mod(0);
        float xs[16] = {bf_lo(xa.x), bf_hi(xa.x), bf_lo(xa.y), bf_hi(xa.y), bf_lo(xa.z), bf_hi(xa.z), bf_lo(xa.w), bf_hi(xa.w),
                        bf_lo(xb.x), bf_hi(xb.x), bf_lo(xb.y), bf_hi(xb.y), bf_lo(xb.z), bf_hi(xb.z), bf_lo(xb.w), bf_hi(xb.w)};
        float s = 0.f;
#pragma unroll
        for (int i = 0; i < 16; i++) s += xs[i];
#pragma unroll
        for (int m = 1; m < 32; m <<= 1) s += __shfl_xor_sync(~0u, s, m);
        const float mean = s * (1.0f / D_);
        float q = 0.f;
#pragma unroll
        for (int i = 0; i < 16; i++) q += (xs[i] - mean) * (xs[i] - mean);
#pragma unroll
        for (int m = 1; m < 32; m <<= 1) q += __shfl_xor_sync(~0u, q, m);
        const uint32_t mean2 = pack2(mean, mean);
        const float rsd = rcp_sd(q);

        mbar_wait(sb + BAR_FULL + 8 * (N_WQ + (w >> 1)), 0);
        const uint32_t tb = sb + SM_RING + (N_WQ + (w >> 1)) * TILE_BYTES + (w & 1) * 8192;
#pragma unroll
        for (int i = 0; i < 16; i++) ldsm4t(tb + (i >> 2) * 2048 + (sw128 ^ ((i & 3) * 32)), A[i]);
        __syncwarp();
        if (lane == 0) mbar_arrive_n(sb + BAR_EMPTY + 8 * (N_WQ + (w >> 1)), 4);

        Pkt2 m;
        for (uint32_t n = 0, k = 0; n < SPIN_LIMIT; n++) {
            fetch_mod(k ^ 4096);
            asm volatile("cp.async.wait_group 1;" ::: "memory");
            const uint4 u = lds128(ms + k);
            m.a = u.x | (u64)u.y << 32; m.b = u.z | (u64)u.w << 32;
            if (__all_sync(~0u, pkt_ok(m, tag))) break;
            k ^= 4096;
        }
        const uint32_t ca0 = __shfl_xor_sync(~0u, lo32(m.a), 16), ca1 = __shfl_xor_sync(~0u, lo32(m.b), 16);
        const uint32_t v0 = ln_mod2(xh0, mean2, rsd, hadd2(ONE2, ca0), lo32(m.a));
        const uint32_t v1 = ln_mod2(xh1, mean2, rsd, hadd2(ONE2, ca1), lo32(m.b));
        float acc[4][4];
#pragma unroll
        for (int i = 0; i < 4; i++) { acc[i][0] = acc[i][1] = acc[i][2] = acc[i][3] = 0.f; }
#pragma unroll
        for (int s4 = 0; s4 < 4; s4++) {
            const uint32_t b0 = __shfl_sync(~0u, v0, 4 * s4 + t), b1 = __shfl_sync(~0u, v1, 4 * s4 + t);
#pragma unroll
            for (int i = 0; i < 4; i++) mma4(acc[i], A[4 * s4 + i], b0, b1);
        }
        sts32f(sb + SM_OP + (w * 64 + 16 * t + g) * 4, sel(t2, sel(t1, acc[3][0], acc[2][0]), sel(t1, acc[1][0], acc[0][0])));
        sts32f(sb + SM_OP + (w * 64 + 16 * t + 8 + g) * 4, sel(t2, sel(t1, acc[3][2], acc[2][2]), sel(t1, acc[1][2], acc[0][2])));
        cbar();
        if (w == 0) {
            float2 sum = make_float2(0.f, 0.f);
#pragma unroll
            for (int i = 0; i < 8; i++) { const float2 u = lds64f(sb + SM_OP + (i * 64 + 2 * lane) * 4); sum.x += u.x; sum.y += u.y; }
            const uint32_t v = pack2(sum.x, sum.y), a = sb + SM_Q + rank * 128 + lane * 4;
            st_async_b32(mapa(a, rank ^ 1), v, mapa(sb + BAR_XQ, rank ^ 1));
            st_async_b32(mapa(a, rank), v, mapa(sb + BAR_XQ, rank));
        }
        mbar_wait_cluster(sb + BAR_XQ, 0);
    }

    Pkt2 mga, msb, mcb;
    uint32_t tx0, tx1;
    const uint2* tmp = &g_mod[ob][32 * w + 2 * (lane & 15)];
    {
        uint4 Q[4];
        uint32_t koff[4];
#pragma unroll
        for (int i = 0; i < 4; i++) {
            const int ch = t + 4 * (i ^ (g & 1));
            Q[i] = lds128(sb + SM_Q + ch * 16);
            koff[i] = (sub * 16 + g) * 256 + ch * 16;
        }
        float mx = -INFINITY;
        int stage = N_K + grp, phase = 0;
#pragma unroll 1
        for (int it = 0; it < NT / 2; it++) {
            const uint32_t tb = sb + SM_RING + stage * TILE_BYTES;
            mbar_wait(sb + BAR_FULL + 8 * stage, phase);
            uint4 Ka[4], Kb[4];
#pragma unroll
            for (int i = 0; i < 4; i++) { Ka[i] = lds128(tb + koff[i]); Kb[i] = lds128(tb + koff[i] + 2048); }
            float c0[4] = {0.f, 0.f, 0.f, 0.f}, c1[4] = {0.f, 0.f, 0.f, 0.f};
#pragma unroll
            for (int i = 0; i < 4; i++) {
                mma(c0, Ka[i].x, Kb[i].x, Ka[i].y, Kb[i].y, Q[i].x, Q[i].y);
                mma(c1, Ka[i].z, Kb[i].z, Ka[i].w, Kb[i].w, Q[i].z, Q[i].w);
            }
            __syncwarp();
            if (lane == 0) mbar_arrive_n(sb + BAR_EMPTY + 8 * stage, 2);
            const float lo = (g & 1) ? c0[1] + c1[1] : c0[0] + c1[0];
            const float hi = (g & 1) ? c0[3] + c1[3] : c0[2] + c1[2];
            const float sc = rbf(rbf(t1 ? hi : lo) * 0.08838834764831845f);
            mx = fmaxf(mx, sc);
            if (t < 2) sts16(sb + SM_P + ((2 * it + grp) * 128 + rank * 64 + sub * 16 + 4 * (g >> 1) + 2 * t + (g & 1)) * 2, __float_as_uint(sc) >> 16);
            stage += 2;
            if (stage >= STAGES) { stage -= STAGES; phase ^= 1; }
        }

        mga = ld_pkt2(tmp + 2 * 256); msb = ld_pkt2(tmp + 3 * 256); mcb = ld_pkt2(tmp + 4 * 256);
        const __nv_bfloat16* xp = q_.x + ob * D_ + 64 * w + 4 * (lane & 8) + (lane & 7);
        tx0 = ldg16(xp) | ldg16(xp + 8) << 16;
        tx1 = ldg16(xp + 16) | ldg16(xp + 24) << 16;

        asm volatile("cp.async.wait_all;" ::: "memory");

#pragma unroll
        for (int m = 1; m < 32; m <<= 1) mx = fmaxf(mx, __shfl_xor_sync(~0u, mx, m));
        if (lane == 0) sts32f(sb + SM_RED + w * 4, mx);
        cbar();
        {
            const float4 u = lds128f(sb + SM_RED), v = lds128f(sb + SM_RED + 16);
            mx = fmaxf(fmaxf(fmaxf(u.x, u.y), fmaxf(u.z, u.w)), fmaxf(fmaxf(v.x, v.y), fmaxf(v.z, v.w)));
        }
        const uint32_t pa = sb + SM_P + (tid >> 3) * 256 + rank * 128 + (tid & 7) * 16;
        const uint4 s0 = lds128(pa);
        const float sc[8] = {bf_lo(s0.x), bf_hi(s0.x), bf_lo(s0.y), bf_hi(s0.y), bf_lo(s0.z), bf_hi(s0.z), bf_lo(s0.w), bf_hi(s0.w)};
        float l = 0.f;
#pragma unroll
        for (int i = 0; i < 8; i++) l += __expf(sc[i] - mx);
#pragma unroll
        for (int m = 1; m < 32; m <<= 1) l += __shfl_xor_sync(~0u, l, m);
        if (lane == 0) sts32f(sb + SM_RED + 32 + w * 4, l);
        cbar();
        {
            const float4 u = lds128f(sb + SM_RED + 32), v = lds128f(sb + SM_RED + 48);
            l = ((u.x + u.y) + (u.z + u.w)) + ((v.x + v.y) + (v.z + v.w));
        }
        if (tid == 0) st_async_v2(mapa(sb + SM_ML, rank ^ 1), mx, l, mapa(sb + BAR_XML, rank ^ 1));
        mbar_wait_cluster(sb + BAR_XML, 0);
        const float2 o = lds64f(sb + SM_ML);
        const float m = fmaxf(mx, o.x);
        const float inv = __fdividef(1.0f, l * __expf(mx - m) + o.y * __expf(o.x - m));
        const uint32_t p0 = pack2(__expf(sc[0] - m) * inv, __expf(sc[1] - m) * inv), p1 = pack2(__expf(sc[2] - m) * inv, __expf(sc[3] - m) * inv);
        const uint32_t p2 = pack2(__expf(sc[4] - m) * inv, __expf(sc[5] - m) * inv), p3 = pack2(__expf(sc[6] - m) * inv, __expf(sc[7] - m) * inv);
        st_async_v4(mapa(pa, rank ^ 1), p0, p1, p2, p3, mapa(sb + BAR_XP, rank ^ 1));
        sts128(pa, p0, p1, p2, p3);
        cbar();
        mbar_wait_cluster(sb + BAR_XP, 0);
    }

#pragma unroll 1
    for (uint32_t n = 0; n < SPIN_LIMIT && !__all_sync(~0u, pkt_ok(mga, tag) && pkt_ok(msb, tag) && pkt_ok(mcb, tag)); n++) {
        mga = ld_pkt2(tmp + 2 * 256); msb = ld_pkt2(tmp + 3 * 256); mcb = ld_pkt2(tmp + 4 * 256);
    }
    const uint32_t ga0 = lo32(mga.a), ga1 = lo32(mga.b), sb0 = lo32(msb.a), sb1 = lo32(msb.b);
    const uint32_t cb0 = hadd2(ONE2, lo32(mcb.a)), cb1 = hadd2(ONE2, lo32(mcb.b));
    const int wb = 4 * rank + sub;
    u64 red_p = s_line(e1_blk(1, wb), 2 * b) + lane * 4, red2_p = s_line(e1_blk(1, wb), 4 + b) + lane * 4;

    PIN64(red_p); PIN64(red2_p);
    float oa[4][4];
#pragma unroll
    for (int i = 0; i < 4; i++) { oa[i][0] = oa[i][1] = oa[i][2] = oa[i][3] = 0.f; }
    {
        int stage = N_V % STAGES, phase = tile_phase(N_V);
        auto v_tiles = [&](int v0, int v1) {
#pragma unroll 1
            for (int v = v0; v < v1; v++) {
                const uint32_t tb = sb + SM_RING + stage * TILE_BYTES + grp * 8192 + (sw128 ^ (sub * 32));
                uint2 P[4];
#pragma unroll
                for (int i = 0; i < 4; i++) P[i] = lds64(sb + SM_P + v * 256 + grp * 128 + i * 32 + t * 8);
                mbar_wait(sb + BAR_FULL + 8 * stage, phase);
                uint32_t a[4][4];
#pragma unroll
                for (int i = 0; i < 4; i++) ldsm4t(tb + i * 2048, a[i]);
#pragma unroll
                for (int i = 0; i < 4; i++) mma4(oa[i], a[i], P[i].x, P[i].y);
                __syncwarp();
                if (lane == 0) mbar_arrive(sb + BAR_EMPTY + 8 * stage);
                if (++stage == STAGES) { stage = 0; phase ^= 1; }
            }
        };
        v_tiles(0, MEET_AT);
        asm volatile("bar.sync 2, 288;" ::: "memory");
        v_tiles(MEET_AT, NT);
    }

    if (t < 2) {
        const uint32_t a = sb + SM_OP + rank * 512 + w * 64 + (g >> 1) * 16 + (g & 1) * 4 + t * 8;
        const uint32_t v = __float_as_uint(sel(t1, (oa[0][2] + oa[1][2]) + (oa[2][2] + oa[3][2]), (oa[0][0] + oa[1][0]) + (oa[2][0] + oa[3][0])));
        st_async_b32(mapa(a, rank ^ 1), v, mapa(sb + BAR_XO, rank ^ 1));
        st_async_b32(mapa(a, rank), v, mapa(sb + BAR_XO, rank));
    }
    __syncwarp();
    mbar_wait_cluster(sb + BAR_XO, 0);

    {
        float acc[4][4];
        const uint32_t o_ld = sb + SM_OP + grp * 512 + (lane & 15) * 16 + vb * 8, x_st = sb + SM_PART + 4096 + sub * 1024 + lane * 16;
        const float2 u = lds64f(o_ld), v = lds64f(o_ld + 256);
        const uint32_t o2 = pack2(u.x + v.x, u.y + v.y);
        uint32_t bo[8];
#pragma unroll
        for (int i = 0; i < 8; i++) bo[i] = __shfl_sync(~0u, o2, 16 * (i & 1) + 4 * (i >> 1) + t);
        float4 x0 = make_float4(0.f, 0.f, 0.f, 0.f), x1 = x0;
#pragma unroll
        for (int i = 0; i < 4; i++) { acc[i][0] = acc[i][1] = acc[i][2] = acc[i][3] = 0.f; }
        static_assert(N_WO % STAGES + 4 <= STAGES, "wo tiles occupy consecutive slots");
        const uint32_t wa = sb + slot_addr(N_WO) + grp * 2 * TILE_BYTES + sub * 4096, wbar = sb + full_bar(N_WO) + grp * 16;
#pragma unroll
        for (int j = 0; j < 2; j++) {
            if (j == 1 && grp) { asm volatile("bar.sync 8, 256;" ::: "memory"); x0 = lds128f(x_st); x1 = lds128f(x_st + 512); }
            mbar_wait(wbar + 8 * j, tile_phase(N_WO));
            if (j == 1) { }
#pragma unroll
            for (int i = 0; i < 8; i++) ldsm4t(wa + j * TILE_BYTES + (i >> 2) * 2048 + (sw128 ^ ((i & 3) * 32)), A[8 * j + i]);
#pragma unroll
            for (int i = 0; i < 8; i++) mma4(acc[i & 3], A[8 * j + i], bo[4 * j + 2 * (i >> 2)], bo[4 * j + 2 * (i >> 2) + 1]);
        }
        if (!grp) {
            sts128f(x_st, acc[0][0], acc[1][0], acc[2][0], acc[3][0]); sts128f(x_st + 512, acc[0][2], acc[1][2], acc[2][2], acc[3][2]);
            asm volatile("bar.arrive 8, 256;" ::: "memory");
        } else {
            acc[0][0] += x0.x; acc[1][0] += x0.y; acc[2][0] += x0.z; acc[3][0] += x0.w; acc[0][2] += x1.x; acc[1][2] += x1.y; acc[2][2] += x1.z; acc[3][2] += x1.w;
            const float r0 = sel(t2, sel(t1, 1.0f, acc[1][0]), sel(t1, acc[0][2], acc[0][0]));
            const float r1 = sel(t2, sel(t1, 1.0f, acc[3][0]), sel(t1, acc[2][2], acc[2][0]));
            const float r2 = sel(t2, 1.0f, sel(t1, acc[3][2], acc[1][2]));
            asm volatile("red.relaxed.gpu.global.add.f32 [%0], %2;\nred.relaxed.gpu.global.add.f32 [%0 + 256], %3;\nred.relaxed.gpu.global.add.f32 [%1], %4;"
                         :: "l"(red_p), "l"(red2_p), "f"(r0), "f"(r1), "f"(r2) : "memory");
            asm volatile("red.relaxed.gpu.global.add.f32 [%0], %2;\nred.relaxed.gpu.global.add.f32 [%0 + 256], %3;\nred.relaxed.gpu.global.add.f32 [%1], %4;"
                         :: "l"(red_p ^ 4096), "l"(red2_p ^ 4096), "f"(r0), "f"(r1), "f"(r2) : "memory");
        }
    }

    constexpr uint32_t CNT = 0x42000000u;
    if (is_gu) {
        uint32_t side;
        asm volatile("ld.volatile.shared.u32 %0, [%1];" : "=r"(side) : "r"(sb + SM_SIDE) : "memory");
        u64 acc_p = (s_line(e1_blk(0, w), lane >> 3) + (lane & 7) * 16) ^ side, acc2_p = (s_line(e1_blk(0, w), 4 + ob) + (lane & 7) * 16) ^ side;
        const int eb = e1_blk(w >> 2, w & 3);
        const bool near = __all_sync(~0u, (w >> 2) * 4096 == side);
        u64 out_p = s_line(eb, lane >> 3) + S_OUT + (lane & 7) * 16, out2_p = s_line(eb, 4 + ob) + S_OUT + (lane & 15) * 8;
        u64 gb_p = (s_line(e1_blk(0, w), 6 + ob) + (lane & 15) * 8) ^ side, y_p = (u64)(q_.out + t1 * D_ + 64 * w + 4 * t2 + g);
        PIN64(acc_p); PIN64(acc2_p); PIN64(out_p); PIN64(out2_p); PIN64(gb_p); PIN64(y_p);
        auto keep = [&](uint32_t x) { return __shfl_sync(~0u, x, lane); };
        const int src = keep(8 * (g & 2) + t), src1 = keep(src + 4), src2 = keep(src + 8), src3 = keep(src + 12);
        const uint32_t p_st = keep(sb + SM_PART + w * 512 + lane * 16), r_st = keep(sb + SM_RED + (vb * 8 + w) * 8);
        tx0 = keep(tx0); tx1 = keep(tx1);
        uint32_t w2a[4];
#pragma unroll
        for (int i = 0; i < 4; i++) w2a[i] = keep(sb + slot_addr(N_FFN + 4) + w * 4096 + (sw128 ^ (i * 32)));
        const uint32_t hva = keep(sb + SM_Q + ((g & 2) * 2 + t) * 16), w2b = keep(sb + BAR_W2 + 8 * (w * NW >> 3)), t2k = keep(t2);
        const uint32_t g1 = g & 1;
        uint32_t cp[8], cn[8];
        float acc[4][4];
#pragma unroll
        for (int i = 0; i < 8; i++) {
            cp[i] = __shfl_sync(~0u, (i & 1) ? cb1 : cb0, 4 * (i >> 1) + src);
            cn[i] = selu(g1, __shfl_sync(~0u, (i & 1) ? sb1 : sb0, 4 * (i >> 1) + src), cp[i]);
        }
        const int frow = (lane & 7) + (lane & 16);
        const uint32_t fa = sb + slot_addr(N_FFN) + grp * 2 * TILE_BYTES + (64 * sub + frow) * 64 + ((lch ^ ((frow >> 1) & 3)) << 4);
        mbar_wait(sb + BAR_FFN + 8 * (w * NQ >> 3), 0);
        uint4 u = ld_strong128(acc_p), v = ld_strong128(acc2_p);
#pragma unroll
        for (int i = 0; i < 16; i++) ldsm4t((fa ^ ((i & 1) * 32)) + (i >> 3) * 2048 + ((i >> 2) & 1) * 512 + ((i >> 1) & 1) * TILE_BYTES, A[i]);
#pragma unroll
        for (int i = 0; i < 4; i++) { acc[i][0] = acc[i][1] = acc[i][2] = acc[i][3] = 0.f; }
#pragma unroll
        for (int i = 0; i < 16; i++)
            mma4(acc[i & 3], A[i], cn[2 * (i >> 2)], cn[2 * (i >> 2) + 1]);
        sts128f(sb + SM_P + w * 1024 + lane * 16, sel(t2, acc[1][0], acc[0][0]), sel(t2, acc[3][0], acc[2][0]), sel(t2, acc[1][2], acc[0][2]), sel(t2, acc[3][2], acc[2][2]));
        sts128f(sb + SM_P + w * 1024 + 512 + lane * 16, sel(t2, acc[1][1], acc[0][1]), sel(t2, acc[3][1], acc[2][1]), sel(t2, acc[1][3], acc[0][3]), sel(t2, acc[3][3], acc[2][3]));
        bar_arrive<3>();
#pragma unroll
        for (int i = 0; i < 8; i++) cn[i] = selu(g1, cp[i] ^ 0x80008000u, 0u);
        settle(tag, sb + SM_OP, cn[0], cn[1], cn[2], cn[3]); settle(tag, sb + SM_OP, cn[4], cn[5], cn[6], cn[7]);
        for (uint32_t n = 0; !__all_sync(~0u, u.w == CNT && v.w == CNT) && n < SPIN_LIMIT; n++) { u = ld_strong128(acc_p); v = ld_strong128(acc2_p); }
        const uint32_t x0 = hadd2(tx0, hmul2(ga0, pack2(__uint_as_float(u.x), __uint_as_float(u.y))));
        const uint32_t x1 = hadd2(tx1, hmul2(ga1, pack2(__uint_as_float(u.z), __uint_as_float(selu(lane & 8, v.y, v.x)))));
        float c[4] = {0.f, 0.f, 0.f, 0.f};
        mma(c, x0, ONE2, x1, ONE2, x0, x1);
#pragma unroll
        for (int i = 0; i < 4; i++) { acc[i][0] = acc[i][1] = acc[i][2] = acc[i][3] = 0.f; }
        float q, s;
#pragma unroll
        for (int s4 = 0; s4 < 4; s4++) {
            const int from = s4 == 0 ? src : s4 == 1 ? src1 : s4 == 2 ? src2 : src3;
            uint32_t b0 = __shfl_sync(~0u, x0, from), b1 = __shfl_sync(~0u, x1, from);
            b0 = hfma2(b0, cp[2 * s4], hmul2(b0, cn[2 * s4]));
            b1 = hfma2(b1, cp[2 * s4 + 1], hmul2(b1, cn[2 * s4 + 1]));
#pragma unroll
            for (int i = 0; i < 4; i++) mma4(acc[i], A[4 * s4 + i], b0, b1);
            if (s4 == 0) { q = sel(g1, c[1], c[0]); s = c[2] + c[3]; q += __shfl_xor_sync(~0u, q, 4); s += __shfl_xor_sync(~0u, s, 9); }
            if (s4 == 1) q += __shfl_xor_sync(~0u, q, 9);
            if (s4 == 2) { if (lane == 0 || lane == 18) sts64f(r_st, s, fmaxf(fmaf(s * (-1.0f / 64), s, q), 0.f)); }
        }
        sts128f(p_st, sel(t2, acc[1][0] + acc[1][1], acc[0][0] + acc[0][1]), sel(t2, acc[3][0] + acc[3][1], acc[2][0] + acc[2][1]),
                sel(t2, acc[1][2] + acc[1][3], acc[0][2] + acc[0][3]), sel(t2, acc[3][2] + acc[3][3], acc[2][2] + acc[2][3]));
        bar_arrive<4>();
        auto w2_frags = [&]() {
            mbar_wait(w2b, 0);
#pragma unroll
            for (int i = 0; i < 8; i++) ldsm4t(w2a[i & 3] + (i >> 2) * 2048, A[i]);
        };
        if (!near) w2_frags();
#pragma unroll
        for (int i = 0; i < 4; i++) { acc[i][0] = acc[i][1] = acc[i][2] = acc[i][3] = 0.f; }
        bar_sync<5>();
        const uint4 hv = lds128(hva);
        if (near) w2_frags();
#pragma unroll
        for (int i = 0; i < 4; i++) mma4(acc[i], A[i], hv.x, hv.y);
#pragma unroll
        for (int i = 0; i < 4; i++) mma4(acc[i], A[4 + i], hv.z, hv.w);
        float r[4], o[6];
#pragma unroll
        for (int i = 0; i < 4; i++) r[i] = sel(t2k, acc[i][2], acc[i][0]);
        asm volatile("atom.relaxed.gpu.global.add.v4.f32 {%0, %1, %2, %3}, [%4], {%5, %6, %7, %8};"
                     : "=f"(o[0]), "=f"(o[1]), "=f"(o[2]), "=f"(o[4]) : "l"(out_p), "f"(r[0]), "f"(r[1]), "f"(r[2]), "f"(1.0f) : "memory");
        asm volatile("atom.relaxed.gpu.global.add.v2.f32 {%0, %1}, [%2], {%3, %4};"
                     : "=f"(o[3]), "=f"(o[5]) : "l"(out2_p), "f"(r[3]), "f"(1.0f) : "memory");
        uint2 gb = ld_strong64(gb_p);
        uint32_t xo[2];
#pragma unroll
        for (int j = 0; j < 2; j++) {
            const uint32_t e0 = __shfl_sync(~0u, x0, 16 * t1 + 8 * j + g), e1 = __shfl_sync(~0u, x1, 16 * t1 + 8 * j + g);
            xo[j] = __byte_perm(e0, e1, t2 ? 0x7632 : 0x5410);
        }
        const uint32_t f0 = pack2(o[0] + r[0], o[1] + r[1]), f1 = pack2(o[2] + r[2], o[3] + r[3]);
#pragma unroll 1
        for (uint32_t n = 0; n < SPIN_LIMIT; n++) {
            const uint32_t y0 = hadd2(xo[0], hmul2(gb.x, f0)), y1 = hadd2(xo[1], hmul2(gb.y, f1));
            uint32_t late;
            asm volatile("{\n.reg .pred p, q, m;\n.reg .b16 a, b, c, d;\n"
                         "mov.b32 {a, b}, %6;\nmov.b32 {c, d}, %7;\nsetp.ne.b16 m, a, 0xffff;\nsetp.ne.and.b16 m, b, 0xffff, m;\nsetp.ne.and.b16 m, c, 0xffff, m;\nsetp.ne.and.b16 m, d, 0xffff, m;\n"
                         "setp.eq.and.f32 p, %4, 0f42280000, m;\nsetp.eq.and.f32 q, %5, 0f42280000, m;\n"
                         "mov.b32 {a, b}, %2;\nmov.b32 {c, d}, %3;\n"
                         "@p st.global.u16 [%1], a;\n@p st.global.u16 [%1 + 32], b;\n@p st.global.u16 [%1 + 64], c;\n@q st.global.u16 [%1 + 96], d;\n"
                         "vote.sync.all.pred m, m, 0xffffffff;\nselp.u32 %0, 0, 1, m;\n}"
                         : "=r"(late) : "l"(y_p), "r"(y0), "r"(y1), "f"(o[4]), "f"(o[5]), "r"(gb.x), "r"(gb.y) : "memory");
            if (!late) break;
            gb = ld_strong64(gb_p);
        }
    } else if (is_gb) {
        const uint32_t fa = sb + slot_addr(N_FFN) + grp * 8192 + (64 * sub + lrow) * 32 + ((lch ^ ((lrow >> 2) & 1)) << 4);
        const int dl = (lane & 7) * 4 + ((lane >> 3) & 1) * 2 + ob;
        u64 gb_p = s_line(2 * (role >> 2), 6 + (dl >> 4)) + (dl & 15) * 8 + (role & 3) * 2;
        PIN64(gb_p);
        uint32_t bs[8];
#pragma unroll
        for (int i = 0; i < 8; i++) bs[i] = __shfl_sync(~0u, (i & 1) ? sc1 : sc0, 4 * (i >> 1) + 16 * ((g >> 1) & 1) + t);
        const uint32_t c_st = sb + SM_PART + (w * 32 + t1 * 16 + (t >> 1) * 8 + g) * 4;
        settle(tag, sb + SM_OP, bs[0], bs[1], bs[2], bs[3]); settle(tag, sb + SM_OP, bs[4], bs[5], bs[6], bs[7]); settle(tag, sb + SM_OP, c_st, fa, 0, 0);
        mbar_wait(sb + BAR_FFN + 8 * grp, 0);
        float c[4][4];
#pragma unroll
        for (int s4 = 0; s4 < 4; s4++) ldsm4t(fa + s4 * 512, A[s4]);
#pragma unroll
        for (int s4 = 0; s4 < 4; s4++) { c[s4][0] = c[s4][1] = c[s4][2] = c[s4][3] = 0.f; mma4(c[s4], A[s4], bs[2 * s4], bs[2 * s4 + 1]); }
        sts32f(c_st, sel(t2, (c[0][2] + c[1][2]) + (c[2][2] + c[3][2]), (c[0][0] + c[1][0]) + (c[2][0] + c[3][0])));
        cbar();
        if (w == 0) {
            float u[8];
#pragma unroll
            for (int i = 0; i < 8; i++) u[i] = lds32f(sb + SM_PART + i * 128 + lane * 4);
            const uint16_t v = (uint16_t)pack2(((u[0] + u[1]) + (u[2] + u[3])) + ((u[4] + u[5]) + (u[6] + u[7])), 0.f);
            asm volatile("st.relaxed.gpu.global.u16 [%0], %1;\nst.relaxed.gpu.global.u16 [%0 + 4096], %1;" :: "l"(gb_p), "h"(v) : "memory");
        }
    }
}

typedef CUresult (*EncodeFn)(CUtensorMap*, CUtensorMapDataType, cuuint32_t, void*, const cuuint64_t*, const cuuint64_t*,
                             const cuuint32_t*, const cuuint32_t*, CUtensorMapInterleave, CUtensorMapSwizzle,
                             CUtensorMapL2promotion, CUtensorMapFloatOOBfill);

void make_map(EncodeFn enc, CUtensorMap* m, void* ptr, int cols, int rows, int box_cols, int box_rows, CUtensorMapSwizzle sw) {
    cuuint64_t gd[2] = {(cuuint64_t)cols, (cuuint64_t)rows}, gs[1] = {(cuuint64_t)cols * 2};
    cuuint32_t bd[2] = {(cuuint32_t)box_cols, (cuuint32_t)box_rows}, es[2] = {1, 1};
    enc(m, CU_TENSOR_MAP_DATA_TYPE_BFLOAT16, 2, ptr, gd, gs, bd, es, CU_TENSOR_MAP_INTERLEAVE_NONE, sw,
        CU_TENSOR_MAP_L2_PROMOTION_NONE, CU_TENSOR_MAP_FLOAT_OOB_FILL_NONE);
}

}

extern "C" void kernel_launch(void* const* d_in, const int* in_sizes, int n_in, void* d_out, int out_size) {
    (void)in_sizes; (void)n_in; (void)out_size;
    static EncodeFn enc = nullptr;
    if (!enc) {
        void* fn = nullptr;
        cudaDriverEntryPointQueryResult qr;
        cudaGetDriverEntryPoint("cuTensorMapEncodeTiled", &fn, cudaEnableDefault, &qr);
        enc = (EncodeFn)fn;
        cudaFuncSetAttribute(fused_decode_kernel, cudaFuncAttributeMaxDynamicSharedMemorySize, SMEM_BYTES);
    }
    Params p;
    Ptrs q;
    make_map(enc, &p.m_wmod, d_in[10], MODW, D_, 32, 256, CU_TENSOR_MAP_SWIZZLE_64B);
    make_map(enc, &p.m_wq, d_in[3], QD, D_, 64, 128, CU_TENSOR_MAP_SWIZZLE_128B);
    make_map(enc, &p.m_v, d_in[2], DH, 64 * SK, 64, 128, CU_TENSOR_MAP_SWIZZLE_128B);
    {
        cuuint64_t gd[3] = {64, QD, 8}, gs[2] = {D_ * 2, 128};
        cuuint32_t bd[3] = {64, 32, 4}, es[3] = {1, 1, 1};
        enc(&p.m_wo, CU_TENSOR_MAP_DATA_TYPE_BFLOAT16, 3, d_in[4], gd, gs, bd, es, CU_TENSOR_MAP_INTERLEAVE_NONE,
            CU_TENSOR_MAP_SWIZZLE_128B, CU_TENSOR_MAP_L2_PROMOTION_NONE, CU_TENSOR_MAP_FLOAT_OOB_FILL_NONE);
    }
    for (int i = 0; i < 2; i++) {
        cuuint64_t gd[4] = {FF, 2, 8, D_ / 16}, gs[3] = {8 * FF * 2, FF * 2, 16 * FF * 2};
        cuuint32_t bd[4] = {32, 2, 8, 32 / NQ}, es[4] = {1, 1, 1, 1};
        enc(i ? &p.m_w3 : &p.m_w1, CU_TENSOR_MAP_DATA_TYPE_BFLOAT16, 4, d_in[6 + i], gd, gs, bd, es, CU_TENSOR_MAP_INTERLEAVE_NONE,
            CU_TENSOR_MAP_SWIZZLE_64B, CU_TENSOR_MAP_L2_PROMOTION_NONE, CU_TENSOR_MAP_FLOAT_OOB_FILL_NONE);
    }
    {
        cuuint64_t gd[5] = {64, 2, 8, FF / 16, 8}, gs[4] = {8 * D_ * 2, D_ * 2, 16 * D_ * 2, 128};
        cuuint32_t bd[5] = {64, 2, 8, 2, 8 / NW}, es[5] = {1, 1, 1, 1, 1};
        enc(&p.m_w2, CU_TENSOR_MAP_DATA_TYPE_BFLOAT16, 5, d_in[8], gd, gs, bd, es, CU_TENSOR_MAP_INTERLEAVE_NONE,
            CU_TENSOR_MAP_SWIZZLE_128B, CU_TENSOR_MAP_L2_PROMOTION_NONE, CU_TENSOR_MAP_FLOAT_OOB_FILL_NONE);
    }
    make_map(enc, &p.m_gb, d_in[10], MODW, D_, 16, 256, CU_TENSOR_MAP_SWIZZLE_32B);
    q.x = (const __nv_bfloat16*)d_in[0];
    q.kwin = (const __nv_bfloat16*)d_in[1] + (size_t)(SK - WIN) * DH;
    q.c = (const __nv_bfloat16*)d_in[9];
    q.out = (__nv_bfloat16*)d_out;
    fused_decode_kernel<<<NCTA, THREADS, SMEM_BYTES, cudaStreamPerThread>>>(q, p);
}
```

```cpp
#include <cuda_runtime.h>
#include <cuda.h>
#include <cuda_bf16.h>
#include <stdint.h>

namespace {

constexpr int D_ = 512, DH = 128, SK = 16384, WIN = 4096, FF = 1376, QD = 4096, MODW = 3072;
constexpr int NCTA = 128;
constexpr int TILE_BYTES = 16384;
constexpr int NT = 32;
constexpr int STAGES = 13;
constexpr int K_FIRST = 2;
constexpr int FIRST_N = 5;
constexpr int MEET_AT = 16;
constexpr int PACE = 656;
constexpr int LEAD_NS = 1295;
constexpr int GATE_X = 25;
constexpr int POLL_NS = 300;
constexpr int ALPHA16 = 4;
constexpr int GU_NS = 4660;
constexpr int W2_NS = 5875;
constexpr int GB_LEAD = 380;
constexpr int NQ = 8;
constexpr int PROBES = 6;
constexpr int PROBE_NS = 1000;
constexpr int EARLY_NS = 800;
constexpr int NW = 4;
constexpr int HEAD_TID = 256;
constexpr int N_WMOD = 0, N_WQ = 2, N_K = 6, N_V = N_K + NT, N_WO = N_V + NT, N_FFN = N_WO + 4;
constexpr int N_GATE = N_V + GATE_X;
constexpr int THREADS = 320;
constexpr int N_MOD_CTA = 80;
#define SPIN_LIMIT_S "4194304"
constexpr unsigned SPIN_LIMIT = 1u << 22;

constexpr int SM_RING = 0;
constexpr int SM_P = STAGES * TILE_BYTES;
constexpr int SM_PART = SM_P + WIN * 2;
constexpr int SM_OP = SM_PART + 8192;
constexpr int SM_Q = SM_OP + 2048;
constexpr int SM_RED = SM_Q + 256;
constexpr int SM_ML = SM_RED + 128;
constexpr int SM_PROG = SM_ML + 16;
constexpr int SM_SIDE = SM_PROG + 16;
constexpr int SM_BAR = SM_SIDE + 16;
constexpr int BAR_FULL = SM_BAR, BAR_EMPTY = SM_BAR + 8 * STAGES, BAR_XQ = SM_BAR + 16 * STAGES,
              BAR_XML = BAR_XQ + 8, BAR_XP = BAR_XQ + 16, BAR_XO = BAR_XQ + 24, BAR_FFN = BAR_XQ + 32;
constexpr int BAR_W2 = BAR_FFN + 8 * NQ;
constexpr int SMEM_BYTES = BAR_W2 + 8 * NW;
static_assert(SMEM_BYTES <= 232448, "shared memory");
__host__ __device__ constexpr uint32_t slot_addr(int n) { return SM_RING + (n % STAGES) * TILE_BYTES; }
__host__ __device__ constexpr uint32_t full_bar(int n) { return BAR_FULL + 8 * (n % STAGES); }
__host__ __device__ constexpr uint32_t empty_bar(int n) { return BAR_EMPTY + 8 * (n % STAGES); }
__host__ __device__ constexpr uint32_t tile_phase(int n) { return (n / STAGES) & 1; }
static_assert((N_FFN + 4) % STAGES + 2 <= STAGES && N_FFN % STAGES + 4 <= STAGES, "w1/w3 tiles and w2 tiles occupy consecutive slots");
static_assert(GATE_X >= MEET_AT && N_GATE - STAGES < N_V + MEET_AT && N_FFN + 5 - 2 * STAGES < N_V + MEET_AT && N_FFN + 5 - STAGES < N_WO,
              "barrier parities the helper warp waits on are unambiguous after the rendezvous; the wo tiles are not replaced");
__host__ __device__ constexpr int fill_tile(int j) { return j < K_FIRST ? N_K + j : j < K_FIRST + N_K ? j - K_FIRST : j; }

struct Ptrs {
    const __nv_bfloat16 *kwin, *x, *c;
    __nv_bfloat16* out;
};
struct Params {
    CUtensorMap m_wmod, m_wq, m_v, m_wo, m_w1, m_w3, m_w2, m_gb;
};

__device__ unsigned g_epoch;
__device__ __align__(128) uint2 g_mod[2][5 * D_ / 2];
__device__ __align__(256) unsigned char g_s[131072];
__device__ __forceinline__ unsigned long long s_line(int blk, int i) {
    return (((unsigned long long)g_s + 65535) & ~65535ull) + blk * 4096 + (i >> 1) * 1024 + (i & 1) * 256;
}
__device__ __forceinline__ int e1_blk(int r, int w) { return 2 * w + (r ^ (w & 1)); }
constexpr int S_OUT = 512, S_PROG = 128;
__device__ __align__(128) unsigned g_clear;

typedef unsigned long long u64;
__device__ __forceinline__ unsigned time_ns() {
    unsigned r;
    asm volatile("mov.u32 %0, %%globaltimer_lo;" : "=r"(r));
    return r;
}
__device__ __forceinline__ bool elect_one() {
    uint32_t r;
    asm volatile("{\n.reg .pred p;\nelect.sync _|p, 0xffffffff;\nselp.u32 %0, 1, 0, p;\n}" : "=r"(r));
    return r != 0;
}
#define PIN64(v) asm volatile("" : "+l"(v))

__device__ __forceinline__ void mbar_init(uint32_t bar, uint32_t cnt) {
    asm volatile("mbarrier.init.shared::cta.b64 [%0], %1;" :: "r"(bar), "r"(cnt) : "memory");
}
__device__ __forceinline__ void mbar_expect_tx(uint32_t bar, uint32_t bytes) {
    asm volatile("mbarrier.arrive.expect_tx.shared::cta.b64 _, [%0], %1;" :: "r"(bar), "r"(bytes) : "memory");
}
__device__ __forceinline__ void mbar_arrive(uint32_t bar) {
    asm volatile("mbarrier.arrive.shared::cta.b64 _, [%0];" :: "r"(bar) : "memory");
}
__device__ __forceinline__ void mbar_arrive_n(uint32_t bar, uint32_t n) {
    asm volatile("mbarrier.arrive.shared::cta.b64 _, [%0], %1;" :: "r"(bar), "r"(n) : "memory");
}
__device__ __forceinline__ void mbar_wait(uint32_t bar, uint32_t parity) {
    asm volatile("{\n.reg .pred p;\n.reg .u32 n;\nmov.u32 n, 0;\nW0:\n"
                 "mbarrier.try_wait.parity.shared::cta.b64 p, [%0], %1;\n@p bra W1;\n"
                 "add.u32 n, n, 1;\nsetp.lt.u32 p, n, " SPIN_LIMIT_S ";\n@p bra W0;\nW1:\n}"
                 :: "r"(bar), "r"(parity) : "memory");
}
__device__ __forceinline__ void mbar_wait_cluster(uint32_t bar, uint32_t parity) {
    asm volatile("{\n.reg .pred p;\n.reg .u32 n;\nmov.u32 n, 0;\nW0:\n"
                 "mbarrier.try_wait.parity.acquire.cluster.shared::cta.b64 p, [%0], %1;\n@p bra W1;\n"
                 "add.u32 n, n, 1;\nsetp.lt.u32 p, n, " SPIN_LIMIT_S ";\n@p bra W0;\nW1:\n}"
                 :: "r"(bar), "r"(parity) : "memory");
}
__device__ __forceinline__ void bulk_load(uint32_t dst, const void* src, uint32_t bytes, uint32_t bar, uint64_t pol) {
    asm volatile("cp.async.bulk.shared::cluster.global.mbarrier::complete_tx::bytes.L2::cache_hint [%0], [%1], %2, [%3], %4;"
                 :: "r"(dst), "l"(src), "r"(bytes), "r"(bar), "l"(pol) : "memory");
}
__device__ __forceinline__ void tma2d(uint32_t dst, const CUtensorMap* m, int c0, int c1, uint32_t bar) {
    asm volatile("cp.async.bulk.tensor.2d.shared::cluster.global.mbarrier::complete_tx::bytes [%0], [%1, {%3, %4}], [%2];"
                 :: "r"(dst), "l"(m), "r"(bar), "r"(c0), "r"(c1) : "memory");
}
__device__ __forceinline__ void tma2d_hint(uint32_t dst, const CUtensorMap* m, int c0, int c1, uint32_t bar, uint64_t pol) {
    asm volatile("cp.async.bulk.tensor.2d.shared::cluster.global.mbarrier::complete_tx::bytes.L2::cache_hint [%0], [%1, {%3, %4}], [%2], %5;"
                 :: "r"(dst), "l"(m), "r"(bar), "r"(c0), "r"(c1), "l"(pol) : "memory");
}
__device__ __forceinline__ void tma3d(uint32_t dst, const CUtensorMap* m, int c0, int c1, int c2, uint32_t bar) {
    asm volatile("cp.async.bulk.tensor.3d.shared::cluster.global.mbarrier::complete_tx::bytes [%0], [%1, {%3, %4, %5}], [%2];"
                 :: "r"(dst), "l"(m), "r"(bar), "r"(c0), "r"(c1), "r"(c2) : "memory");
}
__device__ __forceinline__ void tma4d(uint32_t dst, const CUtensorMap* m, int c0, int c3, uint32_t bar) {
    asm volatile("cp.async.bulk.tensor.4d.shared::cluster.global.mbarrier::complete_tx::bytes [%0], [%1, {%3, %5, %5, %4}], [%2];"
                 :: "r"(dst), "l"(m), "r"(bar), "r"(c0), "r"(c3), "r"(0) : "memory");
}
__device__ __forceinline__ void tma5d(uint32_t dst, const CUtensorMap* m, int c3, int c4, uint32_t bar) {
    asm volatile("cp.async.bulk.tensor.5d.shared::cluster.global.mbarrier::complete_tx::bytes [%0], [%1, {%5, %5, %5, %3, %4}], [%2];"
                 :: "r"(dst), "l"(m), "r"(bar), "r"(c3), "r"(c4), "r"(0) : "memory");
}
__device__ __forceinline__ uint32_t mapa(uint32_t addr, uint32_t rank) {
    uint32_t r;
    asm("mapa.shared::cluster.u32 %0, %1, %2;" : "=r"(r) : "r"(addr), "r"(rank));
    return r;
}
__device__ __forceinline__ void st_async_b32(uint32_t addr, uint32_t v, uint32_t bar) {
    asm volatile("st.async.weak.shared::cluster.mbarrier::complete_tx::bytes.b32 [%0], %1, [%2];" :: "r"(addr), "r"(v), "r"(bar) : "memory");
}
__device__ __forceinline__ void st_async_v2(uint32_t addr, float a, float b, uint32_t bar) {
    asm volatile("st.async.weak.shared::cluster.mbarrier::complete_tx::bytes.v2.f32 [%0], {%1, %2}, [%3];" :: "r"(addr), "f"(a), "f"(b), "r"(bar) : "memory");
}
__device__ __forceinline__ void st_async_v4(uint32_t addr, uint32_t a, uint32_t b, uint32_t c, uint32_t d, uint32_t bar) {
    asm volatile("st.async.weak.shared::cluster.mbarrier::complete_tx::bytes.v4.b32 [%0], {%1, %2, %3, %4}, [%5];"
                 :: "r"(addr), "r"(a), "r"(b), "r"(c), "r"(d), "r"(bar) : "memory");
}
template <int ID> __device__ __forceinline__ void bar_sync() { asm volatile("bar.sync %0, 288;" :: "n"(ID) : "memory"); }
template <int ID> __device__ __forceinline__ void bar_arrive() { asm volatile("bar.arrive %0, 288;" :: "n"(ID) : "memory"); }
__device__ __forceinline__ void cbar() { asm volatile("bar.sync 1, 256;" ::: "memory"); }

__device__ __forceinline__ uint4 ldg128(const void* p) {
    uint4 v;
    asm volatile("ld.global.nc.v4.u32 {%0,%1,%2,%3}, [%4];" : "=r"(v.x), "=r"(v.y), "=r"(v.z), "=r"(v.w) : "l"(p));
    return v;
}
__device__ __forceinline__ uint32_t ldg16(const void* p) {
    uint16_t v;
    asm volatile("ld.global.nc.u16 %0, [%1];" : "=h"(v) : "l"(p));
    return v;
}
__device__ __forceinline__ uint4 ld_strong128(unsigned long long p) {
    uint4 v;
    asm volatile("ld.relaxed.gpu.global.v4.b32 {%0,%1,%2,%3}, [%4];" : "=r"(v.x), "=r"(v.y), "=r"(v.z), "=r"(v.w) : "l"(p) : "memory");
    return v;
}
__device__ __forceinline__ uint2 ld_strong64(unsigned long long p) {
    uint2 v;
    asm volatile("ld.relaxed.gpu.global.v2.b32 {%0,%1}, [%2];" : "=r"(v.x), "=r"(v.y) : "l"(p) : "memory");
    return v;
}
__device__ __forceinline__ uint32_t ldg32(const void* p) {
    uint32_t v;
    asm volatile("ld.global.nc.u32 %0, [%1];" : "=r"(v) : "l"(p));
    return v;
}
struct Pkt2 { u64 a, b; };
__device__ __forceinline__ uint32_t lo32(u64 v) { return (uint32_t)v; }
__device__ __forceinline__ uint32_t hi32(u64 v) { return (uint32_t)(v >> 32); }
__device__ __forceinline__ Pkt2 ld_pkt2(const void* p) {
    Pkt2 r;
    asm volatile("ld.relaxed.gpu.global.v2.b64 {%0,%1}, [%2];" : "=l"(r.a), "=l"(r.b) : "l"(p) : "memory");
    return r;
}
__device__ __forceinline__ bool pkt_ok(const Pkt2& r, uint32_t tag) { return hi32(r.a) == tag && hi32(r.b) == tag; }
__device__ __forceinline__ void st_pkt(u64 p, uint32_t data, uint32_t tag) {
    asm volatile("{\n.reg .b64 v;\nmov.b64 v, {%1, %2};\nst.relaxed.gpu.global.b64 [%0], v;\n}" :: "l"(p), "r"(data), "r"(tag) : "memory");
}
__device__ __forceinline__ uint4 lds128(uint32_t a) {
    uint4 v;
    asm volatile("ld.shared.v4.u32 {%0,%1,%2,%3}, [%4];" : "=r"(v.x), "=r"(v.y), "=r"(v.z), "=r"(v.w) : "r"(a) : "memory");
    return v;
}
__device__ __forceinline__ float4 lds128f(uint32_t a) {
    float4 v;
    asm volatile("ld.shared.v4.f32 {%0,%1,%2,%3}, [%4];" : "=f"(v.x), "=f"(v.y), "=f"(v.z), "=f"(v.w) : "r"(a) : "memory");
    return v;
}
__device__ __forceinline__ uint2 lds64(uint32_t a) {
    uint2 v;
    asm volatile("ld.shared.v2.u32 {%0,%1}, [%2];" : "=r"(v.x), "=r"(v.y) : "r"(a) : "memory");
    return v;
}
__device__ __forceinline__ float2 lds64f(uint32_t a) {
    float2 v;
    asm volatile("ld.shared.v2.f32 {%0,%1}, [%2];" : "=f"(v.x), "=f"(v.y) : "r"(a) : "memory");
    return v;
}
__device__ __forceinline__ float lds32f(uint32_t a) {
    float v;
    asm volatile("ld.shared.f32 %0, [%1];" : "=f"(v) : "r"(a) : "memory");
    return v;
}
__device__ __forceinline__ void sts64f(uint32_t a, float x, float y) {
    asm volatile("st.shared.v2.f32 [%0], {%1,%2};" :: "r"(a), "f"(x), "f"(y) : "memory");
}
__device__ __forceinline__ void sts128f(uint32_t a, float x, float y, float z, float w) {
    asm volatile("st.shared.v4.f32 [%0], {%1,%2,%3,%4};" :: "r"(a), "f"(x), "f"(y), "f"(z), "f"(w) : "memory");
}
__device__ __forceinline__ void sts32f(uint32_t a, float x) {
    asm volatile("st.shared.f32 [%0], %1;" :: "r"(a), "f"(x) : "memory");
}
__device__ __forceinline__ void sts128(uint32_t a, uint32_t x, uint32_t y, uint32_t z, uint32_t w) {
    asm volatile("st.shared.v4.u32 [%0], {%1,%2,%3,%4};" :: "r"(a), "r"(x), "r"(y), "r"(z), "r"(w) : "memory");
}
__device__ __forceinline__ void settle(uint32_t tag, uint32_t a, uint32_t x, uint32_t y, uint32_t z, uint32_t w) {
    asm volatile("{\n.reg .pred p;\nsetp.eq.u32 p, %0, 0;\n@p st.shared.v4.u32 [%1], {%2,%3,%4,%5};\n}" :: "r"(tag), "r"(a), "r"(x), "r"(y), "r"(z), "r"(w) : "memory");
}
__device__ __forceinline__ void settle(uint32_t tag, uint32_t a, const float4& v) {
    settle(tag, a, __float_as_uint(v.x), __float_as_uint(v.y), __float_as_uint(v.z), __float_as_uint(v.w));
}
__device__ __forceinline__ void sts16(uint32_t a, uint32_t x) {
    asm volatile("st.shared.u16 [%0], %1;" :: "r"(a), "h"((uint16_t)x) : "memory");
}
__device__ __forceinline__ void ldsm4t(uint32_t a, uint32_t (&r)[4]) {
    asm volatile("ldmatrix.sync.aligned.m8n8.x4.trans.shared.b16 {%0,%1,%2,%3}, [%4];"
                 : "=r"(r[0]), "=r"(r[1]), "=r"(r[2]), "=r"(r[3]) : "r"(a) : "memory");
}
__device__ __forceinline__ void mma(float (&c)[4], uint32_t a0, uint32_t a1, uint32_t a2, uint32_t a3, uint32_t b0, uint32_t b1) {
    asm volatile("mma.sync.aligned.m16n8k16.row.col.f32.bf16.bf16.f32 {%0,%1,%2,%3}, {%4,%5,%6,%7}, {%8,%9}, {%0,%1,%2,%3};"
                 : "+f"(c[0]), "+f"(c[1]), "+f"(c[2]), "+f"(c[3]) : "r"(a0), "r"(a1), "r"(a2), "r"(a3), "r"(b0), "r"(b1));
}
__device__ __forceinline__ void mma4(float (&c)[4], const uint32_t (&a)[4], uint32_t b0, uint32_t b1) { mma(c, a[0], a[1], a[2], a[3], b0, b1); }
__device__ __forceinline__ float sel(uint32_t c, float a, float b) {
    float r;
    asm("{\n.reg .pred p;\nsetp.ne.u32 p, %3, 0;\nselp.f32 %0, %1, %2, p;\n}" : "=f"(r) : "f"(a), "f"(b), "r"(c));
    return r;
}
__device__ __forceinline__ float bf_lo(uint32_t v) { return __uint_as_float(v << 16); }
__device__ __forceinline__ float bf_hi(uint32_t v) { return __uint_as_float(v & 0xffff0000u); }
__device__ __forceinline__ uint32_t pack2(float lo, float hi) {
    uint32_t r;
    asm("cvt.rn.bf16x2.f32 %0, %1, %2;" : "=r"(r) : "f"(hi), "f"(lo));
    return r;
}
__device__ __forceinline__ float rbf(float x) { return __uint_as_float(pack2(0.f, x)); }
__device__ __forceinline__ uint32_t hadd2(uint32_t a, uint32_t b) { uint32_t r; asm("add.rn.bf16x2 %0, %1, %2;" : "=r"(r) : "r"(a), "r"(b)); return r; }
__device__ __forceinline__ uint32_t hsub2(uint32_t a, uint32_t b) { uint32_t r; asm("sub.rn.bf16x2 %0, %1, %2;" : "=r"(r) : "r"(a), "r"(b)); return r; }
__device__ __forceinline__ uint32_t hmul2(uint32_t a, uint32_t b) { uint32_t r; asm("mul.rn.bf16x2 %0, %1, %2;" : "=r"(r) : "r"(a), "r"(b)); return r; }
__device__ __forceinline__ uint32_t hfma2(uint32_t a, uint32_t b, uint32_t c) { uint32_t r; asm("fma.rn.bf16x2 %0, %1, %2, %3;" : "=r"(r) : "r"(a), "r"(b), "r"(c)); return r; }
__device__ __forceinline__ uint32_t selu(uint32_t c, uint32_t a, uint32_t b) { return __float_as_uint(sel(c, __uint_as_float(a), __uint_as_float(b))); }
constexpr uint32_t ONE2 = 0x3f803f80u;
__device__ __forceinline__ float sigmoid_f(float x) {
    float e, r;
    asm("ex2.approx.ftz.f32 %0, %1;" : "=f"(e) : "f"(x * -1.4426950408889634f));
    asm("rcp.approx.ftz.f32 %0, %1;" : "=f"(r) : "f"(1.0f + e));
    return r;
}
__device__ __forceinline__ float silu_f(float x) { return x * sigmoid_f(x); }
__device__ __forceinline__ float rcp_sd(float m2) {
    float s, r;
    asm("sqrt.approx.ftz.f32 %0, %1;" : "=f"(s) : "f"(rbf(rbf(m2 * (1.0f / D_)) + 1e-5f)));
    asm("rcp.approx.ftz.f32 %0, %1;" : "=f"(r) : "f"(rbf(s)));
    return r;
}
__device__ __forceinline__ uint32_t ln_mod2(uint32_t x, uint32_t mean2, float rsd, uint32_t c1, uint32_t sh) {
    const uint32_t d = hsub2(x, mean2);
    return hadd2(hmul2(pack2(bf_lo(d) * rsd, bf_hi(d) * rsd), c1), sh);
}
__device__ __forceinline__ int pair_pos(int j) { return 2 * (j & 3) + (j >> 2); }

__global__ void __cluster_dims__(2, 1, 1) __launch_bounds__(THREADS, 1)
fused_decode_kernel(const __grid_constant__ Ptrs q_, const __grid_constant__ Params p) {
    extern __shared__ __align__(1024) unsigned char smem[];
    unsigned t_top;
    asm volatile("mov.u32 %0, %%globaltimer_lo;" : "=r"(t_top));
    const int tid = threadIdx.x;
    uint32_t z0;
    asm("and.b32 %0, %1, 1024;" : "=r"(z0) : "r"(tid));
    const char* kw = *(const char* const*)((const char*)&q_.kwin + z0);
    const uint32_t sb = (uint32_t)__cvta_generic_to_shared(smem);
    auto place = [](int cl) { return cl < 4 ? 8 * cl + 39 : cl - 4 + max((cl * 37 - 36 * 37) >> 8, 0); };
    uint32_t z2;
    asm("and.b32 %0, %1, 2048;" : "=r"(z2) : "r"(tid));
    const int cv = blockIdx.x + z2, pw = place(cv >> 1);
    static_assert(SK * DH * 2 == 1 << 22 && TILE_BYTES == 1 << 14, "koff");
    const char* kp;
    auto set_kp = [&](uint32_t off) {
        asm volatile("{\n.reg .u32 lo, hi;\nmov.b64 {lo, hi}, %1;\nadd.cc.u32 lo, lo, %2;\naddc.u32 hi, hi, 0;\nmov.b64 %0, {lo, hi};\n}"
                     : "=l"(kp) : "l"(kw), "r"(off));
    };
    uint64_t pol;
    asm("createpolicy.fractional.L2::evict_first.b64 %0, 1.0;" : "=l"(pol));
    auto fill_k = [&](int n) {
        mbar_expect_tx(sb + full_bar(n), TILE_BYTES);
        bulk_load(sb + slot_addr(n), kp + (n - N_K) * 2 * TILE_BYTES, TILE_BYTES, sb + full_bar(n), pol);
    };
    static_assert(K_FIRST >= 1, "head block starts with K tile 0");
    if (tid + (sb >> 28) == HEAD_TID) {
        mbar_init(sb + full_bar(N_K), 1);
        set_kp(((pw & 7) << 22) | ((pw & 8) << 24) | ((pw & 48) << 21) | ((cv & 1) << 14));
        bulk_load(sb + slot_addr(N_K), kp, TILE_BYTES, sb + full_bar(N_K), pol);
        mbar_expect_tx(sb + full_bar(N_K), TILE_BYTES);
#pragma unroll
        for (int j = 1; j < K_FIRST; j++) { mbar_init(sb + full_bar(N_K + j), 1); fill_k(N_K + j); }
    }
    __syncwarp();
    const int cta = blockIdx.x, rank = cta & 1, pv = place(cta >> 1);
    const int b = (pv >> 3) & 1, h = (pv & 7) | ((pv >> 1) & 24), bh = 32 * b + h;
    const int mc = 2 * pv + rank;
    auto first_fill = [&](int j) {
        const int n = fill_tile(j);
        if (n >= N_K) {
            fill_k(n);
        } else if (n >= N_WQ) {
            mbar_expect_tx(sb + full_bar(n), TILE_BYTES);
            tma2d(sb + slot_addr(n), &p.m_wq, h * DH + 64 * rank, 128 * (n - N_WQ), sb + full_bar(n));
        } else if (mc < N_MOD_CTA) {
            mbar_expect_tx(sb + full_bar(n), TILE_BYTES);
            tma2d(sb + slot_addr(n), &p.m_wmod, 32 * mc, 256 * n, sb + full_bar(n));
        } else {
            mbar_arrive(sb + full_bar(n));
        }
    };
    if (tid == HEAD_TID) {
#pragma unroll
        for (int j = K_FIRST; j < FIRST_N; j++) mbar_init(sb + full_bar(fill_tile(j)), 1);
#pragma unroll
        for (int j = K_FIRST; j < FIRST_N; j++) first_fill(j);
        asm volatile("fence.mbarrier_init.release.cluster;" ::: "memory");
    }
    __syncwarp();
    const int role = cta / 3;
    const bool is_gu = cta == 3 * role, is_gb = cta == 3 * role + 1 && role < 32;
    if (tid >= 288) {
        const unsigned t_start = t_top;
        asm volatile("barrier.cluster.arrive.relaxed.aligned;" ::: "memory");
        unsigned tag;
        asm volatile("ld.relaxed.gpu.global.u32 %0, [%1];" : "=r"(tag) : "l"(&g_epoch) : "memory");
        tag += 1;
        if (cta == NCTA - 1) {
#pragma unroll 2
            for (int i = tid - 288; i < 128 * 8; i += 32) {
                uint4* q = reinterpret_cast<uint4*>(s_line(i >> 6, (i >> 3) & 7)) + (i & 7);
                const uint32_t v = (i & 48) == 48 ? ~0u : 0u;
                q[0] = make_uint4(v, v, v, v);
                q[8] = q[32] = q[40] = make_uint4(0u, 0u, 0u, 0u);
            }
            __syncwarp();
            asm volatile("fence.acq_rel.gpu;" ::: "memory");
            if (tid == 288) asm volatile("st.relaxed.gpu.global.u32 [%0], %1;" :: "l"(&g_clear), "r"(tag) : "memory");
        }
        asm volatile("barrier.cluster.wait.acquire.aligned;" ::: "memory");
        mbar_wait_cluster(sb + BAR_XQ, 0);
#pragma unroll 1
        for (uint32_t n = 0; n < SPIN_LIMIT; n++) {
            unsigned c;
            asm volatile("ld.relaxed.gpu.global.u32 %0, [%1];" : "=r"(c) : "l"(&g_clear) : "memory");
            if (c == tag) break;
        }
        asm volatile("fence.acq_rel.gpu;" ::: "memory");
        asm volatile("st.volatile.shared.u32 [%0], %1;" :: "r"(sb + SM_SIDE), "r"(0) : "memory");
        asm volatile("bar.sync 2, 288;" ::: "memory");
        if (elect_one()) {
            asm volatile("prefetch.tensormap [%0];" :: "l"(is_gu ? &p.m_w1 : &p.m_gb) : "memory");
            asm volatile("prefetch.tensormap [%0];" :: "l"(&p.m_w3) : "memory");
            asm volatile("prefetch.tensormap [%0];" :: "l"(&p.m_w2) : "memory");
            const int issue = ((4 * N_GATE - 11) * PACE >> 2) - LEAD_NS;
            unsigned now, c = 0, best[2] = {~0u, ~0u}, np = is_gu ? 0 : PROBES;
            auto probe = [&]() {
                const int k = np >> 1, i = (role >> 3) + 2 * k;
                const u64 a = (s_line(e1_blk(0, role & 7), i < 6 ? i : i - 6) + (k ? 512 * k - 384 : 0)) ^ ((np & 1) << 12);
                unsigned v, c0, c1 = 0;
                asm volatile("mov.u32 %0, %%clock;" : "=r"(c0));
                asm volatile("ld.relaxed.gpu.global.u32 %0, [%1];" : "=r"(v) : "l"(a) : "memory");
                asm volatile("{\n.reg .pred p;\nsetp.ne.u32 p, %1, 0xffffffff;\n@p mov.u32 %0, %%clock;\n}" : "+r"(c1) : "r"(v));
                if (np & 1) best[1] = min(best[1], c1 - c0); else best[0] = min(best[0], c1 - c0);
                np++;
                if (!(np & 1)) asm volatile("st.volatile.shared.u32 [%0], %1;" :: "r"(sb + SM_SIDE), "r"(best[0] <= best[1] ? 0 : 4096) : "memory");
            };
#pragma unroll 1
            while (np < PROBES) {
                now = time_ns();
                if ((int)(now - t_start) >= issue + EARLY_NS) break;
                probe();
            }
            mbar_wait(sb + full_bar(N_GATE), tile_phase(N_GATE));
            now = time_ns();
            const unsigned mine = (1u << 24) + min(now - t_start, 100000u);
            const u64 prog = s_line(0, 7) + S_PROG;
            asm volatile("red.relaxed.gpu.global.add.u32 [%0], %1;" :: "l"(prog), "r"(mine) : "memory");
            if (is_gu || is_gb) {
#pragma unroll
                for (int i = 0; i < 6; i++) mbar_wait(sb + empty_bar(N_FFN + i), tile_phase(N_FFN + i) ^ 1);
#pragma unroll
                for (int i = 0; i < NQ; i++) mbar_expect_tx(sb + BAR_FFN + 8 * i, is_gu ? 65536 / NQ : 8192);
#pragma unroll
                for (int i = 0; i < NW; i++) mbar_expect_tx(sb + BAR_W2 + 8 * i, 32768 / NW);
                unsigned due = 0, next = now;
                constexpr unsigned full = (unsigned)NCTA << 24;
                asm volatile("st.volatile.shared.u32 [%0], %1;" :: "r"(sb + SM_PROG), "r"(mine) : "memory");
#pragma unroll 1
                for (uint32_t n = 0; n < 4096; n++) {
                    unsigned v;
                    asm volatile("ld.volatile.shared.u32 %0, [%1];" : "=r"(v) : "r"(sb + SM_PROG) : "memory");
                    if (v > c) {
                        c = v;
                        const int arr = (int)__fdividef((float)(c & 0xffffffu), (float)(c >> 24));
                        due = arr - ((arr - issue) * ALPHA16 >> 4) + (is_gb ? W2_NS - GB_LEAD : GU_NS);
                    }
                    now = time_ns();
                    if (now - t_start + PROBE_NS >= due) np = PROBES;
                    if ((c >= full && np == PROBES) || now - t_start >= due) break;
                    if ((int)(now - next) >= 0 && c < full) {
                        asm volatile("cp.async.cg.shared.global [%0], [%1], 16;" :: "r"(sb + SM_PROG), "l"(prog) : "memory");
                        next = now + POLL_NS;
                    }
                    if (np < PROBES) probe();
                }
#pragma unroll 1
                for (uint32_t n = 0; n < 1024 && now - t_start < due; n++) now = time_ns();
                if (is_gu) {
#pragma unroll
                    for (int i = 0; i < 2 * NQ; i++) {
                        const int q = i >> 1, r0 = q * (512 / NQ);
                        tma4d(sb + slot_addr(N_FFN) + (r0 >> 8) * 2 * TILE_BYTES + (i & 1) * TILE_BYTES + (r0 & 255) * 64, (i & 1) ? &p.m_w3 : &p.m_w1, 32 * role, r0 / 16, sb + BAR_FFN + 8 * q);
                    }
#pragma unroll 1
                    for (uint32_t n = 0; n < 1024 && now - t_start < due + (W2_NS - GU_NS); n++) now = time_ns();
                    const int f = best[0] <= best[1] ? NW / 2 : 0;
#pragma unroll
                    for (int i = 0; i < NW; i++) tma5d(sb + slot_addr(N_FFN + 4) + (i ^ f) * (32768 / NW), &p.m_w2, 2 * role, (i ^ f) * (8 / NW), sb + BAR_W2 + 8 * (i ^ f));
                } else {
                    tma2d(sb + slot_addr(N_FFN), &p.m_gb, 5 * D_ + 16 * role, 0, sb + BAR_FFN);
                    tma2d(sb + slot_addr(N_FFN) + 8192, &p.m_gb, 5 * D_ + 16 * role, 256, sb + BAR_FFN + 8);
                }
                asm volatile("cp.async.wait_all;" ::: "memory");
            }
        }
        __syncwarp();
        if (is_gu) {
            const int lane = tid & 31;
            auto sum8 = [&](uint32_t a, int stride) {
                float4 u[8];
#pragma unroll
                for (int i = 0; i < 8; i++) u[i] = lds128f(a + i * stride);
                return make_float4(((u[0].x + u[1].x) + (u[2].x + u[3].x)) + ((u[4].x + u[5].x) + (u[6].x + u[7].x)),
                                   ((u[0].y + u[1].y) + (u[2].y + u[3].y)) + ((u[4].y + u[5].y) + (u[6].y + u[7].y)),
                                   ((u[0].z + u[1].z) + (u[2].z + u[3].z)) + ((u[4].z + u[5].z) + (u[6].z + u[7].z)),
                                   ((u[0].w + u[1].w) + (u[2].w + u[3].w)) + ((u[4].w + u[5].w) + (u[6].w + u[7].w)));
            };
            uint32_t h_st = sb + SM_Q + (((lane & 1) * 4 + ((lane >> 2) & 3)) * 4 + (lane & 2) + (lane >> 4)) * 4;
            bar_sync<3>();
            const float4 C = sum8(sb + SM_P + lane * 16, 1024), S = sum8(sb + SM_P + 512 + lane * 16, 1024);
            const uint32_t st_ld = sb + SM_RED + (lane & 1) * 64;
            settle(tag, sb + SM_OP, C); settle(tag, sb + SM_OP, S); settle(tag, sb + SM_OP, h_st, st_ld, 0, 0);
            bar_sync<4>();
            const float4 r0 = lds128f(st_ld), r1 = lds128f(st_ld + 16), r2 = lds128f(st_ld + 32), r3 = lds128f(st_ld + 48);
            const float4 Y = sum8(sb + SM_PART + lane * 16, 512);
            const float e1 = r0.z - r0.x, e2 = r1.x - r0.x, e3 = r1.z - r0.x, e4 = r2.x - r0.x, e5 = r2.z - r0.x, e6 = r3.x - r0.x, e7 = r3.z - r0.x;
            const float se = ((e1 + e2) + (e3 + e4)) + ((e5 + e6) + e7);
            const float ee = (fmaf(e1, e1, e2 * e2) + fmaf(e3, e3, e4 * e4)) + fmaf(e5, e5, fmaf(e6, e6, e7 * e7));
            const float sq = ((r0.y + r0.w) + (r1.y + r1.w)) + ((r2.y + r2.w) + (r3.y + r3.w));
            float rsd;
            asm("rsqrt.approx.ftz.f32 %0, %1;" : "=f"(rsd) : "f"(fmaf(fmaf(se * (-1.0f / D_), se, fmaf(ee, 1.0f / 64, sq)), 1.0f / D_, 1e-5f)));
            const float mu = -rbf(fmaf(r0.x, 8.0f, se) * (1.0f / D_));
            const float g0 = fmaf(rsd, fmaf(mu, C.x, Y.x), S.x), g1 = fmaf(rsd, fmaf(mu, C.z, Y.z), S.z);
            const float u0 = fmaf(rsd, fmaf(mu, C.y, Y.y), S.y), u1 = fmaf(rsd, fmaf(mu, C.w, Y.w), S.w);
            const uint32_t hv = pack2(silu_f(g0) * u0, silu_f(g1) * u1);
            sts32f(h_st, __uint_as_float(hv));
            bar_arrive<5>();
            if (role == 0 && lane == 0) g_epoch = tag;
        }
        return;
    }
    if (tid >= 256) {
        set_kp(bh * (SK * DH * 2) + rank * TILE_BYTES);
        const unsigned t_start = t_top;
        auto pace = [&](int q4) {
            const int due = (q4 * PACE >> 2) - LEAD_NS;
            unsigned now, n = 0;
            do { now = time_ns(); } while ((int)(now - t_start) < due && ++n < 256);
        };
        if (tid == 256) {
#pragma unroll
            for (int j = FIRST_N; j < STAGES; j++) mbar_init(sb + full_bar(fill_tile(j)), 1);
#pragma unroll
            for (int s = 0; s < STAGES; s++) mbar_init(sb + BAR_EMPTY + 8 * s, 8);
            mbar_init(sb + BAR_XQ, 1); mbar_init(sb + BAR_XML, 1); mbar_init(sb + BAR_XP, 1); mbar_init(sb + BAR_XO, 1);
#pragma unroll
            for (int i = 0; i < NQ + NW; i++) mbar_init(sb + BAR_FFN + 8 * i, 1);
            mbar_expect_tx(sb + BAR_XQ, 256); mbar_expect_tx(sb + BAR_XML, 8); mbar_expect_tx(sb + BAR_XP, WIN); mbar_expect_tx(sb + BAR_XO, 1024);
            asm volatile("fence.mbarrier_init.release.cluster;" ::: "memory");
            asm volatile("fence.proxy.async.shared::cta;" ::: "memory");
        }
        __syncwarp();
        asm volatile("barrier.cluster.arrive.relaxed.aligned;" ::: "memory");
        if (elect_one()) {
#pragma unroll
            for (int j = FIRST_N; j < STAGES; j++) {
                pace(j <= K_FIRST ? 4 * j : j <= K_FIRST + 2 ? 4 * K_FIRST + 5 * (j - K_FIRST) / 2 :
                     j <= K_FIRST + 6 ? 4 * K_FIRST + 5 + 2 * (j - K_FIRST - 2) : 4 * j - 11);
                first_fill(j);
            }
        }
        __syncwarp();
        asm volatile("barrier.cluster.wait.acquire.aligned;" ::: "memory");
        if (elect_one()) {
            asm volatile("prefetch.tensormap [%0];" :: "l"(&p.m_v) : "memory");
            asm volatile("prefetch.tensormap [%0];" :: "l"(&p.m_wo) : "memory");
            int s = 0, ph = 0;
#pragma unroll 1
            for (int n = STAGES; n < N_FFN; n++) {
                const uint32_t dst = sb + SM_RING + s * TILE_BYTES, bar = sb + BAR_FULL + 8 * s;
                mbar_wait(sb + BAR_EMPTY + 8 * s, ph);
                mbar_expect_tx(bar, TILE_BYTES);
                pace(n < N_WO ? 4 * n - 11 : 2 * (N_WO + n) - 11);
                if (n < N_V) bulk_load(dst, kp + (n - N_K) * 2 * TILE_BYTES, TILE_BYTES, bar, pol);
                else if (n < N_WO) tma2d_hint(dst, &p.m_v, 64 * rank, bh * SK + (SK - WIN) + 128 * (n - N_V), bar, pol);
                else tma3d(dst, &p.m_wo, 0, h * DH + 32 * (n - N_WO), 4 * rank, bar);
                if (++s == STAGES) { s = 0; ph ^= 1; }
            }
        }
        return;
    }

    const unsigned t_c = t_top;
    const int lane = tid & 31, w = tid >> 5, g = lane >> 2, t = lane & 3;
    const int hgrp = 4 * w + (g & 3);
    const int vb = g >> 2;
    const uint32_t cv0 = ldg32(q_.c + vb * D_ + 16 * hgrp + 2 * t), cv1 = ldg32(q_.c + vb * D_ + 16 * hgrp + 8 + 2 * t);
    unsigned tag;
    asm volatile("ld.relaxed.gpu.global.u32 %0, [%1];" : "=r"(tag) : "l"(&g_epoch) : "memory");
    const uint4 xa = ldg128(q_.x + b * D_ + 16 * lane), xb = ldg128(q_.x + b * D_ + 16 * lane + 8);
    const uint32_t xh0 = ldg32(q_.x + b * D_ + 16 * hgrp + 2 * t), xh1 = ldg32(q_.x + b * D_ + 16 * hgrp + 8 + 2 * t);
    asm volatile("barrier.cluster.arrive.relaxed.aligned;" ::: "memory");
#pragma unroll 1
    for (uint32_t n = t_c; n < 2; n++) asm volatile("nanosleep.u32 1;" ::: "memory");
    const int grp = w >> 2, sub = w & 3;
    const int lrow = (lane & 7) + 8 * (lane >> 4);
    const int lch = (lane >> 3) & 1;
    const int ob = lane >> 4;
    const uint32_t t1 = t & 1, t2 = t & 2;
    const int gsrc = 16 * (g & 1) + t;
    const uint32_t sw128 = lrow * 128 + ((lch ^ (lrow & 7)) << 4);
    uint32_t A[16][4];

    const uint32_t sc0 = pack2(silu_f(bf_lo(cv0)), silu_f(bf_hi(cv0))), sc1 = pack2(silu_f(bf_lo(cv1)), silu_f(bf_hi(cv1)));
    tag += 1;
    asm volatile("barrier.cluster.wait.acquire.aligned;" ::: "memory");
    mbar_wait(sb + BAR_FULL + 8 * (N_WMOD + grp), 0);
    if (mc < N_MOD_CTA) {
        const uint32_t tb = sb + SM_RING + (N_WMOD + grp) * TILE_BYTES + (64 * sub + lrow) * 64;
#pragma unroll
        for (int i = 0; i < 8; i++)
            ldsm4t(tb + (i >> 1) * 1024 + (((2 * (i & 1) + lch) ^ ((lrow >> 1) & 3)) << 4), A[i]);
        float acc[2][4] = {{0.f, 0.f, 0.f, 0.f}, {0.f, 0.f, 0.f, 0.f}};
#pragma unroll
        for (int s = 0; s < 4; s++) {
            const uint32_t b0 = __shfl_sync(~0u, sc0, 4 * s + gsrc), b1 = __shfl_sync(~0u, sc1, 4 * s + gsrc);
            mma4(acc[0], A[2 * s], b0, b1);
            mma4(acc[1], A[2 * s + 1], b0, b1);
        }
        sts32f(sb + SM_P + (w * 64 + 8 * t + g) * 4, sel(t2, sel(t1, acc[1][2], acc[1][0]), sel(t1, acc[0][2], acc[0][0])));
        sts32f(sb + SM_P + (w * 64 + 32 + 8 * t + g) * 4, sel(t2, sel(t1, acc[1][3], acc[1][1]), sel(t1, acc[0][3], acc[0][1])));
        cbar();
        if (w == 0) {
            const bool adj = mc < 32;
            const uint32_t a0 = sb + SM_P + (adj ? 2 * lane : ob * 32 + (lane & 1) * 16 + ((lane >> 1) & 7)) * 4, a1 = a0 + (adj ? 4 : 32);
            float2 sum = make_float2(0.f, 0.f);
#pragma unroll
            for (int i = 0; i < 8; i++) { sum.x += lds32f(a0 + i * 256); sum.y += lds32f(a1 + i * 256); }
            st_pkt((u64)&g_mod[ob][16 * mc + (adj ? (lane & 8) + pair_pos(lane & 7) : lane & 15)], pack2(sum.x, sum.y), tag);
        }
    }
    __syncwarp();
    if (lane == 0) mbar_arrive_n(sb + BAR_EMPTY + 8 * (N_WMOD + grp), 2);

    {
        const uint2* mp = &g_mod[b][vb * 256 + 8 * hgrp + 2 * t];
        const uint32_t ms = sb + SM_PART + tid * 16;
        auto fetch_mod = [&](uint32_t k) {
            asm volatile("cp.async.cg.shared.global [%0], [%1], 16;\ncp.async.commit_group;" :: "r"(ms + k), "l"(mp) : "memory");
        };
        fetch_mod(0);
        float xs[16] = {bf_lo(xa.x), bf_hi(xa.x), bf_lo(xa.y), bf_hi(xa.y), bf_lo(xa.z), bf_hi(xa.z), bf_lo(xa.w), bf_hi(xa.w),
                        bf_lo(xb.x), bf_hi(xb.x), bf_lo(xb.y), bf_hi(xb.y), bf_lo(xb.z), bf_hi(xb.z), bf_lo(xb.w), bf_hi(xb.w)};
        float s = 0.f;
#pragma unroll
        for (int i = 0; i < 16; i++) s += xs[i];
#pragma unroll
        for (int m = 1; m < 32; m <<= 1) s += __shfl_xor_sync(~0u, s, m);
        const float mean = s * (1.0f / D_);
        float q = 0.f;
#pragma unroll
        for (int i = 0; i < 16; i++) q += (xs[i] - mean) * (xs[i] - mean);
#pragma unroll
        for (int m = 1; m < 32; m <<= 1) q += __shfl_xor_sync(~0u, q, m);
        const uint32_t mean2 = pack2(mean, mean);
        const float rsd = rcp_sd(q);

        mbar_wait(sb + BAR_FULL + 8 * (N_WQ + (w >> 1)), 0);
        const uint32_t tb = sb + SM_RING + (N_WQ + (w >> 1)) * TILE_BYTES + (w & 1) * 8192;
#pragma unroll
        for (int i = 0; i < 16; i++) ldsm4t(tb + (i >> 2) * 2048 + (sw128 ^ ((i & 3) * 32)), A[i]);
        __syncwarp();
        if (lane == 0) mbar_arrive_n(sb + BAR_EMPTY + 8 * (N_WQ + (w >> 1)), 4);

        Pkt2 m;
        for (uint32_t n = 0, k = 0; n < SPIN_LIMIT; n++) {
            fetch_mod(k ^ 4096);
            asm volatile("cp.async.wait_group 1;" ::: "memory");
            const uint4 u = lds128(ms + k);
            m.a = u.x | (u64)u.y << 32; m.b = u.z | (u64)u.w << 32;
            if (__all_sync(~0u, pkt_ok(m, tag))) break;
            k ^= 4096;
        }
        const uint32_t ca0 = __shfl_xor_sync(~0u, lo32(m.a), 16), ca1 = __shfl_xor_sync(~0u, lo32(m.b), 16);
        const uint32_t v0 = ln_mod2(xh0, mean2, rsd, hadd2(ONE2, ca0), lo32(m.a));
        const uint32_t v1 = ln_mod2(xh1, mean2, rsd, hadd2(ONE2, ca1), lo32(m.b));
        float acc[4][4];
#pragma unroll
        for (int i = 0; i < 4; i++) { acc[i][0] = acc[i][1] = acc[i][2] = acc[i][3] = 0.f; }
#pragma unroll
        for (int s4 = 0; s4 < 4; s4++) {
            const uint32_t b0 = __shfl_sync(~0u, v0, 4 * s4 + t), b1 = __shfl_sync(~0u, v1, 4 * s4 + t);
#pragma unroll
            for (int i = 0; i < 4; i++) mma4(acc[i], A[4 * s4 + i], b0, b1);
        }
        sts32f(sb + SM_OP + (w * 64 + 16 * t + g) * 4, sel(t2, sel(t1, acc[3][0], acc[2][0]), sel(t1, acc[1][0], acc[0][0])));
        sts32f(sb + SM_OP + (w * 64 + 16 * t + 8 + g) * 4, sel(t2, sel(t1, acc[3][2], acc[2][2]), sel(t1, acc[1][2], acc[0][2])));
        cbar();
        if (w == 0) {
            float2 sum = make_float2(0.f, 0.f);
#pragma unroll
            for (int i = 0; i < 8; i++) { const float2 u = lds64f(sb + SM_OP + (i * 64 + 2 * lane) * 4); sum.x += u.x; sum.y += u.y; }
            const uint32_t v = pack2(sum.x, sum.y), a = sb + SM_Q + rank * 128 + lane * 4;
            st_async_b32(mapa(a, rank ^ 1), v, mapa(sb + BAR_XQ, rank ^ 1));
            st_async_b32(mapa(a, rank), v, mapa(sb + BAR_XQ, rank));
        }
        mbar_wait_cluster(sb + BAR_XQ, 0);
    }

    Pkt2 mga, msb, mcb;
    uint32_t tx0, tx1;
    const uint2* tmp = &g_mod[ob][32 * w + 2 * (lane & 15)];
    {
        uint4 Q[4];
        uint32_t koff[4];
#pragma unroll
        for (int i = 0; i < 4; i++) {
            const int ch = t + 4 * (i ^ (g & 1));
            Q[i] = lds128(sb + SM_Q + ch * 16);
            koff[i] = (sub * 16 + g) * 256 + ch * 16;
        }
        float mx = -INFINITY;
        int stage = N_K + grp, phase = 0;
#pragma unroll 1
        for (int it = 0; it < NT / 2; it++) {
            const uint32_t tb = sb + SM_RING + stage * TILE_BYTES;
            mbar_wait(sb + BAR_FULL + 8 * stage, phase);
            uint4 Ka[4], Kb[4];
#pragma unroll
            for (int i = 0; i < 4; i++) { Ka[i] = lds128(tb + koff[i]); Kb[i] = lds128(tb + koff[i] + 2048); }
            float c0[4] = {0.f, 0.f, 0.f, 0.f}, c1[4] = {0.f, 0.f, 0.f, 0.f};
#pragma unroll
            for (int i = 0; i < 4; i++) {
                mma(c0, Ka[i].x, Kb[i].x, Ka[i].y, Kb[i].y, Q[i].x, Q[i].y);
                mma(c1, Ka[i].z, Kb[i].z, Ka[i].w, Kb[i].w, Q[i].z, Q[i].w);
            }
            __syncwarp();
            if (lane == 0) mbar_arrive_n(sb + BAR_EMPTY + 8 * stage, 2);
            const float lo = (g & 1) ? c0[1] + c1[1] : c0[0] + c1[0];
            const float hi = (g & 1) ? c0[3] + c1[3] : c0[2] + c1[2];
            const float sc = rbf(rbf(t1 ? hi : lo) * 0.08838834764831845f);
            mx = fmaxf(mx, sc);
            if (t < 2) sts16(sb + SM_P + ((2 * it + grp) * 128 + rank * 64 + sub * 16 + 4 * (g >> 1) + 2 * t + (g & 1)) * 2, __float_as_uint(sc) >> 16);
            stage += 2;
            if (stage >= STAGES) { stage -= STAGES; phase ^= 1; }
        }

        mga = ld_pkt2(tmp + 2 * 256); msb = ld_pkt2(tmp + 3 * 256); mcb = ld_pkt2(tmp + 4 * 256);
        const __nv_bfloat16* xp = q_.x + ob * D_ + 64 * w + 4 * (lane & 8) + (lane & 7);
        tx0 = ldg16(xp) | ldg16(xp + 8) << 16;
        tx1 = ldg16(xp + 16) | ldg16(xp + 24) << 16;

        asm volatile("cp.async.wait_all;" ::: "memory");

#pragma unroll
        for (int m = 1; m < 32; m <<= 1) mx = fmaxf(mx, __shfl_xor_sync(~0u, mx, m));
        if (lane == 0) sts32f(sb + SM_RED + w * 4, mx);
        cbar();
        {
            const float4 u = lds128f(sb + SM_RED), v = lds128f(sb + SM_RED + 16);
            mx = fmaxf(fmaxf(fmaxf(u.x, u.y), fmaxf(u.z, u.w)), fmaxf(fmaxf(v.x, v.y), fmaxf(v.z, v.w)));
        }
        const uint32_t pa = sb + SM_P + (tid >> 3) * 256 + rank * 128 + (tid & 7) * 16;
        const uint4 s0 = lds128(pa);
        const float sc[8] = {bf_lo(s0.x), bf_hi(s0.x), bf_lo(s0.y), bf_hi(s0.y), bf_lo(s0.z), bf_hi(s0.z), bf_lo(s0.w), bf_hi(s0.w)};
        float l = 0.f;
#pragma unroll
        for (int i = 0; i < 8; i++) l += __expf(sc[i] - mx);
#pragma unroll
        for (int m = 1; m < 32; m <<= 1) l += __shfl_xor_sync(~0u, l, m);
        if (lane == 0) sts32f(sb + SM_RED + 32 + w * 4, l);
        cbar();
        {
            const float4 u = lds128f(sb + SM_RED + 32), v = lds128f(sb + SM_RED + 48);
            l = ((u.x + u.y) + (u.z + u.w)) + ((v.x + v.y) + (v.z + v.w));
        }
        if (tid == 0) st_async_v2(mapa(sb + SM_ML, rank ^ 1), mx, l, mapa(sb + BAR_XML, rank ^ 1));
        mbar_wait_cluster(sb + BAR_XML, 0);
        const float2 o = lds64f(sb + SM_ML);
        const float m = fmaxf(mx, o.x);
        const float inv = __fdividef(1.0f, l * __expf(mx - m) + o.y * __expf(o.x - m));
        const uint32_t p0 = pack2(__expf(sc[0] - m) * inv, __expf(sc[1] - m) * inv), p1 = pack2(__expf(sc[2] - m) * inv, __expf(sc[3] - m) * inv);
        const uint32_t p2 = pack2(__expf(sc[4] - m) * inv, __expf(sc[5] - m) * inv), p3 = pack2(__expf(sc[6] - m) * inv, __expf(sc[7] - m) * inv);
        st_async_v4(mapa(pa, rank ^ 1), p0, p1, p2, p3, mapa(sb + BAR_XP, rank ^ 1));
        sts128(pa, p0, p1, p2, p3);
        cbar();
        mbar_wait_cluster(sb + BAR_XP, 0);
    }

#pragma unroll 1
    for (uint32_t n = 0; n < SPIN_LIMIT && !__all_sync(~0u, pkt_ok(mga, tag) && pkt_ok(msb, tag) && pkt_ok(mcb, tag)); n++) {
        mga = ld_pkt2(tmp + 2 * 256); msb = ld_pkt2(tmp + 3 * 256); mcb = ld_pkt2(tmp + 4 * 256);
    }
    const uint32_t ga0 = lo32(mga.a), ga1 = lo32(mga.b), sb0 = lo32(msb.a), sb1 = lo32(msb.b);
    const uint32_t cb0 = hadd2(ONE2, lo32(mcb.a)), cb1 = hadd2(ONE2, lo32(mcb.b));
    const int wb = 4 * rank + sub;
    u64 red_p = s_line(e1_blk(1, wb), 2 * b) + lane * 4, red2_p = s_line(e1_blk(1, wb), 4 + b) + lane * 4;

    PIN64(red_p); PIN64(red2_p);
    float oa[4][4];
#pragma unroll
    for (int i = 0; i < 4; i++) { oa[i][0] = oa[i][1] = oa[i][2] = oa[i][3] = 0.f; }
    {
        int stage = N_V % STAGES, phase = tile_phase(N_V);
        auto v_tiles = [&](int v0, int v1) {
#pragma unroll 1
            for (int v = v0; v < v1; v++) {
                const uint32_t tb = sb + SM_RING + stage * TILE_BYTES + grp * 8192 + (sw128 ^ (sub * 32));
                uint2 P[4];
#pragma unroll
                for (int i = 0; i < 4; i++) P[i] = lds64(sb + SM_P + v * 256 + grp * 128 + i * 32 + t * 8);
                mbar_wait(sb + BAR_FULL + 8 * stage, phase);
                uint32_t a[4][4];
#pragma unroll
                for (int i = 0; i < 4; i++) ldsm4t(tb + i * 2048, a[i]);
#pragma unroll
                for (int i = 0; i < 4; i++) mma4(oa[i], a[i], P[i].x, P[i].y);
                __syncwarp();
                if (lane == 0) mbar_arrive(sb + BAR_EMPTY + 8 * stage);
                if (++stage == STAGES) { stage = 0; phase ^= 1; }
            }
        };
        v_tiles(0, MEET_AT);
        asm volatile("bar.sync 2, 288;" ::: "memory");
        v_tiles(MEET_AT, NT);
    }

    if (t < 2) {
        const uint32_t a = sb + SM_OP + rank * 512 + w * 64 + (g >> 1) * 16 + (g & 1) * 4 + t * 8;
        const uint32_t v = __float_as_uint(sel(t1, (oa[0][2] + oa[1][2]) + (oa[2][2] + oa[3][2]), (oa[0][0] + oa[1][0]) + (oa[2][0] + oa[3][0])));
        st_async_b32(mapa(a, rank ^ 1), v, mapa(sb + BAR_XO, rank ^ 1));
        st_async_b32(mapa(a, rank), v, mapa(sb + BAR_XO, rank));
    }
    __syncwarp();
    mbar_wait_cluster(sb + BAR_XO, 0);

    {
        float acc[4][4];
        const uint32_t o_ld = sb + SM_OP + grp * 512 + (lane & 15) * 16 + vb * 8, x_st = sb + SM_PART + 4096 + sub * 1024 + lane * 16;
        const float2 u = lds64f(o_ld), v = lds64f(o_ld + 256);
        const uint32_t o2 = pack2(u.x + v.x, u.y + v.y);
        uint32_t bo[8];
#pragma unroll
        for (int i = 0; i < 8; i++) bo[i] = __shfl_sync(~0u, o2, 16 * (i & 1) + 4 * (i >> 1) + t);
        float4 x0 = make_float4(0.f, 0.f, 0.f, 0.f), x1 = x0;
#pragma unroll
        for (int i = 0; i < 4; i++) { acc[i][0] = acc[i][1] = acc[i][2] = acc[i][3] = 0.f; }
        static_assert(N_WO % STAGES + 4 <= STAGES, "wo tiles occupy consecutive slots");
        const uint32_t wa = sb + slot_addr(N_WO) + grp * 2 * TILE_BYTES + sub * 4096, wbar = sb + full_bar(N_WO) + grp * 16;
#pragma unroll
        for (int j = 0; j < 2; j++) {
            if (j == 1 && grp) { asm volatile("bar.sync 8, 256;" ::: "memory"); x0 = lds128f(x_st); x1 = lds128f(x_st + 512); }
            mbar_wait(wbar + 8 * j, tile_phase(N_WO));
            if (j == 1) { }
#pragma unroll
            for (int i = 0; i < 8; i++) ldsm4t(wa + j * TILE_BYTES + (i >> 2) * 2048 + (sw128 ^ ((i & 3) * 32)), A[8 * j + i]);
#pragma unroll
            for (int i = 0; i < 8; i++) mma4(acc[i & 3], A[8 * j + i], bo[4 * j + 2 * (i >> 2)], bo[4 * j + 2 * (i >> 2) + 1]);
        }
        if (!grp) {
            sts128f(x_st, acc[0][0], acc[1][0], acc[2][0], acc[3][0]); sts128f(x_st + 512, acc[0][2], acc[1][2], acc[2][2], acc[3][2]);
            asm volatile("bar.arrive 8, 256;" ::: "memory");
        } else {
            acc[0][0] += x0.x; acc[1][0] += x0.y; acc[2][0] += x0.z; acc[3][0] += x0.w; acc[0][2] += x1.x; acc[1][2] += x1.y; acc[2][2] += x1.z; acc[3][2] += x1.w;
            const float r0 = sel(t2, sel(t1, 1.0f, acc[1][0]), sel(t1, acc[0][2], acc[0][0]));
            const float r1 = sel(t2, sel(t1, 1.0f, acc[3][0]), sel(t1, acc[2][2], acc[2][0]));
            const float r2 = sel(t2, 1.0f, sel(t1, acc[3][2], acc[1][2]));
            asm volatile("red.relaxed.gpu.global.add.f32 [%0], %2;\nred.relaxed.gpu.global.add.f32 [%0 + 256], %3;\nred.relaxed.gpu.global.add.f32 [%1], %4;"
                         :: "l"(red_p), "l"(red2_p), "f"(r0), "f"(r1), "f"(r2) : "memory");
            asm volatile("red.relaxed.gpu.global.add.f32 [%0], %2;\nred.relaxed.gpu.global.add.f32 [%0 + 256], %3;\nred.relaxed.gpu.global.add.f32 [%1], %4;"
                         :: "l"(red_p ^ 4096), "l"(red2_p ^ 4096), "f"(r0), "f"(r1), "f"(r2) : "memory");
        }
    }

    constexpr uint32_t CNT = 0x42000000u;
    if (is_gu) {
        uint32_t side;
        asm volatile("ld.volatile.shared.u32 %0, [%1];" : "=r"(side) : "r"(sb + SM_SIDE) : "memory");
        u64 acc_p = (s_line(e1_blk(0, w), lane >> 3) + (lane & 7) * 16) ^ side, acc2_p = (s_line(e1_blk(0, w), 4 + ob) + (lane & 7) * 16) ^ side;
        const int eb = e1_blk(w >> 2, w & 3);
        const bool near = __all_sync(~0u, (w >> 2) * 4096 == side);
        u64 out_p = s_line(eb, lane >> 3) + S_OUT + (lane & 7) * 16, out2_p = s_line(eb, 4 + ob) + S_OUT + (lane & 15) * 8;
        u64 gb_p = (s_line(e1_blk(0, w), 6 + ob) + (lane & 15) * 8) ^ side, y_p = (u64)(q_.out + t1 * D_ + 64 * w + 4 * t2 + g);
        PIN64(acc_p); PIN64(acc2_p); PIN64(out_p); PIN64(out2_p); PIN64(gb_p); PIN64(y_p);
        auto keep = [&](uint32_t x) { return __shfl_sync(~0u, x, lane); };
        const int src = keep(8 * (g & 2) + t), src1 = keep(src + 4), src2 = keep(src + 8), src3 = keep(src + 12);
        const uint32_t p_st = keep(sb + SM_PART + w * 512 + lane * 16), r_st = keep(sb + SM_RED + (vb * 8 + w) * 8);
        tx0 = keep(tx0); tx1 = keep(tx1);
        uint32_t w2a[4];
#pragma unroll
        for (int i = 0; i < 4; i++) w2a[i] = keep(sb + slot_addr(N_FFN + 4) + w * 4096 + (sw128 ^ (i * 32)));
        const uint32_t hva = keep(sb + SM_Q + ((g & 2) * 2 + t) * 16), w2b = keep(sb + BAR_W2 + 8 * (w * NW >> 3)), t2k = keep(t2);
        const uint32_t g1 = g & 1;
        uint32_t cp[8], cn[8];
        float acc[4][4];
#pragma unroll
        for (int i = 0; i < 8; i++) {
            cp[i] = __shfl_sync(~0u, (i & 1) ? cb1 : cb0, 4 * (i >> 1) + src);
            cn[i] = selu(g1, __shfl_sync(~0u, (i & 1) ? sb1 : sb0, 4 * (i >> 1) + src), cp[i]);
        }
        const int frow = (lane & 7) + (lane & 16);
        const uint32_t fa = sb + slot_addr(N_FFN) + grp * 2 * TILE_BYTES + (64 * sub + frow) * 64 + ((lch ^ ((frow >> 1) & 3)) << 4);
        mbar_wait(sb + BAR_FFN + 8 * (w * NQ >> 3), 0);
        uint4 u = ld_strong128(acc_p), v = ld_strong128(acc2_p);
#pragma unroll
        for (int i = 0; i < 16; i++) ldsm4t((fa ^ ((i & 1) * 32)) + (i >> 3) * 2048 + ((i >> 2) & 1) * 512 + ((i >> 1) & 1) * TILE_BYTES, A[i]);
#pragma unroll
        for (int i = 0; i < 4; i++) { acc[i][0] = acc[i][1] = acc[i][2] = acc[i][3] = 0.f; }
#pragma unroll
        for (int i = 0; i < 16; i++)
            mma4(acc[i & 3], A[i], cn[2 * (i >> 2)], cn[2 * (i >> 2) + 1]);
        sts128f(sb + SM_P + w * 1024 + lane * 16, sel(t2, acc[1][0], acc[0][0]), sel(t2, acc[3][0], acc[2][0]), sel(t2, acc[1][2], acc[0][2]), sel(t2, acc[3][2], acc[2][2]));
        sts128f(sb + SM_P + w * 1024 + 512 + lane * 16, sel(t2, acc[1][1], acc[0][1]), sel(t2, acc[3][1], acc[2][1]), sel(t2, acc[1][3], acc[0][3]), sel(t2, acc[3][3], acc[2][3]));
        bar_arrive<3>();
#pragma unroll
        for (int i = 0; i < 8; i++) cn[i] = selu(g1, cp[i] ^ 0x80008000u, 0u);
        settle(tag, sb + SM_OP, cn[0], cn[1], cn[2], cn[3]); settle(tag, sb + SM_OP, cn[4], cn[5], cn[6], cn[7]);
        for (uint32_t n = 0; !__all_sync(~0u, u.w == CNT && v.w == CNT) && n < SPIN_LIMIT; n++) { u = ld_strong128(acc_p); v = ld_strong128(acc2_p); }
        const uint32_t x0 = hadd2(tx0, hmul2(ga0, pack2(__uint_as_float(u.x), __uint_as_float(u.y))));
        const uint32_t x1 = hadd2(tx1, hmul2(ga1, pack2(__uint_as_float(u.z), __uint_as_float(selu(lane & 8, v.y, v.x)))));
        float c[4] = {0.f, 0.f, 0.f, 0.f};
        mma(c, x0, ONE2, x1, ONE2, x0, x1);
#pragma unroll
        for (int i = 0; i < 4; i++) { acc[i][0] = acc[i][1] = acc[i][2] = acc[i][3] = 0.f; }
        float q, s;
#pragma unroll
        for (int s4 = 0; s4 < 4; s4++) {
            const int from = s4 == 0 ? src : s4 == 1 ? src1 : s4 == 2 ? src2 : src3;
            uint32_t b0 = __shfl_sync(~0u, x0, from), b1 = __shfl_sync(~0u, x1, from);
            b0 = hfma2(b0, cp[2 * s4], hmul2(b0, cn[2 * s4]));
            b1 = hfma2(b1, cp[2 * s4 + 1], hmul2(b1, cn[2 * s4 + 1]));
#pragma unroll
            for (int i = 0; i < 4; i++) mma4(acc[i], A[4 * s4 + i], b0, b1);
            if (s4 == 0) { q = sel(g1, c[1], c[0]); s = c[2] + c[3]; q += __shfl_xor_sync(~0u, q, 4); s += __shfl_xor_sync(~0u, s, 9); }
            if (s4 == 1) q += __shfl_xor_sync(~0u, q, 9);
            if (s4 == 2) { if (lane == 0 || lane == 18) sts64f(r_st, s, fmaxf(fmaf(s * (-1.0f / 64), s, q), 0.f)); }
        }
        sts128f(p_st, sel(t2, acc[1][0] + acc[1][1], acc[0][0] + acc[0][1]), sel(t2, acc[3][0] + acc[3][1], acc[2][0] + acc[2][1]),
                sel(t2, acc[1][2] + acc[1][3], acc[0][2] + acc[0][3]), sel(t2, acc[3][2] + acc[3][3], acc[2][2] + acc[2][3]));
        bar_arrive<4>();
        auto w2_frags = [&]() {
            mbar_wait(w2b, 0);
#pragma unroll
            for (int i = 0; i < 8; i++) ldsm4t(w2a[i & 3] + (i >> 2) * 2048, A[i]);
        };
        if (!near) w2_frags();
#pragma unroll
        for (int i = 0; i < 4; i++) { acc[i][0] = acc[i][1] = acc[i][2] = acc[i][3] = 0.f; }
        bar_sync<5>();
        const uint4 hv = lds128(hva);
        if (near) w2_frags();
#pragma unroll
        for (int i = 0; i < 4; i++) mma4(acc[i], A[i], hv.x, hv.y);
#pragma unroll
        for (int i = 0; i < 4; i++) mma4(acc[i], A[4 + i], hv.z, hv.w);
        float r[4], o[6];
#pragma unroll
        for (int i = 0; i < 4; i++) r[i] = sel(t2k, acc[i][2], acc[i][0]);
        asm volatile("atom.relaxed.gpu.global.add.v4.f32 {%0, %1, %2, %3}, [%4], {%5, %6, %7, %8};"
                     : "=f"(o[0]), "=f"(o[1]), "=f"(o[2]), "=f"(o[4]) : "l"(out_p), "f"(r[0]), "f"(r[1]), "f"(r[2]), "f"(1.0f) : "memory");
        asm volatile("atom.relaxed.gpu.global.add.v2.f32 {%0, %1}, [%2], {%3, %4};"
                     : "=f"(o[3]), "=f"(o[5]) : "l"(out2_p), "f"(r[3]), "f"(1.0f) : "memory");
        uint2 gb = ld_strong64(gb_p);
        uint32_t xo[2];
#pragma unroll
        for (int j = 0; j < 2; j++) {
            const uint32_t e0 = __shfl_sync(~0u, x0, 16 * t1 + 8 * j + g), e1 = __shfl_sync(~0u, x1, 16 * t1 + 8 * j + g);
            xo[j] = __byte_perm(e0, e1, t2 ? 0x7632 : 0x5410);
        }
        const uint32_t f0 = pack2(o[0] + r[0], o[1] + r[1]), f1 = pack2(o[2] + r[2], o[3] + r[3]);
#pragma unroll 1
        for (uint32_t n = 0; n < SPIN_LIMIT; n++) {
            const uint32_t y0 = hadd2(xo[0], hmul2(gb.x, f0)), y1 = hadd2(xo[1], hmul2(gb.y, f1));
            uint32_t late;
            asm volatile("{\n.reg .pred p, q, m;\n.reg .b16 a, b, c, d;\n"
                         "mov.b32 {a, b}, %6;\nmov.b32 {c, d}, %7;\nsetp.ne.b16 m, a, 0xffff;\nsetp.ne.and.b16 m, b, 0xffff, m;\nsetp.ne.and.b16 m, c, 0xffff, m;\nsetp.ne.and.b16 m, d, 0xffff, m;\n"
                         "setp.eq.and.f32 p, %4, 0f42280000, m;\nsetp.eq.and.f32 q, %5, 0f42280000, m;\n"
                         "mov.b32 {a, b}, %2;\nmov.b32 {c, d}, %3;\n"
                         "@p st.global.u16 [%1], a;\n@p st.global.u16 [%1 + 32], b;\n@p st.global.u16 [%1 + 64], c;\n@q st.global.u16 [%1 + 96], d;\n"
                         "vote.sync.all.pred m, m, 0xffffffff;\nselp.u32 %0, 0, 1, m;\n}"
                         : "=r"(late) : "l"(y_p), "r"(y0), "r"(y1), "f"(o[4]), "f"(o[5]), "r"(gb.x), "r"(gb.y) : "memory");
            if (!late) break;
            gb = ld_strong64(gb_p);
        }
    } else if (is_gb) {
        const uint32_t fa = sb + slot_addr(N_FFN) + grp * 8192 + (64 * sub + lrow) * 32 + ((lch ^ ((lrow >> 2) & 1)) << 4);
        const int dl = (lane & 7) * 4 + ((lane >> 3) & 1) * 2 + ob;
        u64 gb_p = s_line(2 * (role >> 2), 6 + (dl >> 4)) + (dl & 15) * 8 + (role & 3) * 2;
        PIN64(gb_p);
        uint32_t bs[8];
#pragma unroll
        for (int i = 0; i < 8; i++) bs[i] = __shfl_sync(~0u, (i & 1) ? sc1 : sc0, 4 * (i >> 1) + 16 * ((g >> 1) & 1) + t);
        const uint32_t c_st = sb + SM_PART + (w * 32 + t1 * 16 + (t >> 1) * 8 + g) * 4;
        settle(tag, sb + SM_OP, bs[0], bs[1], bs[2], bs[3]); settle(tag, sb + SM_OP, bs[4], bs[5], bs[6], bs[7]); settle(tag, sb + SM_OP, c_st, fa, 0, 0);
        mbar_wait(sb + BAR_FFN + 8 * grp, 0);
        float c[4][4];
#pragma unroll
        for (int s4 = 0; s4 < 4; s4++) ldsm4t(fa + s4 * 512, A[s4]);
#pragma unroll
        for (int s4 = 0; s4 < 4; s4++) { c[s4][0] = c[s4][1] = c[s4][2] = c[s4][3] = 0.f; mma4(c[s4], A[s4], bs[2 * s4], bs[2 * s4 + 1]); }
        sts32f(c_st, sel(t2, (c[0][2] + c[1][2]) + (c[2][2] + c[3][2]), (c[0][0] + c[1][0]) + (c[2][0] + c[3][0])));
        cbar();
        if (w == 0) {
            float u[8];
#pragma unroll
            for (int i = 0; i < 8; i++) u[i] = lds32f(sb + SM_PART + i * 128 + lane * 4);
            const uint16_t v = (uint16_t)pack2(((u[0] + u[1]) + (u[2] + u[3])) + ((u[4] + u[5]) + (u[6] + u[7])), 0.f);
            asm volatile("st.relaxed.gpu.global.u16 [%0], %1;\nst.relaxed.gpu.global.u16 [%0 + 4096], %1;" :: "l"(gb_p), "h"(v) : "memory");
        }
    }
}

typedef CUresult (*EncodeFn)(CUtensorMap*, CUtensorMapDataType, cuuint32_t, void*, const cuuint64_t*, const cuuint64_t*,
                             const cuuint32_t*, const cuuint32_t*, CUtensorMapInterleave, CUtensorMapSwizzle,
                             CUtensorMapL2promotion, CUtensorMapFloatOOBfill);

void make_map(EncodeFn enc, CUtensorMap* m, void* ptr, int cols, int rows, int box_cols, int box_rows, CUtensorMapSwizzle sw) {
    cuuint64_t gd[2] = {(cuuint64_t)cols, (cuuint64_t)rows}, gs[1] = {(cuuint64_t)cols * 2};
    cuuint32_t bd[2] = {(cuuint32_t)box_cols, (cuuint32_t)box_rows}, es[2] = {1, 1};
    enc(m, CU_TENSOR_MAP_DATA_TYPE_BFLOAT16, 2, ptr, gd, gs, bd, es, CU_TENSOR_MAP_INTERLEAVE_NONE, sw,
        CU_TENSOR_MAP_L2_PROMOTION_NONE, CU_TENSOR_MAP_FLOAT_OOB_FILL_NONE);
}

}

extern "C" void kernel_launch(void* const* d_in, const int* in_sizes, int n_in, void* d_out, int out_size) {
    (void)in_sizes; (void)n_in; (void)out_size;
    static EncodeFn enc = nullptr;
    if (!enc) {
        void* fn = nullptr;
        cudaDriverEntryPointQueryResult qr;
        cudaGetDriverEntryPoint("cuTensorMapEncodeTiled", &fn, cudaEnableDefault, &qr);
        enc = (EncodeFn)fn;
        cudaFuncSetAttribute(fused_decode_kernel, cudaFuncAttributeMaxDynamicSharedMemorySize, SMEM_BYTES);
    }
    Params p;
    Ptrs q;
    make_map(enc, &p.m_wmod, d_in[10], MODW, D_, 32, 256, CU_TENSOR_MAP_SWIZZLE_64B);
    make_map(enc, &p.m_wq, d_in[3], QD, D_, 64, 128, CU_TENSOR_MAP_SWIZZLE_128B);
    make_map(enc, &p.m_v, d_in[2], DH, 64 * SK, 64, 128, CU_TENSOR_MAP_SWIZZLE_128B);
    {
        cuuint64_t gd[3] = {64, QD, 8}, gs[2] = {D_ * 2, 128};
        cuuint32_t bd[3] = {64, 32, 4}, es[3] = {1, 1, 1};
        enc(&p.m_wo, CU_TENSOR_MAP_DATA_TYPE_BFLOAT16, 3, d_in[4], gd, gs, bd, es, CU_TENSOR_MAP_INTERLEAVE_NONE,
            CU_TENSOR_MAP_SWIZZLE_128B, CU_TENSOR_MAP_L2_PROMOTION_NONE, CU_TENSOR_MAP_FLOAT_OOB_FILL_NONE);
    }
    for (int i = 0; i < 2; i++) {
        cuuint64_t gd[4] = {FF, 2, 8, D_ / 16}, gs[3] = {8 * FF * 2, FF * 2, 16 * FF * 2};
        cuuint32_t bd[4] = {32, 2, 8, 32 / NQ}, es[4] = {1, 1, 1, 1};
        enc(i ? &p.m_w3 : &p.m_w1, CU_TENSOR_MAP_DATA_TYPE_BFLOAT16, 4, d_in[6 + i], gd, gs, bd, es, CU_TENSOR_MAP_INTERLEAVE_NONE,
            CU_TENSOR_MAP_SWIZZLE_64B, CU_TENSOR_MAP_L2_PROMOTION_NONE, CU_TENSOR_MAP_FLOAT_OOB_FILL_NONE);
    }
    {
        cuuint64_t gd[5] = {64, 2, 8, FF / 16, 8}, gs[4] = {8 * D_ * 2, D_ * 2, 16 * D_ * 2, 128};
        cuuint32_t bd[5] = {64, 2, 8, 2, 8 / NW}, es[5] = {1, 1, 1, 1, 1};
        enc(&p.m_w2, CU_TENSOR_MAP_DATA_TYPE_BFLOAT16, 5, d_in[8], gd, gs, bd, es, CU_TENSOR_MAP_INTERLEAVE_NONE,
            CU_TENSOR_MAP_SWIZZLE_128B, CU_TENSOR_MAP_L2_PROMOTION_NONE, CU_TENSOR_MAP_FLOAT_OOB_FILL_NONE);
    }
    make_map(enc, &p.m_gb, d_in[10], MODW, D_, 16, 256, CU_TENSOR_MAP_SWIZZLE_32B);
    q.x = (const __nv_bfloat16*)d_in[0];
    q.kwin = (const __nv_bfloat16*)d_in[1] + (size_t)(SK - WIN) * DH;
    q.c = (const __nv_bfloat16*)d_in[9];
    q.out = (__nv_bfloat16*)d_out;
    fused_decode_kernel<<<NCTA, THREADS, SMEM_BYTES, cudaStreamPerThread>>>(q, p);
}
```

```cpp
#include <cuda_runtime.h>
#include <cuda.h>
#include <cuda_bf16.h>
#include <stdint.h>

namespace {

constexpr int D_ = 512, DH = 128, SK = 16384, WIN = 4096, FF = 1376, QD = 4096, MODW = 3072;
constexpr int NCTA = 128;
constexpr int TILE_BYTES = 16384;
constexpr int NT = 32;
constexpr int STAGES = 13;
constexpr int K_FIRST = 2;
constexpr int FIRST_N = 5;
constexpr int MEET_AT = 16;
constexpr int PACE = 656;
constexpr int LEAD_NS = 1295;
constexpr int GATE_X = 25;
constexpr int POLL_NS = 300;
constexpr int ALPHA16 = 4;
constexpr int GU_NS = 4660;
constexpr int W2_NS = 5875;
constexpr int GB_LEAD = 380;
constexpr int NQ = 8;
constexpr int PROBES = 6;
constexpr int PROBE_NS = 1000;
constexpr int EARLY_NS = 800;
constexpr int NW = 4;
constexpr int HEAD_TID = 256;
constexpr int N_WMOD = 0, N_WQ = 2, N_K = 6, N_V = N_K + NT, N_WO = N_V + NT, N_FFN = N_WO + 4;
constexpr int N_GATE = N_V + GATE_X;
constexpr int THREADS = 320;
constexpr int N_MOD_CTA = 80;
#define SPIN_LIMIT_S "4194304"
constexpr unsigned SPIN_LIMIT = 1u << 22;

constexpr int SM_RING = 0;
constexpr int SM_P = STAGES * TILE_BYTES;
constexpr int SM_PART = SM_P + WIN * 2;
constexpr int SM_OP = SM_PART + 8192;
constexpr int SM_Q = SM_OP + 2048;
constexpr int SM_RED = SM_Q + 256;
constexpr int SM_ML = SM_RED + 128;
constexpr int SM_PROG = SM_ML + 16;
constexpr int SM_SIDE = SM_PROG + 16;
constexpr int SM_BAR = SM_SIDE + 16;
constexpr int BAR_FULL = SM_BAR, BAR_EMPTY = SM_BAR + 8 * STAGES, BAR_XQ = SM_BAR + 16 * STAGES,
              BAR_XML = BAR_XQ + 8, BAR_XP = BAR_XQ + 16, BAR_XO = BAR_XQ + 24, BAR_FFN = BAR_XQ + 32;
constexpr int BAR_W2 = BAR_FFN + 8 * NQ;
constexpr int SMEM_BYTES = BAR_W2 + 8 * NW;
static_assert(SMEM_BYTES <= 232448, "shared memory");
__host__ __device__ constexpr uint32_t slot_addr(int n) { return SM_RING + (n % STAGES) * TILE_BYTES; }
__host__ __device__ constexpr uint32_t full_bar(int n) { return BAR_FULL + 8 * (n % STAGES); }
__host__ __device__ constexpr uint32_t empty_bar(int n) { return BAR_EMPTY + 8 * (n % STAGES); }
__host__ __device__ constexpr uint32_t tile_phase(int n) { return (n / STAGES) & 1; }
static_assert((N_FFN + 4) % STAGES + 2 <= STAGES && N_FFN % STAGES + 4 <= STAGES, "w1/w3 tiles and w2 tiles occupy consecutive slots");
static_assert(GATE_X >= MEET_AT && N_GATE - STAGES < N_V + MEET_AT && N_FFN + 5 - 2 * STAGES < N_V + MEET_AT && N_FFN + 5 - STAGES < N_WO,
              "barrier parities the helper warp waits on are unambiguous after the rendezvous; the wo tiles are not replaced");
__host__ __device__ constexpr int fill_tile(int j) { return j < K_FIRST ? N_K + j : j < K_FIRST + N_K ? j - K_FIRST : j; }

struct Ptrs {
    const __nv_bfloat16 *kwin, *x, *c;
    __nv_bfloat16* out;
};
struct Params {
    CUtensorMap m_wmod, m_wq, m_v, m_wo, m_w1, m_w3, m_w2, m_gb;
};

__device__ unsigned g_epoch;
__device__ __align__(128) uint2 g_mod[2][5 * D_ / 2];
__device__ __align__(256) unsigned char g_s[131072];
__device__ __forceinline__ unsigned long long s_line(int blk, int i) {
    return (((unsigned long long)g_s + 65535) & ~65535ull) + blk * 4096 + (i >> 1) * 1024 + (i & 1) * 256;
}
__device__ __forceinline__ int e1_blk(int r, int w) { return 2 * w + (r ^ (w & 1)); }
constexpr int S_OUT = 512, S_PROG = 128;
__device__ __align__(128) unsigned g_clear;

typedef unsigned long long u64;
__device__ __forceinline__ unsigned time_ns() {
    unsigned r;
    asm volatile("mov.u32 %0, %%globaltimer_lo;" : "=r"(r));
    return r;
}
__device__ __forceinline__ bool elect_one() {
    uint32_t r;
    asm volatile("{\n.reg .pred p;\nelect.sync _|p, 0xffffffff;\nselp.u32 %0, 1, 0, p;\n}" : "=r"(r));
    return r != 0;
}
#define PIN64(v) asm volatile("" : "+l"(v))

__device__ __forceinline__ void mbar_init(uint32_t bar, uint32_t cnt) {
    asm volatile("mbarrier.init.shared::cta.b64 [%0], %1;" :: "r"(bar), "r"(cnt) : "memory");
}
__device__ __forceinline__ void mbar_expect_tx(uint32_t bar, uint32_t bytes) {
    asm volatile("mbarrier.arrive.expect_tx.shared::cta.b64 _, [%0], %1;" :: "r"(bar), "r"(bytes) : "memory");
}
__device__ __forceinline__ void mbar_arrive(uint32_t bar) {
    asm volatile("mbarrier.arrive.shared::cta.b64 _, [%0];" :: "r"(bar) : "memory");
}
__device__ __forceinline__ void mbar_arrive_n(uint32_t bar, uint32_t n) {
    asm volatile("mbarrier.arrive.shared::cta.b64 _, [%0], %1;" :: "r"(bar), "r"(n) : "memory");
}
__device__ __forceinline__ void mbar_wait(uint32_t bar, uint32_t parity) {
    asm volatile("{\n.reg .pred p;\n.reg .u32 n;\nmov.u32 n, 0;\nW0:\n"
                 "mbarrier.try_wait.parity.shared::cta.b64 p, [%0], %1;\n@p bra W1;\n"
                 "add.u32 n, n, 1;\nsetp.lt.u32 p, n, " SPIN_LIMIT_S ";\n@p bra W0;\nW1:\n}"
                 :: "r"(bar), "r"(parity) : "memory");
}
__device__ __forceinline__ void mbar_wait_cluster(uint32_t bar, uint32_t parity) {
    asm volatile("{\n.reg .pred p;\n.reg .u32 n;\nmov.u32 n, 0;\nW0:\n"
                 "mbarrier.try_wait.parity.acquire.cluster.shared::cta.b64 p, [%0], %1;\n@p bra W1;\n"
                 "add.u32 n, n, 1;\nsetp.lt.u32 p, n, " SPIN_LIMIT_S ";\n@p bra W0;\nW1:\n}"
                 :: "r"(bar), "r"(parity) : "memory");
}
__device__ __forceinline__ void bulk_load(uint32_t dst, const void* src, uint32_t bytes, uint32_t bar, uint64_t pol) {
    asm volatile("cp.async.bulk.shared::cluster.global.mbarrier::complete_tx::bytes.L2::cache_hint [%0], [%1], %2, [%3], %4;"
                 :: "r"(dst), "l"(src), "r"(bytes), "r"(bar), "l"(pol) : "memory");
}
__device__ __forceinline__ void tma2d(uint32_t dst, const CUtensorMap* m, int c0, int c1, uint32_t bar) {
    asm volatile("cp.async.bulk.tensor.2d.shared::cluster.global.mbarrier::complete_tx::bytes [%0], [%1, {%3, %4}], [%2];"
                 :: "r"(dst), "l"(m), "r"(bar), "r"(c0), "r"(c1) : "memory");
}
__device__ __forceinline__ void tma2d_hint(uint32_t dst, const CUtensorMap* m, int c0, int c1, uint32_t bar, uint64_t pol) {
    asm volatile("cp.async.bulk.tensor.2d.shared::cluster.global.mbarrier::complete_tx::bytes.L2::cache_hint [%0], [%1, {%3, %4}], [%2], %5;"
                 :: "r"(dst), "l"(m), "r"(bar), "r"(c0), "r"(c1), "l"(pol) : "memory");
}
__device__ __forceinline__ void tma3d(uint32_t dst, const CUtensorMap* m, int c0, int c1, int c2, uint32_t bar) {
    asm volatile("cp.async.bulk.tensor.3d.shared::cluster.global.mbarrier::complete_tx::bytes [%0], [%1, {%3, %4, %5}], [%2];"
                 :: "r"(dst), "l"(m), "r"(bar), "r"(c0), "r"(c1), "r"(c2) : "memory");
}
__device__ __forceinline__ void tma4d(uint32_t dst, const CUtensorMap* m, int c0, int c3, uint32_t bar) {
    asm volatile("cp.async.bulk.tensor.4d.shared::cluster.global.mbarrier::complete_tx::bytes [%0], [%1, {%3, %5, %5, %4}], [%2];"
                 :: "r"(dst), "l"(m), "r"(bar), "r"(c0), "r"(c3), "r"(0) : "memory");
}
__device__ __forceinline__ void tma5d(uint32_t dst, const CUtensorMap* m, int c3, int c4, uint32_t bar) {
    asm volatile("cp.async.bulk.tensor.5d.shared::cluster.global.mbarrier::complete_tx::bytes [%0], [%1, {%5, %5, %5, %3, %4}], [%2];"
                 :: "r"(dst), "l"(m), "r"(bar), "r"(c3), "r"(c4), "r"(0) : "memory");
}
__device__ __forceinline__ uint32_t mapa(uint32_t addr, uint32_t rank) {
    uint32_t r;
    asm("mapa.shared::cluster.u32 %0, %1, %2;" : "=r"(r) : "r"(addr), "r"(rank));
    return r;
}
__device__ __forceinline__ void st_async_b32(uint32_t addr, uint32_t v, uint32_t bar) {
    asm volatile("st.async.weak.shared::cluster.mbarrier::complete_tx::bytes.b32 [%0], %1, [%2];" :: "r"(addr), "r"(v), "r"(bar) : "memory");
}
__device__ __forceinline__ void st_async_v2(uint32_t addr, float a, float b, uint32_t bar) {
    asm volatile("st.async.weak.shared::cluster.mbarrier::complete_tx::bytes.v2.f32 [%0], {%1, %2}, [%3];" :: "r"(addr), "f"(a), "f"(b), "r"(bar) : "memory");
}
__device__ __forceinline__ void st_async_v4(uint32_t addr, uint32_t a, uint32_t b, uint32_t c, uint32_t d, uint32_t bar) {
    asm volatile("st.async.weak.shared::cluster.mbarrier::complete_tx::bytes.v4.b32 [%0], {%1, %2, %3, %4}, [%5];"
                 :: "r"(addr), "r"(a), "r"(b), "r"(c), "r"(d), "r"(bar) : "memory");
}
template <int ID> __device__ __forceinline__ void bar_sync() { asm volatile("bar.sync %0, 288;" :: "n"(ID) : "memory"); }
template <int ID> __device__ __forceinline__ void bar_arrive() { asm volatile("bar.arrive %0, 288;" :: "n"(ID) : "memory"); }
__device__ __forceinline__ void cbar() { asm volatile("bar.sync 1, 256;" ::: "memory"); }

__device__ __forceinline__ uint4 ldg128(const void* p) {
    uint4 v;
    asm volatile("ld.global.nc.v4.u32 {%0,%1,%2,%3}, [%4];" : "=r"(v.x), "=r"(v.y), "=r"(v.z), "=r"(v.w) : "l"(p));
    return v;
}
__device__ __forceinline__ uint32_t ldg16(const void* p) {
    uint16_t v;
    asm volatile("ld.global.nc.u16 %0, [%1];" : "=h"(v) : "l"(p));
    return v;
}
__device__ __forceinline__ uint4 ld_strong128(unsigned long long p) {
    uint4 v;
    asm volatile("ld.relaxed.gpu.global.v4.b32 {%0,%1,%2,%3}, [%4];" : "=r"(v.x), "=r"(v.y), "=r"(v.z), "=r"(v.w) : "l"(p) : "memory");
    return v;
}
__device__ __forceinline__ uint2 ld_strong64(unsigned long long p) {
    uint2 v;
    asm volatile("ld.relaxed.gpu.global.v2.b32 {%0,%1}, [%2];" : "=r"(v.x), "=r"(v.y) : "l"(p) : "memory");
    return v;
}
__device__ __forceinline__ uint32_t ldg32(const void* p) {
    uint32_t v;
    asm volatile("ld.global.nc.u32 %0, [%1];" : "=r"(v) : "l"(p));
    return v;
}
struct Pkt2 { u64 a, b; };
__device__ __forceinline__ uint32_t lo32(u64 v) { return (uint32_t)v; }
__device__ __forceinline__ uint32_t hi32(u64 v) { return (uint32_t)(v >> 32); }
__device__ __forceinline__ Pkt2 ld_pkt2(const void* p) {
    Pkt2 r;
    asm volatile("ld.relaxed.gpu.global.v2.b64 {%0,%1}, [%2];" : "=l"(r.a), "=l"(r.b) : "l"(p) : "memory");
    return r;
}
__device__ __forceinline__ bool pkt_ok(const Pkt2& r, uint32_t tag) { return hi32(r.a) == tag && hi32(r.b) == tag; }
__device__ __forceinline__ void st_pkt(u64 p, uint32_t data, uint32_t tag) {
    asm volatile("{\n.reg .b64 v;\nmov.b64 v, {%1, %2};\nst.relaxed.gpu.global.b64 [%0], v;\n}" :: "l"(p), "r"(data), "r"(tag) : "memory");
}
__device__ __forceinline__ uint4 lds128(uint32_t a) {
    uint4 v;
    asm volatile("ld.shared.v4.u32 {%0,%1,%2,%3}, [%4];" : "=r"(v.x), "=r"(v.y), "=r"(v.z), "=r"(v.w) : "r"(a) : "memory");
    return v;
}
__device__ __forceinline__ float4 lds128f(uint32_t a) {
    float4 v;
    asm volatile("ld.shared.v4.f32 {%0,%1,%2,%3}, [%4];" : "=f"(v.x), "=f"(v.y), "=f"(v.z), "=f"(v.w) : "r"(a) : "memory");
    return v;
}
__device__ __forceinline__ uint2 lds64(uint32_t a) {
    uint2 v;
    asm volatile("ld.shared.v2.u32 {%0,%1}, [%2];" : "=r"(v.x), "=r"(v.y) : "r"(a) : "memory");
    return v;
}
__device__ __forceinline__ float2 lds64f(uint32_t a) {
    float2 v;
    asm volatile("ld.shared.v2.f32 {%0,%1}, [%2];" : "=f"(v.x), "=f"(v.y) : "r"(a) : "memory");
    return v;
}
__device__ __forceinline__ float lds32f(uint32_t a) {
    float v;
    asm volatile("ld.shared.f32 %0, [%1];" : "=f"(v) : "r"(a) : "memory");
    return v;
}
__device__ __forceinline__ void sts64f(uint32_t a, float x, float y) {
    asm volatile("st.shared.v2.f32 [%0], {%1,%2};" :: "r"(a), "f"(x), "f"(y) : "memory");
}
__device__ __forceinline__ void sts128f(uint32_t a, float x, float y, float z, float w) {
    asm volatile("st.shared.v4.f32 [%0], {%1,%2,%3,%4};" :: "r"(a), "f"(x), "f"(y), "f"(z), "f"(w) : "memory");
}
__device__ __forceinline__ void sts32f(uint32_t a, float x) {
    asm volatile("st.shared.f32 [%0], %1;" :: "r"(a), "f"(x) : "memory");
}
__device__ __forceinline__ void sts128(uint32_t a, uint32_t x, uint32_t y, uint32_t z, uint32_t w) {
    asm volatile("st.shared.v4.u32 [%0], {%1,%2,%3,%4};" :: "r"(a), "r"(x), "r"(y), "r"(z), "r"(w) : "memory");
}
__device__ __forceinline__ void settle(uint32_t tag, uint32_t a, uint32_t x, uint32_t y, uint32_t z, uint32_t w) {
    asm volatile("{\n.reg .pred p;\nsetp.eq.u32 p, %0, 0;\n@p st.shared.v4.u32 [%1], {%2,%3,%4,%5};\n}" :: "r"(tag), "r"(a), "r"(x), "r"(y), "r"(z), "r"(w) : "memory");
}
__device__ __forceinline__ void settle(uint32_t tag, uint32_t a, const float4& v) {
    settle(tag, a, __float_as_uint(v.x), __float_as_uint(v.y), __float_as_uint(v.z), __float_as_uint(v.w));
}
__device__ __forceinline__ void sts16(uint32_t a, uint32_t x) {
    asm volatile("st.shared.u16 [%0], %1;" :: "r"(a), "h"((uint16_t)x) : "memory");
}
__device__ __forceinline__ void ldsm4t(uint32_t a, uint32_t (&r)[4]) {
    asm volatile("ldmatrix.sync.aligned.m8n8.x4.trans.shared.b16 {%0,%1,%2,%3}, [%4];"
                 : "=r"(r[0]), "=r"(r[1]), "=r"(r[2]), "=r"(r[3]) : "r"(a) : "memory");
}
__device__ __forceinline__ void mma(float (&c)[4], uint32_t a0, uint32_t a1, uint32_t a2, uint32_t a3, uint32_t b0, uint32_t b1) {
    asm volatile("mma.sync.aligned.m16n8k16.row.col.f32.bf16.bf16.f32 {%0,%1,%2,%3}, {%4,%5,%6,%7}, {%8,%9}, {%0,%1,%2,%3};"
                 : "+f"(c[0]), "+f"(c[1]), "+f"(c[2]), "+f"(c[3]) : "r"(a0), "r"(a1), "r"(a2), "r"(a3), "r"(b0), "r"(b1));
}
__device__ __forceinline__ void mma4(float (&c)[4], const uint32_t (&a)[4], uint32_t b0, uint32_t b1) { mma(c, a[0], a[1], a[2], a[3], b0, b1); }
__device__ __forceinline__ float sel(uint32_t c, float a, float b) {
    float r;
    asm("{\n.reg .pred p;\nsetp.ne.u32 p, %3, 0;\nselp.f32 %0, %1, %2, p;\n}" : "=f"(r) : "f"(a), "f"(b), "r"(c));
    return r;
}
__device__ __forceinline__ float bf_lo(uint32_t v) { return __uint_as_float(v << 16); }
__device__ __forceinline__ float bf_hi(uint32_t v) { return __uint_as_float(v & 0xffff0000u); }
__device__ __forceinline__ uint32_t pack2(float lo, float hi) {
    uint32_t r;
    asm("cvt.rn.bf16x2.f32 %0, %1, %2;" : "=r"(r) : "f"(hi), "f"(lo));
    return r;
}
__device__ __forceinline__ float rbf(float x) { return __uint_as_float(pack2(0.f, x)); }
__device__ __forceinline__ uint32_t hadd2(uint32_t a, uint32_t b) { uint32_t r; asm("add.rn.bf16x2 %0, %1, %2;" : "=r"(r) : "r"(a), "r"(b)); return r; }
__device__ __forceinline__ uint32_t hsub2(uint32_t a, uint32_t b) { uint32_t r; asm("sub.rn.bf16x2 %0, %1, %2;" : "=r"(r) : "r"(a), "r"(b)); return r; }
__device__ __forceinline__ uint32_t hmul2(uint32_t a, uint32_t b) { uint32_t r; asm("mul.rn.bf16x2 %0, %1, %2;" : "=r"(r) : "r"(a), "r"(b)); return r; }
__device__ __forceinline__ uint32_t hfma2(uint32_t a, uint32_t b, uint32_t c) { uint32_t r; asm("fma.rn.bf16x2 %0, %1, %2, %3;" : "=r"(r) : "r"(a), "r"(b), "r"(c)); return r; }
__device__ __forceinline__ uint32_t selu(uint32_t c, uint32_t a, uint32_t b) { return __float_as_uint(sel(c, __uint_as_float(a), __uint_as_float(b))); }
constexpr uint32_t ONE2 = 0x3f803f80u;
__device__ __forceinline__ float sigmoid_f(float x) {
    float e, r;
    asm("ex2.approx.ftz.f32 %0, %1;" : "=f"(e) : "f"(x * -1.4426950408889634f));
    asm("rcp.approx.ftz.f32 %0, %1;" : "=f"(r) : "f"(1.0f + e));
    return r;
}
__device__ __forceinline__ float silu_f(float x) { return x * sigmoid_f(x); }
__device__ __forceinline__ float rcp_sd(float m2) {
    float s, r;
    asm("sqrt.approx.ftz.f32 %0, %1;" : "=f"(s) : "f"(rbf(rbf(m2 * (1.0f / D_)) + 1e-5f)));
    asm("rcp.approx.ftz.f32 %0, %1;" : "=f"(r) : "f"(rbf(s)));
    return r;
}
__device__ __forceinline__ uint32_t ln_mod2(uint32_t x, uint32_t mean2, float rsd, uint32_t c1, uint32_t sh) {
    const uint32_t d = hsub2(x, mean2);
    return hadd2(hmul2(pack2(bf_lo(d) * rsd, bf_hi(d) * rsd), c1), sh);
}
__device__ __forceinline__ int pair_pos(int j) { return 2 * (j & 3) + (j >> 2); }

__global__ void __cluster_dims__(2, 1, 1) __launch_bounds__(THREADS, 1)
fused_decode_kernel(const __grid_constant__ Ptrs q_, const __grid_constant__ Params p) {
    extern __shared__ __align__(1024) unsigned char smem[];
    unsigned t_top;
    asm volatile("mov.u32 %0, %%globaltimer_lo;" : "=r"(t_top));
    const int tid = threadIdx.x;
    uint32_t z0;
    asm("and.b32 %0, %1, 1024;" : "=r"(z0) : "r"(tid));
    const char* kw = *(const char* const*)((const char*)&q_.kwin + z0);
    const uint32_t sb = (uint32_t)__cvta_generic_to_shared(smem);
    auto place = [](int cl) { return cl < 4 ? 8 * cl + 39 : cl - 4 + max((cl * 37 - 36 * 37) >> 8, 0); };
    uint32_t z2;
    asm("and.b32 %0, %1, 2048;" : "=r"(z2) : "r"(tid));
    const int cv = blockIdx.x + z2, pw = place(cv >> 1);
    static_assert(SK * DH * 2 == 1 << 22 && TILE_BYTES == 1 << 14, "koff");
    const char* kp;
    auto set_kp = [&](uint32_t off) {
        asm volatile("{\n.reg .u32 lo, hi;\nmov.b64 {lo, hi}, %1;\nadd.cc.u32 lo, lo, %2;\naddc.u32 hi, hi, 0;\nmov.b64 %0, {lo, hi};\n}"
                     : "=l"(kp) : "l"(kw), "r"(off));
    };
    uint64_t pol;
    asm("createpolicy.fractional.L2::evict_first.b64 %0, 1.0;" : "=l"(pol));
    auto fill_k = [&](int n) {
        mbar_expect_tx(sb + full_bar(n), TILE_BYTES);
        bulk_load(sb + slot_addr(n), kp + (n - N_K) * 2 * TILE_BYTES, TILE_BYTES, sb + full_bar(n), pol);
    };
    static_assert(K_FIRST >= 1, "head block starts with K tile 0");
    if (tid + (sb >> 28) == HEAD_TID) {
        mbar_init(sb + full_bar(N_K), 1);
        set_kp(((pw & 7) << 22) | ((pw & 8) << 24) | ((pw & 48) << 21) | ((cv & 1) << 14));
        bulk_load(sb + slot_addr(N_K), kp, TILE_BYTES, sb + full_bar(N_K), pol);
        mbar_expect_tx(sb + full_bar(N_K), TILE_BYTES);
#pragma unroll
        for (int j = 1; j < K_FIRST; j++) { mbar_init(sb + full_bar(N_K + j), 1); fill_k(N_K + j); }
    }
    __syncwarp();
    const int cta = blockIdx.x, rank = cta & 1, pv = place(cta >> 1);
    const int b = (pv >> 3) & 1, h = (pv & 7) | ((pv >> 1) & 24), bh = 32 * b + h;
    const int mc = 2 * pv + rank;
    auto first_fill = [&](int j) {
        const int n = fill_tile(j);
        if (n >= N_K) {
            fill_k(n);
        } else if (n >= N_WQ) {
            mbar_expect_tx(sb + full_bar(n), TILE_BYTES);
            tma2d(sb + slot_addr(n), &p.m_wq, h * DH + 64 * rank, 128 * (n - N_WQ), sb + full_bar(n));
        } else if (mc < N_MOD_CTA) {
            mbar_expect_tx(sb + full_bar(n), TILE_BYTES);
            tma2d(sb + slot_addr(n), &p.m_wmod, 32 * mc, 256 * n, sb + full_bar(n));
        } else {
            mbar_arrive(sb + full_bar(n));
        }
    };
    if (tid == HEAD_TID) {
#pragma unroll
        for (int j = K_FIRST; j < FIRST_N; j++) mbar_init(sb + full_bar(fill_tile(j)), 1);
#pragma unroll
        for (int j = K_FIRST; j < FIRST_N; j++) first_fill(j);
        asm volatile("fence.mbarrier_init.release.cluster;" ::: "memory");
    }
    __syncwarp();
    const int role = cta / 3;
    const bool is_gu = cta == 3 * role, is_gb = cta == 3 * role + 1 && role < 32;
    if (tid >= 288) {
        const unsigned t_start = t_top;
        asm volatile("barrier.cluster.arrive.relaxed.aligned;" ::: "memory");
        unsigned tag;
        asm volatile("ld.relaxed.gpu.global.u32 %0, [%1];" : "=r"(tag) : "l"(&g_epoch) : "memory");
        tag += 1;
        if (cta == NCTA - 1) {
#pragma unroll 2
            for (int i = tid - 288; i < 128 * 8; i += 32) {
                uint4* q = reinterpret_cast<uint4*>(s_line(i >> 6, (i >> 3) & 7)) + (i & 7);
                const uint32_t v = (i & 48) == 48 ? ~0u : 0u;
                q[0] = make_uint4(v, v, v, v);
                q[8] = q[32] = q[40] = make_uint4(0u, 0u, 0u, 0u);
            }
            __syncwarp();
            asm volatile("fence.acq_rel.gpu;" ::: "memory");
            if (tid == 288) asm volatile("st.relaxed.gpu.global.u32 [%0], %1;" :: "l"(&g_clear), "r"(tag) : "memory");
        }
        asm volatile("barrier.cluster.wait.acquire.aligned;" ::: "memory");
        mbar_wait_cluster(sb + BAR_XQ, 0);
#pragma unroll 1
        for (uint32_t n = 0; n < SPIN_LIMIT; n++) {
            unsigned c;
            asm volatile("ld.relaxed.gpu.global.u32 %0, [%1];" : "=r"(c) : "l"(&g_clear) : "memory");
            if (c == tag) break;
        }
        asm volatile("fence.acq_rel.gpu;" ::: "memory");
        asm volatile("st.volatile.shared.u32 [%0], %1;" :: "r"(sb + SM_SIDE), "r"(0) : "memory");
        asm volatile("bar.sync 2, 288;" ::: "memory");
        if (elect_one()) {
            asm volatile("prefetch.tensormap [%0];" :: "l"(is_gu ? &p.m_w1 : &p.m_gb) : "memory");
            asm volatile("prefetch.tensormap [%0];" :: "l"(&p.m_w3) : "memory");
            asm volatile("prefetch.tensormap [%0];" :: "l"(&p.m_w2) : "memory");
            const int issue = ((4 * N_GATE - 11) * PACE >> 2) - LEAD_NS;
            unsigned now, c = 0, best[2] = {~0u, ~0u}, np = is_gu ? 0 : PROBES;
            auto probe = [&]() {
                const int k = np >> 1, i = (role >> 3) + 2 * k;
                const u64 a = (s_line(e1_blk(0, role & 7), i < 6 ? i : i - 6) + (k ? 512 * k - 384 : 0)) ^ ((np & 1) << 12);
                unsigned v, c0, c1 = 0;
                asm volatile("mov.u32 %0, %%clock;" : "=r"(c0));
                asm volatile("ld.relaxed.gpu.global.u32 %0, [%1];" : "=r"(v) : "l"(a) : "memory");
                asm volatile("{\n.reg .pred p;\nsetp.ne.u32 p, %1, 0xffffffff;\n@p mov.u32 %0, %%clock;\n}" : "+r"(c1) : "r"(v));
                if (np & 1) best[1] = min(best[1], c1 - c0); else best[0] = min(best[0], c1 - c0);
                np++;
                if (!(np & 1)) asm volatile("st.volatile.shared.u32 [%0], %1;" :: "r"(sb + SM_SIDE), "r"(best[0] <= best[1] ? 0 : 4096) : "memory");
            };
#pragma unroll 1
            while (np < PROBES) {
                now = time_ns();
                if ((int)(now - t_start) >= issue + EARLY_NS) break;
                probe();
            }
            mbar_wait(sb + full_bar(N_GATE), tile_phase(N_GATE));
            now = time_ns();
            const unsigned ref = t_start & ~0x3ffffu, mine = (1u << 24) + min((now - ref) >> 2, 100000u);
            const int own = now - t_start;
            const u64 prog = s_line(0, 7) + S_PROG;
            asm volatile("red.relaxed.gpu.global.add.u32 [%0], %1;" :: "l"(prog), "r"(mine) : "memory");
            if (is_gu || is_gb) {
#pragma unroll
                for (int i = 0; i < 6; i++) mbar_wait(sb + empty_bar(N_FFN + i), tile_phase(N_FFN + i) ^ 1);
#pragma unroll
                for (int i = 0; i < NQ; i++) mbar_expect_tx(sb + BAR_FFN + 8 * i, is_gu ? 65536 / NQ : 8192);
#pragma unroll
                for (int i = 0; i < NW; i++) mbar_expect_tx(sb + BAR_W2 + 8 * i, 32768 / NW);
                unsigned due = 0, next = now;
                constexpr unsigned full = (unsigned)NCTA << 24;
                asm volatile("st.volatile.shared.u32 [%0], %1;" :: "r"(sb + SM_PROG), "r"(mine) : "memory");
#pragma unroll 1
                for (uint32_t n = 0; n < 4096; n++) {
                    unsigned v;
                    asm volatile("ld.volatile.shared.u32 %0, [%1];" : "=r"(v) : "r"(sb + SM_PROG) : "memory");
                    if (v > c) {
                        c = v;
                        int arr = (int)__fdividef((float)(c & 0xffffffu) * 4.0f, (float)(c >> 24)) - (int)(t_start - ref);
                        if (abs(arr - own) > 2000) arr = own;
                        due = arr - ((arr - issue) * ALPHA16 >> 4) + (is_gb ? W2_NS - GB_LEAD : GU_NS);
                    }
                    now = time_ns();
                    if (now - t_start + PROBE_NS >= due) np = PROBES;
                    if ((c >= full && np == PROBES) || now - t_start >= due) break;
                    if ((int)(now - next) >= 0 && c < full) {
                        asm volatile("cp.async.cg.shared.global [%0], [%1], 16;" :: "r"(sb + SM_PROG), "l"(prog) : "memory");
                        next = now + POLL_NS;
                    }
                    if (np < PROBES) probe();
                }
#pragma unroll 1
                for (uint32_t n = 0; n < 1024 && now - t_start < due; n++) now = time_ns();
                if (is_gu) {
#pragma unroll
                    for (int i = 0; i < 2 * NQ; i++) {
                        const int q = i >> 1, r0 = q * (512 / NQ);
                        tma4d(sb + slot_addr(N_FFN) + (r0 >> 8) * 2 * TILE_BYTES + (i & 1) * TILE_BYTES + (r0 & 255) * 64, (i & 1) ? &p.m_w3 : &p.m_w1, 32 * role, r0 / 16, sb + BAR_FFN + 8 * q);
                    }
#pragma unroll 1
                    for (uint32_t n = 0; n < 1024 && now - t_start < due + (W2_NS - GU_NS); n++) now = time_ns();
                    const int f = best[0] <= best[1] ? NW / 2 : 0;
#pragma unroll
                    for (int i = 0; i < NW; i++) tma5d(sb + slot_addr(N_FFN + 4) + (i ^ f) * (32768 / NW), &p.m_w2, 2 * role, (i ^ f) * (8 / NW), sb + BAR_W2 + 8 * (i ^ f));
                } else {
                    tma2d(sb + slot_addr(N_FFN), &p.m_gb, 5 * D_ + 16 * role, 0, sb + BAR_FFN);
                    tma2d(sb + slot_addr(N_FFN) + 8192, &p.m_gb, 5 * D_ + 16 * role, 256, sb + BAR_FFN + 8);
                }
                asm volatile("cp.async.wait_all;" ::: "memory");
            }
        }
        __syncwarp();
        if (is_gu) {
            const int lane = tid & 31;
            auto sum8 = [&](uint32_t a, int stride) {
                float4 u[8];
#pragma unroll
                for (int i = 0; i < 8; i++) u[i] = lds128f(a + i * stride);
                return make_float4(((u[0].x + u[1].x) + (u[2].x + u[3].x)) + ((u[4].x + u[5].x) + (u[6].x + u[7].x)),
                                   ((u[0].y + u[1].y) + (u[2].y + u[3].y)) + ((u[4].y + u[5].y) + (u[6].y + u[7].y)),
                                   ((u[0].z + u[1].z) + (u[2].z + u[3].z)) + ((u[4].z + u[5].z) + (u[6].z + u[7].z)),
                                   ((u[0].w + u[1].w) + (u[2].w + u[3].w)) + ((u[4].w + u[5].w) + (u[6].w + u[7].w)));
            };
            uint32_t h_st = sb + SM_Q + (((lane & 1) * 4 + ((lane >> 2) & 3)) * 4 + (lane & 2) + (lane >> 4)) * 4;
            bar_sync<3>();
            const float4 C = sum8(sb + SM_P + lane * 16, 1024), S = sum8(sb + SM_P + 512 + lane * 16, 1024);
            const uint32_t st_ld = sb + SM_RED + (lane & 1) * 64;
            settle(tag, sb + SM_OP, C); settle(tag, sb + SM_OP, S); settle(tag, sb + SM_OP, h_st, st_ld, 0, 0);
            bar_sync<4>();
            const float4 r0 = lds128f(st_ld), r1 = lds128f(st_ld + 16), r2 = lds128f(st_ld + 32), r3 = lds128f(st_ld + 48);
            const float4 Y = sum8(sb + SM_PART + lane * 16, 512);
            const float e1 = r0.z - r0.x, e2 = r1.x - r0.x, e3 = r1.z - r0.x, e4 = r2.x - r0.x, e5 = r2.z - r0.x, e6 = r3.x - r0.x, e7 = r3.z - r0.x;
            const float se = ((e1 + e2) + (e3 + e4)) + ((e5 + e6) + e7);
            const float ee = (fmaf(e1, e1, e2 * e2) + fmaf(e3, e3, e4 * e4)) + fmaf(e5, e5, fmaf(e6, e6, e7 * e7));
            const float sq = ((r0.y + r0.w) + (r1.y + r1.w)) + ((r2.y + r2.w) + (r3.y + r3.w));
            float rsd;
            asm("rsqrt.approx.ftz.f32 %0, %1;" : "=f"(rsd) : "f"(fmaf(fmaf(se * (-1.0f / D_), se, fmaf(ee, 1.0f / 64, sq)), 1.0f / D_, 1e-5f)));
            const float mu = -rbf(fmaf(r0.x, 8.0f, se) * (1.0f / D_));
            const float g0 = fmaf(rsd, fmaf(mu, C.x, Y.x), S.x), g1 = fmaf(rsd, fmaf(mu, C.z, Y.z), S.z);
            const float u0 = fmaf(rsd, fmaf(mu, C.y, Y.y), S.y), u1 = fmaf(rsd, fmaf(mu, C.w, Y.w), S.w);
            const uint32_t hv = pack2(silu_f(g0) * u0, silu_f(g1) * u1);
            sts32f(h_st, __uint_as_float(hv));
            bar_arrive<5>();
            if (role == 0 && lane == 0) g_epoch = tag;
        }
        return;
    }
    if (tid >= 256) {
        set_kp(bh * (SK * DH * 2) + rank * TILE_BYTES);
        const unsigned t_start = t_top;
        auto pace = [&](int q4) {
            const int due = (q4 * PACE >> 2) - LEAD_NS;
            unsigned now, n = 0;
            do { now = time_ns(); } while ((int)(now - t_start) < due && ++n < 256);
        };
        if (tid == 256) {
#pragma unroll
            for (int j = FIRST_N; j < STAGES; j++) mbar_init(sb + full_bar(fill_tile(j)), 1);
#pragma unroll
            for (int s = 0; s < STAGES; s++) mbar_init(sb + BAR_EMPTY + 8 * s, 8);
            mbar_init(sb + BAR_XQ, 1); mbar_init(sb + BAR_XML, 1); mbar_init(sb + BAR_XP, 1); mbar_init(sb + BAR_XO, 1);
#pragma unroll
            for (int i = 0; i < NQ + NW; i++) mbar_init(sb + BAR_FFN + 8 * i, 1);
            mbar_expect_tx(sb + BAR_XQ, 256); mbar_expect_tx(sb + BAR_XML, 8); mbar_expect_tx(sb + BAR_XP, WIN); mbar_expect_tx(sb + BAR_XO, 1024);
            asm volatile("fence.mbarrier_init.release.cluster;" ::: "memory");
            asm volatile("fence.proxy.async.shared::cta;" ::: "memory");
        }
        __syncwarp();
        asm volatile("barrier.cluster.arrive.relaxed.aligned;" ::: "memory");
        if (elect_one()) {
#pragma unroll
            for (int j = FIRST_N; j < STAGES; j++) {
                pace(j <= K_FIRST ? 4 * j : j <= K_FIRST + 2 ? 4 * K_FIRST + 5 * (j - K_FIRST) / 2 :
                     j <= K_FIRST + 6 ? 4 * K_FIRST + 5 + 2 * (j - K_FIRST - 2) : 4 * j - 11);
                first_fill(j);
            }
        }
        __syncwarp();
        asm volatile("barrier.cluster.wait.acquire.aligned;" ::: "memory");
        if (elect_one()) {
            asm volatile("prefetch.tensormap [%0];" :: "l"(&p.m_v) : "memory");
            asm volatile("prefetch.tensormap [%0];" :: "l"(&p.m_wo) : "memory");
            int s = 0, ph = 0;
#pragma unroll 1
            for (int n = STAGES; n < N_FFN; n++) {
                const uint32_t dst = sb + SM_RING + s * TILE_BYTES, bar = sb + BAR_FULL + 8 * s;
                mbar_wait(sb + BAR_EMPTY + 8 * s, ph);
                mbar_expect_tx(bar, TILE_BYTES);
                pace(n < N_WO ? 4 * n - 11 : 2 * (N_WO + n) - 11);
                if (n < N_V) bulk_load(dst, kp + (n - N_K) * 2 * TILE_BYTES, TILE_BYTES, bar, pol);
                else if (n < N_WO) tma2d_hint(dst, &p.m_v, 64 * rank, bh * SK + (SK - WIN) + 128 * (n - N_V), bar, pol);
                else tma3d(dst, &p.m_wo, 0, h * DH + 32 * (n - N_WO), 4 * rank, bar);
                if (++s == STAGES) { s = 0; ph ^= 1; }
            }
        }
        return;
    }

    const unsigned t_c = t_top;
    const int lane = tid & 31, w = tid >> 5, g = lane >> 2, t = lane & 3;
    const int hgrp = 4 * w + (g & 3);
    const int vb = g >> 2;
    const uint32_t cv0 = ldg32(q_.c + vb * D_ + 16 * hgrp + 2 * t), cv1 = ldg32(q_.c + vb * D_ + 16 * hgrp + 8 + 2 * t);
    unsigned tag;
    asm volatile("ld.relaxed.gpu.global.u32 %0, [%1];" : "=r"(tag) : "l"(&g_epoch) : "memory");
    const uint4 xa = ldg128(q_.x + b * D_ + 16 * lane), xb = ldg128(q_.x + b * D_ + 16 * lane + 8);
    const uint32_t xh0 = ldg32(q_.x + b * D_ + 16 * hgrp + 2 * t), xh1 = ldg32(q_.x + b * D_ + 16 * hgrp + 8 + 2 * t);
    asm volatile("barrier.cluster.arrive.relaxed.aligned;" ::: "memory");
#pragma unroll 1
    for (uint32_t n = t_c; n < 2; n++) asm volatile("nanosleep.u32 1;" ::: "memory");
    const int grp = w >> 2, sub = w & 3;
    const int lrow = (lane & 7) + 8 * (lane >> 4);
    const int lch = (lane >> 3) & 1;
    const int ob = lane >> 4;
    const uint32_t t1 = t & 1, t2 = t & 2;
    const int gsrc = 16 * (g & 1) + t;
    const uint32_t sw128 = lrow * 128 + ((lch ^ (lrow & 7)) << 4);
    uint32_t A[16][4];

    const uint32_t sc0 = pack2(silu_f(bf_lo(cv0)), silu_f(bf_hi(cv0))), sc1 = pack2(silu_f(bf_lo(cv1)), silu_f(bf_hi(cv1)));
    tag += 1;
    asm volatile("barrier.cluster.wait.acquire.aligned;" ::: "memory");
    mbar_wait(sb + BAR_FULL + 8 * (N_WMOD + grp), 0);
    if (mc < N_MOD_CTA) {
        const uint32_t tb = sb + SM_RING + (N_WMOD + grp) * TILE_BYTES + (64 * sub + lrow) * 64;
#pragma unroll
        for (int i = 0; i < 8; i++)
            ldsm4t(tb + (i >> 1) * 1024 + (((2 * (i & 1) + lch) ^ ((lrow >> 1) & 3)) << 4), A[i]);
        float acc[2][4] = {{0.f, 0.f, 0.f, 0.f}, {0.f, 0.f, 0.f, 0.f}};
#pragma unroll
        for (int s = 0; s < 4; s++) {
            const uint32_t b0 = __shfl_sync(~0u, sc0, 4 * s + gsrc), b1 = __shfl_sync(~0u, sc1, 4 * s + gsrc);
            mma4(acc[0], A[2 * s], b0, b1);
            mma4(acc[1], A[2 * s + 1], b0, b1);
        }
        sts32f(sb + SM_P + (w * 64 + 8 * t + g) * 4, sel(t2, sel(t1, acc[1][2], acc[1][0]), sel(t1, acc[0][2], acc[0][0])));
        sts32f(sb + SM_P + (w * 64 + 32 + 8 * t + g) * 4, sel(t2, sel(t1, acc[1][3], acc[1][1]), sel(t1, acc[0][3], acc[0][1])));
        cbar();
        if (w == 0) {
            const bool adj = mc < 32;
            const uint32_t a0 = sb + SM_P + (adj ? 2 * lane : ob * 32 + (lane & 1) * 16 + ((lane >> 1) & 7)) * 4, a1 = a0 + (adj ? 4 : 32);
            float2 sum = make_float2(0.f, 0.f);
#pragma unroll
            for (int i = 0; i < 8; i++) { sum.x += lds32f(a0 + i * 256); sum.y += lds32f(a1 + i * 256); }
            st_pkt((u64)&g_mod[ob][16 * mc + (adj ? (lane & 8) + pair_pos(lane & 7) : lane & 15)], pack2(sum.x, sum.y), tag);
        }
    }
    __syncwarp();
    if (lane == 0) mbar_arrive_n(sb + BAR_EMPTY + 8 * (N_WMOD + grp), 2);

    {
        const uint2* mp = &g_mod[b][vb * 256 + 8 * hgrp + 2 * t];
        const uint32_t ms = sb + SM_PART + tid * 16;
        auto fetch_mod = [&](uint32_t k) {
            asm volatile("cp.async.cg.shared.global [%0], [%1], 16;\ncp.async.commit_group;" :: "r"(ms + k), "l"(mp) : "memory");
        };
        fetch_mod(0);
        float xs[16] = {bf_lo(xa.x), bf_hi(xa.x), bf_lo(xa.y), bf_hi(xa.y), bf_lo(xa.z), bf_hi(xa.z), bf_lo(xa.w), bf_hi(xa.w),
                        bf_lo(xb.x), bf_hi(xb.x), bf_lo(xb.y), bf_hi(xb.y), bf_lo(xb.z), bf_hi(xb.z), bf_lo(xb.w), bf_hi(xb.w)};
        float s = 0.f;
#pragma unroll
        for (int i = 0; i < 16; i++) s += xs[i];
#pragma unroll
        for (int m = 1; m < 32; m <<= 1) s += __shfl_xor_sync(~0u, s, m);
        const float mean = s * (1.0f / D_);
        float q = 0.f;
#pragma unroll
        for (int i = 0; i < 16; i++) q += (xs[i] - mean) * (xs[i] - mean);
#pragma unroll
        for (int m = 1; m < 32; m <<= 1) q += __shfl_xor_sync(~0u, q, m);
        const uint32_t mean2 = pack2(mean, mean);
        const float rsd = rcp_sd(q);

        mbar_wait(sb + BAR_FULL + 8 * (N_WQ + (w >> 1)), 0);
        const uint32_t tb = sb + SM_RING + (N_WQ + (w >> 1)) * TILE_BYTES + (w & 1) * 8192;
#pragma unroll
        for (int i = 0; i < 16; i++) ldsm4t(tb + (i >> 2) * 2048 + (sw128 ^ ((i & 3) * 32)), A[i]);
        __syncwarp();
        if (lane == 0) mbar_arrive_n(sb + BAR_EMPTY + 8 * (N_WQ + (w >> 1)), 4);

        Pkt2 m;
        for (uint32_t n = 0, k = 0; n < SPIN_LIMIT; n++) {
            fetch_mod(k ^ 4096);
            asm volatile("cp.async.wait_group 1;" ::: "memory");
            const uint4 u = lds128(ms + k);
            m.a = u.x | (u64)u.y << 32; m.b = u.z | (u64)u.w << 32;
            if (__all_sync(~0u, pkt_ok(m, tag))) break;
            k ^= 4096;
        }
        const uint32_t ca0 = __shfl_xor_sync(~0u, lo32(m.a), 16), ca1 = __shfl_xor_sync(~0u, lo32(m.b), 16);
        const uint32_t v0 = ln_mod2(xh0, mean2, rsd, hadd2(ONE2, ca0), lo32(m.a));
        const uint32_t v1 = ln_mod2(xh1, mean2, rsd, hadd2(ONE2, ca1), lo32(m.b));
        float acc[4][4];
#pragma unroll
        for (int i = 0; i < 4; i++) { acc[i][0] = acc[i][1] = acc[i][2] = acc[i][3] = 0.f; }
#pragma unroll
        for (int s4 = 0; s4 < 4; s4++) {
            const uint32_t b0 = __shfl_sync(~0u, v0, 4 * s4 + t), b1 = __shfl_sync(~0u, v1, 4 * s4 + t);
#pragma unroll
            for (int i = 0; i < 4; i++) mma4(acc[i], A[4 * s4 + i], b0, b1);
        }
        sts32f(sb + SM_OP + (w * 64 + 16 * t + g) * 4, sel(t2, sel(t1, acc[3][0], acc[2][0]), sel(t1, acc[1][0], acc[0][0])));
        sts32f(sb + SM_OP + (w * 64 + 16 * t + 8 + g) * 4, sel(t2, sel(t1, acc[3][2], acc[2][2]), sel(t1, acc[1][2], acc[0][2])));
        cbar();
        if (w == 0) {
            float2 sum = make_float2(0.f, 0.f);
#pragma unroll
            for (int i = 0; i < 8; i++) { const float2 u = lds64f(sb + SM_OP + (i * 64 + 2 * lane) * 4); sum.x += u.x; sum.y += u.y; }
            const uint32_t v = pack2(sum.x, sum.y), a = sb + SM_Q + rank * 128 + lane * 4;
            st_async_b32(mapa(a, rank ^ 1), v, mapa(sb + BAR_XQ, rank ^ 1));
            st_async_b32(mapa(a, rank), v, mapa(sb + BAR_XQ, rank));
        }
        mbar_wait_cluster(sb + BAR_XQ, 0);
    }

    Pkt2 mga, msb, mcb;
    uint32_t tx0, tx1;
    const uint2* tmp = &g_mod[ob][32 * w + 2 * (lane & 15)];
    {
        uint4 Q[4];
        uint32_t koff[4];
#pragma unroll
        for (int i = 0; i < 4; i++) {
            const int ch = t + 4 * (i ^ (g & 1));
            Q[i] = lds128(sb + SM_Q + ch * 16);
            koff[i] = (sub * 16 + g) * 256 + ch * 16;
        }
        float mx = -INFINITY;
        int stage = N_K + grp, phase = 0;
#pragma unroll 1
        for (int it = 0; it < NT / 2; it++) {
            const uint32_t tb = sb + SM_RING + stage * TILE_BYTES;
            mbar_wait(sb + BAR_FULL + 8 * stage, phase);
            uint4 Ka[4], Kb[4];
#pragma unroll
            for (int i = 0; i < 4; i++) { Ka[i] = lds128(tb + koff[i]); Kb[i] = lds128(tb + koff[i] + 2048); }
            float c0[4] = {0.f, 0.f, 0.f, 0.f}, c1[4] = {0.f, 0.f, 0.f, 0.f};
#pragma unroll
            for (int i = 0; i < 4; i++) {
                mma(c0, Ka[i].x, Kb[i].x, Ka[i].y, Kb[i].y, Q[i].x, Q[i].y);
                mma(c1, Ka[i].z, Kb[i].z, Ka[i].w, Kb[i].w, Q[i].z, Q[i].w);
            }
            __syncwarp();
            if (lane == 0) mbar_arrive_n(sb + BAR_EMPTY + 8 * stage, 2);
            const float lo = (g & 1) ? c0[1] + c1[1] : c0[0] + c1[0];
            const float hi = (g & 1) ? c0[3] + c1[3] : c0[2] + c1[2];
            const float sc = rbf(rbf(t1 ? hi : lo) * 0.08838834764831845f);
            mx = fmaxf(mx, sc);
            if (t < 2) sts16(sb + SM_P + ((2 * it + grp) * 128 + rank * 64 + sub * 16 + 4 * (g >> 1) + 2 * t + (g & 1)) * 2, __float_as_uint(sc) >> 16);
            stage += 2;
            if (stage >= STAGES) { stage -= STAGES; phase ^= 1; }
        }

        mga = ld_pkt2(tmp + 2 * 256); msb = ld_pkt2(tmp + 3 * 256); mcb = ld_pkt2(tmp + 4 * 256);
        const __nv_bfloat16* xp = q_.x + ob * D_ + 64 * w + 4 * (lane & 8) + (lane & 7);
        tx0 = ldg16(xp) | ldg16(xp + 8) << 16;
        tx1 = ldg16(xp + 16) | ldg16(xp + 24) << 16;

        asm volatile("cp.async.wait_all;" ::: "memory");

#pragma unroll
        for (int m = 1; m < 32; m <<= 1) mx = fmaxf(mx, __shfl_xor_sync(~0u, mx, m));
        if (lane == 0) sts32f(sb + SM_RED + w * 4, mx);
        cbar();
        {
            const float4 u = lds128f(sb + SM_RED), v = lds128f(sb + SM_RED + 16);
            mx = fmaxf(fmaxf(fmaxf(u.x, u.y), fmaxf(u.z, u.w)), fmaxf(fmaxf(v.x, v.y), fmaxf(v.z, v.w)));
        }
        const uint32_t pa = sb + SM_P + (tid >> 3) * 256 + rank * 128 + (tid & 7) * 16;
        const uint4 s0 = lds128(pa);
        const float sc[8] = {bf_lo(s0.x), bf_hi(s0.x), bf_lo(s0.y), bf_hi(s0.y), bf_lo(s0.z), bf_hi(s0.z), bf_lo(s0.w), bf_hi(s0.w)};
        float l = 0.f;
#pragma unroll
        for (int i = 0; i < 8; i++) l += __expf(sc[i] - mx);
#pragma unroll
        for (int m = 1; m < 32; m <<= 1) l += __shfl_xor_sync(~0u, l, m);
        if (lane == 0) sts32f(sb + SM_RED + 32 + w * 4, l);
        cbar();
        {
            const float4 u = lds128f(sb + SM_RED + 32), v = lds128f(sb + SM_RED + 48);
            l = ((u.x + u.y) + (u.z + u.w)) + ((v.x + v.y) + (v.z + v.w));
        }
        if (tid == 0) st_async_v2(mapa(sb + SM_ML, rank ^ 1), mx, l, mapa(sb + BAR_XML, rank ^ 1));
        mbar_wait_cluster(sb + BAR_XML, 0);
        const float2 o = lds64f(sb + SM_ML);
        const float m = fmaxf(mx, o.x);
        const float inv = __fdividef(1.0f, l * __expf(mx - m) + o.y * __expf(o.x - m));
        const uint32_t p0 = pack2(__expf(sc[0] - m) * inv, __expf(sc[1] - m) * inv), p1 = pack2(__expf(sc[2] - m) * inv, __expf(sc[3] - m) * inv);
        const uint32_t p2 = pack2(__expf(sc[4] - m) * inv, __expf(sc[5] - m) * inv), p3 = pack2(__expf(sc[6] - m) * inv, __expf(sc[7] - m) * inv);
        st_async_v4(mapa(pa, rank ^ 1), p0, p1, p2, p3, mapa(sb + BAR_XP, rank ^ 1));
        sts128(pa, p0, p1, p2, p3);
        cbar();
        mbar_wait_cluster(sb + BAR_XP, 0);
    }

#pragma unroll 1
    for (uint32_t n = 0; n < SPIN_LIMIT && !__all_sync(~0u, pkt_ok(mga, tag) && pkt_ok(msb, tag) && pkt_ok(mcb, tag)); n++) {
        mga = ld_pkt2(tmp + 2 * 256); msb = ld_pkt2(tmp + 3 * 256); mcb = ld_pkt2(tmp + 4 * 256);
    }
    const uint32_t ga0 = lo32(mga.a), ga1 = lo32(mga.b), sb0 = lo32(msb.a), sb1 = lo32(msb.b);
    const uint32_t cb0 = hadd2(ONE2, lo32(mcb.a)), cb1 = hadd2(ONE2, lo32(mcb.b));
    const int wb = 4 * rank + sub;
    u64 red_p = s_line(e1_blk(1, wb), 2 * b) + lane * 4, red2_p = s_line(e1_blk(1, wb), 4 + b) + lane * 4;

    PIN64(red_p); PIN64(red2_p);
    float oa[4][4];
#pragma unroll
    for (int i = 0; i < 4; i++) { oa[i][0] = oa[i][1] = oa[i][2] = oa[i][3] = 0.f; }
    {
        int stage = N_V % STAGES, phase = tile_phase(N_V);
        auto v_tiles = [&](int v0, int v1) {
#pragma unroll 1
            for (int v = v0; v < v1; v++) {
                const uint32_t tb = sb + SM_RING + stage * TILE_BYTES + grp * 8192 + (sw128 ^ (sub * 32));
                uint2 P[4];
#pragma unroll
                for (int i = 0; i < 4; i++) P[i] = lds64(sb + SM_P + v * 256 + grp * 128 + i * 32 + t * 8);
                mbar_wait(sb + BAR_FULL + 8 * stage, phase);
                uint32_t a[4][4];
#pragma unroll
                for (int i = 0; i < 4; i++) ldsm4t(tb + i * 2048, a[i]);
#pragma unroll
                for (int i = 0; i < 4; i++) mma4(oa[i], a[i], P[i].x, P[i].y);
                __syncwarp();
                if (lane == 0) mbar_arrive(sb + BAR_EMPTY + 8 * stage);
                if (++stage == STAGES) { stage = 0; phase ^= 1; }
            }
        };
        v_tiles(0, MEET_AT);
        asm volatile("bar.sync 2, 288;" ::: "memory");
        v_tiles(MEET_AT, NT);
    }

    if (t < 2) {
        const uint32_t a = sb + SM_OP + rank * 512 + w * 64 + (g >> 1) * 16 + (g & 1) * 4 + t * 8;
        const uint32_t v = __float_as_uint(sel(t1, (oa[0][2] + oa[1][2]) + (oa[2][2] + oa[3][2]), (oa[0][0] + oa[1][0]) + (oa[2][0] + oa[3][0])));
        st_async_b32(mapa(a, rank ^ 1), v, mapa(sb + BAR_XO, rank ^ 1));
        st_async_b32(mapa(a, rank), v, mapa(sb + BAR_XO, rank));
    }
    __syncwarp();
    mbar_wait_cluster(sb + BAR_XO, 0);

    {
        float acc[4][4];
        const uint32_t o_ld = sb + SM_OP + grp * 512 + (lane & 15) * 16 + vb * 8, x_st = sb + SM_PART + 4096 + sub * 1024 + lane * 16;
        const float2 u = lds64f(o_ld), v = lds64f(o_ld + 256);
        const uint32_t o2 = pack2(u.x + v.x, u.y + v.y);
        uint32_t bo[8];
#pragma unroll
        for (int i = 0; i < 8; i++) bo[i] = __shfl_sync(~0u, o2, 16 * (i & 1) + 4 * (i >> 1) + t);
        float4 x0 = make_float4(0.f, 0.f, 0.f, 0.f), x1 = x0;
#pragma unroll
        for (int i = 0; i < 4; i++) { acc[i][0] = acc[i][1] = acc[i][2] = acc[i][3] = 0.f; }
        static_assert(N_WO % STAGES + 4 <= STAGES, "wo tiles occupy consecutive slots");
        const uint32_t wa = sb + slot_addr(N_WO) + grp * 2 * TILE_BYTES + sub * 4096, wbar = sb + full_bar(N_WO) + grp * 16;
#pragma unroll
        for (int j = 0; j < 2; j++) {
            if (j == 1 && grp) { asm volatile("bar.sync 8, 256;" ::: "memory"); x0 = lds128f(x_st); x1 = lds128f(x_st + 512); }
            mbar_wait(wbar + 8 * j, tile_phase(N_WO));
            if (j == 1) { }
#pragma unroll
            for (int i = 0; i < 8; i++) ldsm4t(wa + j * TILE_BYTES + (i >> 2) * 2048 + (sw128 ^ ((i & 3) * 32)), A[8 * j + i]);
#pragma unroll
            for (int i = 0; i < 8; i++) mma4(acc[i & 3], A[8 * j + i], bo[4 * j + 2 * (i >> 2)], bo[4 * j + 2 * (i >> 2) + 1]);
        }
        if (!grp) {
            sts128f(x_st, acc[0][0], acc[1][0], acc[2][0], acc[3][0]); sts128f(x_st + 512, acc[0][2], acc[1][2], acc[2][2], acc[3][2]);
            asm volatile("bar.arrive 8, 256;" ::: "memory");
        } else {
            acc[0][0] += x0.x; acc[1][0] += x0.y; acc[2][0] += x0.z; acc[3][0] += x0.w; acc[0][2] += x1.x; acc[1][2] += x1.y; acc[2][2] += x1.z; acc[3][2] += x1.w;
            const float r0 = sel(t2, sel(t1, 1.0f, acc[1][0]), sel(t1, acc[0][2], acc[0][0]));
            const float r1 = sel(t2, sel(t1, 1.0f, acc[3][0]), sel(t1, acc[2][2], acc[2][0]));
            const float r2 = sel(t2, 1.0f, sel(t1, acc[3][2], acc[1][2]));
            asm volatile("red.relaxed.gpu.global.add.f32 [%0], %2;\nred.relaxed.gpu.global.add.f32 [%0 + 256], %3;\nred.relaxed.gpu.global.add.f32 [%1], %4;"
                         :: "l"(red_p), "l"(red2_p), "f"(r0), "f"(r1), "f"(r2) : "memory");
            asm volatile("red.relaxed.gpu.global.add.f32 [%0], %2;\nred.relaxed.gpu.global.add.f32 [%0 + 256], %3;\nred.relaxed.gpu.global.add.f32 [%1], %4;"
                         :: "l"(red_p ^ 4096), "l"(red2_p ^ 4096), "f"(r0), "f"(r1), "f"(r2) : "memory");
        }
    }

    constexpr uint32_t CNT = 0x42000000u;
    if (is_gu) {
        uint32_t side;
        asm volatile("ld.volatile.shared.u32 %0, [%1];" : "=r"(side) : "r"(sb + SM_SIDE) : "memory");
        u64 acc_p = (s_line(e1_blk(0, w), lane >> 3) + (lane & 7) * 16) ^ side, acc2_p = (s_line(e1_blk(0, w), 4 + ob) + (lane & 7) * 16) ^ side;
        const int eb = e1_blk(w >> 2, w & 3);
        const bool near = __all_sync(~0u, (w >> 2) * 4096 == side);
        u64 out_p = s_line(eb, lane >> 3) + S_OUT + (lane & 7) * 16, out2_p = s_line(eb, 4 + ob) + S_OUT + (lane & 15) * 8;
        u64 gb_p = (s_line(e1_blk(0, w), 6 + ob) + (lane & 15) * 8) ^ side, y_p = (u64)(q_.out + t1 * D_ + 64 * w + 4 * t2 + g);
        PIN64(acc_p); PIN64(acc2_p); PIN64(out_p); PIN64(out2_p); PIN64(gb_p); PIN64(y_p);
        auto keep = [&](uint32_t x) { return __shfl_sync(~0u, x, lane); };
        const int src = keep(8 * (g & 2) + t), src1 = keep(src + 4), src2 = keep(src + 8), src3 = keep(src + 12);
        const uint32_t p_st = keep(sb + SM_PART + w * 512 + lane * 16), r_st = keep(sb + SM_RED + (vb * 8 + w) * 8);
        tx0 = keep(tx0); tx1 = keep(tx1);
        uint32_t w2a[4];
#pragma unroll
        for (int i = 0; i < 4; i++) w2a[i] = keep(sb + slot_addr(N_FFN + 4) + w * 4096 + (sw128 ^ (i * 32)));
        const uint32_t hva = keep(sb + SM_Q + ((g & 2) * 2 + t) * 16), w2b = keep(sb + BAR_W2 + 8 * (w * NW >> 3)), t2k = keep(t2);
        const uint32_t g1 = g & 1;
        uint32_t cp[8], cn[8];
        float acc[4][4];
#pragma unroll
        for (int i = 0; i < 8; i++) {
            cp[i] = __shfl_sync(~0u, (i & 1) ? cb1 : cb0, 4 * (i >> 1) + src);
            cn[i] = selu(g1, __shfl_sync(~0u, (i & 1) ? sb1 : sb0, 4 * (i >> 1) + src), cp[i]);
        }
        const int frow = (lane & 7) + (lane & 16);
        const uint32_t fa = sb + slot_addr(N_FFN) + grp * 2 * TILE_BYTES + (64 * sub + frow) * 64 + ((lch ^ ((frow >> 1) & 3)) << 4);
        mbar_wait(sb + BAR_FFN + 8 * (w * NQ >> 3), 0);
        uint4 u = ld_strong128(acc_p), v = ld_strong128(acc2_p);
#pragma unroll
        for (int i = 0; i < 16; i++) ldsm4t((fa ^ ((i & 1) * 32)) + (i >> 3) * 2048 + ((i >> 2) & 1) * 512 + ((i >> 1) & 1) * TILE_BYTES, A[i]);
#pragma unroll
        for (int i = 0; i < 4; i++) { acc[i][0] = acc[i][1] = acc[i][2] = acc[i][3] = 0.f; }
#pragma unroll
        for (int i = 0; i < 16; i++)
            mma4(acc[i & 3], A[i], cn[2 * (i >> 2)], cn[2 * (i >> 2) + 1]);
        sts128f(sb + SM_P + w * 1024 + lane * 16, sel(t2, acc[1][0], acc[0][0]), sel(t2, acc[3][0], acc[2][0]), sel(t2, acc[1][2], acc[0][2]), sel(t2, acc[3][2], acc[2][2]));
        sts128f(sb + SM_P + w * 1024 + 512 + lane * 16, sel(t2, acc[1][1], acc[0][1]), sel(t2, acc[3][1], acc[2][1]), sel(t2, acc[1][3], acc[0][3]), sel(t2, acc[3][3], acc[2][3]));
        bar_arrive<3>();
#pragma unroll
        for (int i = 0; i < 8; i++) cn[i] = selu(g1, cp[i] ^ 0x80008000u, 0u);
        settle(tag, sb + SM_OP, cn[0], cn[1], cn[2], cn[3]); settle(tag, sb + SM_OP, cn[4], cn[5], cn[6], cn[7]);
        for (uint32_t n = 0; !__all_sync(~0u, u.w == CNT && v.w == CNT) && n < SPIN_LIMIT; n++) { u = ld_strong128(acc_p); v = ld_strong128(acc2_p); }
        const uint32_t x0 = hadd2(tx0, hmul2(ga0, pack2(__uint_as_float(u.x), __uint_as_float(u.y))));
        const uint32_t x1 = hadd2(tx1, hmul2(ga1, pack2(__uint_as_float(u.z), __uint_as_float(selu(lane & 8, v.y, v.x)))));
        float c[4] = {0.f, 0.f, 0.f, 0.f};
        mma(c, x0, ONE2, x1, ONE2, x0, x1);
#pragma unroll
        for (int i = 0; i < 4; i++) { acc[i][0] = acc[i][1] = acc[i][2] = acc[i][3] = 0.f; }
        float q, s;
#pragma unroll
        for (int s4 = 0; s4 < 4; s4++) {
            const int from = s4 == 0 ? src : s4 == 1 ? src1 : s4 == 2 ? src2 : src3;
            uint32_t b0 = __shfl_sync(~0u, x0, from), b1 = __shfl_sync(~0u, x1, from);
            b0 = hfma2(b0, cp[2 * s4], hmul2(b0, cn[2 * s4]));
            b1 = hfma2(b1, cp[2 * s4 + 1], hmul2(b1, cn[2 * s4 + 1]));
#pragma unroll
            for (int i = 0; i < 4; i++) mma4(acc[i], A[4 * s4 + i], b0, b1);
            if (s4 == 0) { q = sel(g1, c[1], c[0]); s = c[2] + c[3]; q += __shfl_xor_sync(~0u, q, 4); s += __shfl_xor_sync(~0u, s, 9); }
            if (s4 == 1) q += __shfl_xor_sync(~0u, q, 9);
            if (s4 == 2) { if (lane == 0 || lane == 18) sts64f(r_st, s, fmaxf(fmaf(s * (-1.0f / 64), s, q), 0.f)); }
        }
        sts128f(p_st, sel(t2, acc[1][0] + acc[1][1], acc[0][0] + acc[0][1]), sel(t2, acc[3][0] + acc[3][1], acc[2][0] + acc[2][1]),
                sel(t2, acc[1][2] + acc[1][3], acc[0][2] + acc[0][3]), sel(t2, acc[3][2] + acc[3][3], acc[2][2] + acc[2][3]));
        bar_arrive<4>();
        auto w2_frags = [&]() {
            mbar_wait(w2b, 0);
#pragma unroll
            for (int i = 0; i < 8; i++) ldsm4t(w2a[i & 3] + (i >> 2) * 2048, A[i]);
        };
        if (!near) w2_frags();
#pragma unroll
        for (int i = 0; i < 4; i++) { acc[i][0] = acc[i][1] = acc[i][2] = acc[i][3] = 0.f; }
        bar_sync<5>();
        const uint4 hv = lds128(hva);
        if (near) w2_frags();
#pragma unroll
        for (int i = 0; i < 4; i++) mma4(acc[i], A[i], hv.x, hv.y);
#pragma unroll
        for (int i = 0; i < 4; i++) mma4(acc[i], A[4 + i], hv.z, hv.w);
        float r[4], o[6];
#pragma unroll
        for (int i = 0; i < 4; i++) r[i] = sel(t2k, acc[i][2], acc[i][0]);
        asm volatile("atom.relaxed.gpu.global.add.v4.f32 {%0, %1, %2, %3}, [%4], {%5, %6, %7, %8};"
                     : "=f"(o[0]), "=f"(o[1]), "=f"(o[2]), "=f"(o[4]) : "l"(out_p), "f"(r[0]), "f"(r[1]), "f"(r[2]), "f"(1.0f) : "memory");
        asm volatile("atom.relaxed.gpu.global.add.v2.f32 {%0, %1}, [%2], {%3, %4};"
                     : "=f"(o[3]), "=f"(o[5]) : "l"(out2_p), "f"(r[3]), "f"(1.0f) : "memory");
        uint2 gb = ld_strong64(gb_p);
        uint32_t xo[2];
#pragma unroll
        for (int j = 0; j < 2; j++) {
            const uint32_t e0 = __shfl_sync(~0u, x0, 16 * t1 + 8 * j + g), e1 = __shfl_sync(~0u, x1, 16 * t1 + 8 * j + g);
            xo[j] = __byte_perm(e0, e1, t2 ? 0x7632 : 0x5410);
        }
        const uint32_t f0 = pack2(o[0] + r[0], o[1] + r[1]), f1 = pack2(o[2] + r[2], o[3] + r[3]);
#pragma unroll 1
        for (uint32_t n = 0; n < SPIN_LIMIT; n++) {
            const uint32_t y0 = hadd2(xo[0], hmul2(gb.x, f0)), y1 = hadd2(xo[1], hmul2(gb.y, f1));
            uint32_t late;
            asm volatile("{\n.reg .pred p, q, m;\n.reg .b16 a, b, c, d;\n"
                         "mov.b32 {a, b}, %6;\nmov.b32 {c, d}, %7;\nsetp.ne.b16 m, a, 0xffff;\nsetp.ne.and.b16 m, b, 0xffff, m;\nsetp.ne.and.b16 m, c, 0xffff, m;\nsetp.ne.and.b16 m, d, 0xffff, m;\n"
                         "setp.eq.and.f32 p, %4, 0f42280000, m;\nsetp.eq.and.f32 q, %5, 0f42280000, m;\n"
                         "mov.b32 {a, b}, %2;\nmov.b32 {c, d}, %3;\n"
                         "@p st.global.u16 [%1], a;\n@p st.global.u16 [%1 + 32], b;\n@p st.global.u16 [%1 + 64], c;\n@q st.global.u16 [%1 + 96], d;\n"
                         "vote.sync.all.pred m, m, 0xffffffff;\nselp.u32 %0, 0, 1, m;\n}"
                         : "=r"(late) : "l"(y_p), "r"(y0), "r"(y1), "f"(o[4]), "f"(o[5]), "r"(gb.x), "r"(gb.y) : "memory");
            if (!late) break;
            gb = ld_strong64(gb_p);
        }
    } else if (is_gb) {
        const uint32_t fa = sb + slot_addr(N_FFN) + grp * 8192 + (64 * sub + lrow) * 32 + ((lch ^ ((lrow >> 2) & 1)) << 4);
        const int dl = (lane & 7) * 4 + ((lane >> 3) & 1) * 2 + ob;
        u64 gb_p = s_line(2 * (role >> 2), 6 + (dl >> 4)) + (dl & 15) * 8 + (role & 3) * 2;
        PIN64(gb_p);
        uint32_t bs[8];
#pragma unroll
        for (int i = 0; i < 8; i++) bs[i] = __shfl_sync(~0u, (i & 1) ? sc1 : sc0, 4 * (i >> 1) + 16 * ((g >> 1) & 1) + t);
        const uint32_t c_st = sb + SM_PART + (w * 32 + t1 * 16 + (t >> 1) * 8 + g) * 4;
        settle(tag, sb + SM_OP, bs[0], bs[1], bs[2], bs[3]); settle(tag, sb + SM_OP, bs[4], bs[5], bs[6], bs[7]); settle(tag, sb + SM_OP, c_st, fa, 0, 0);
        mbar_wait(sb + BAR_FFN + 8 * grp, 0);
        float c[4][4];
#pragma unroll
        for (int s4 = 0; s4 < 4; s4++) ldsm4t(fa + s4 * 512, A[s4]);
#pragma unroll
        for (int s4 = 0; s4 < 4; s4++) { c[s4][0] = c[s4][1] = c[s4][2] = c[s4][3] = 0.f; mma4(c[s4], A[s4], bs[2 * s4], bs[2 * s4 + 1]); }
        sts32f(c_st, sel(t2, (c[0][2] + c[1][2]) + (c[2][2] + c[3][2]), (c[0][0] + c[1][0]) + (c[2][0] + c[3][0])));
        cbar();
        if (w == 0) {
            float u[8];
#pragma unroll
            for (int i = 0; i < 8; i++) u[i] = lds32f(sb + SM_PART + i * 128 + lane * 4);
            const uint16_t v = (uint16_t)pack2(((u[0] + u[1]) + (u[2] + u[3])) + ((u[4] + u[5]) + (u[6] + u[7])), 0.f);
            asm volatile("st.relaxed.gpu.global.u16 [%0], %1;\nst.relaxed.gpu.global.u16 [%0 + 4096], %1;" :: "l"(gb_p), "h"(v) : "memory");
        }
    }
}

typedef CUresult (*EncodeFn)(CUtensorMap*, CUtensorMapDataType, cuuint32_t, void*, const cuuint64_t*, const cuuint64_t*,
                             const cuuint32_t*, const cuuint32_t*, CUtensorMapInterleave, CUtensorMapSwizzle,
                             CUtensorMapL2promotion, CUtensorMapFloatOOBfill);

void make_map(EncodeFn enc, CUtensorMap* m, void* ptr, int cols, int rows, int box_cols, int box_rows, CUtensorMapSwizzle sw) {
    cuuint64_t gd[2] = {(cuuint64_t)cols, (cuuint64_t)rows}, gs[1] = {(cuuint64_t)cols * 2};
    cuuint32_t bd[2] = {(cuuint32_t)box_cols, (cuuint32_t)box_rows}, es[2] = {1, 1};
    enc(m, CU_TENSOR_MAP_DATA_TYPE_BFLOAT16, 2, ptr, gd, gs, bd, es, CU_TENSOR_MAP_INTERLEAVE_NONE, sw,
        CU_TENSOR_MAP_L2_PROMOTION_NONE, CU_TENSOR_MAP_FLOAT_OOB_FILL_NONE);
}

}

extern "C" void kernel_launch(void* const* d_in, const int* in_sizes, int n_in, void* d_out, int out_size) {
    (void)in_sizes; (void)n_in; (void)out_size;
    static EncodeFn enc = nullptr;
    if (!enc) {
        void* fn = nullptr;
        cudaDriverEntryPointQueryResult qr;
        cudaGetDriverEntryPoint("cuTensorMapEncodeTiled", &fn, cudaEnableDefault, &qr);
        enc = (EncodeFn)fn;
        cudaFuncSetAttribute(fused_decode_kernel, cudaFuncAttributeMaxDynamicSharedMemorySize, SMEM_BYTES);
    }
    Params p;
    Ptrs q;
    make_map(enc, &p.m_wmod, d_in[10], MODW, D_, 32, 256, CU_TENSOR_MAP_SWIZZLE_64B);
    make_map(enc, &p.m_wq, d_in[3], QD, D_, 64, 128, CU_TENSOR_MAP_SWIZZLE_128B);
    make_map(enc, &p.m_v, d_in[2], DH, 64 * SK, 64, 128, CU_TENSOR_MAP_SWIZZLE_128B);
    {
        cuuint64_t gd[3] = {64, QD, 8}, gs[2] = {D_ * 2, 128};
        cuuint32_t bd[3] = {64, 32, 4}, es[3] = {1, 1, 1};
        enc(&p.m_wo, CU_TENSOR_MAP_DATA_TYPE_BFLOAT16, 3, d_in[4], gd, gs, bd, es, CU_TENSOR_MAP_INTERLEAVE_NONE,
            CU_TENSOR_MAP_SWIZZLE_128B, CU_TENSOR_MAP_L2_PROMOTION_NONE, CU_TENSOR_MAP_FLOAT_OOB_FILL_NONE);
    }
    for (int i = 0; i < 2; i++) {
        cuuint64_t gd[4] = {FF, 2, 8, D_ / 16}, gs[3] = {8 * FF * 2, FF * 2, 16 * FF * 2};
        cuuint32_t bd[4] = {32, 2, 8, 32 / NQ}, es[4] = {1, 1, 1, 1};
        enc(i ? &p.m_w3 : &p.m_w1, CU_TENSOR_MAP_DATA_TYPE_BFLOAT16, 4, d_in[6 + i], gd, gs, bd, es, CU_TENSOR_MAP_INTERLEAVE_NONE,
            CU_TENSOR_MAP_SWIZZLE_64B, CU_TENSOR_MAP_L2_PROMOTION_NONE, CU_TENSOR_MAP_FLOAT_OOB_FILL_NONE);
    }
    {
        cuuint64_t gd[5] = {64, 2, 8, FF / 16, 8}, gs[4] = {8 * D_ * 2, D_ * 2, 16 * D_ * 2, 128};
        cuuint32_t bd[5] = {64, 2, 8, 2, 8 / NW}, es[5] = {1, 1, 1, 1, 1};
        enc(&p.m_w2, CU_TENSOR_MAP_DATA_TYPE_BFLOAT16, 5, d_in[8], gd, gs, bd, es, CU_TENSOR_MAP_INTERLEAVE_NONE,
            CU_TENSOR_MAP_SWIZZLE_128B, CU_TENSOR_MAP_L2_PROMOTION_NONE, CU_TENSOR_MAP_FLOAT_OOB_FILL_NONE);
    }
    make_map(enc, &p.m_gb, d_in[10], MODW, D_, 16, 256, CU_TENSOR_MAP_SWIZZLE_32B);
    q.x = (const __nv_bfloat16*)d_in[0];
    q.kwin = (const __nv_bfloat16*)d_in[1] + (size_t)(SK - WIN) * DH;
    q.c = (const __nv_bfloat16*)d_in[9];
    q.out = (__nv_bfloat16*)d_out;
    fused_decode_kernel<<<NCTA, THREADS, SMEM_BYTES, cudaStreamPerThread>>>(q, p);
}
```

```cpp
#include <cuda_runtime.h>
#include <cuda.h>
#include <cuda_bf16.h>
#include <stdint.h>

namespace {

constexpr int D_ = 512, DH = 128, SK = 16384, WIN = 4096, FF = 1376, QD = 4096, MODW = 3072;
constexpr int NCTA = 128;
constexpr int TILE_BYTES = 16384;
constexpr int NT = 32;
constexpr int STAGES = 13;
constexpr int K_FIRST = 2;
constexpr int FIRST_N = 5;
constexpr int MEET_AT = 16;
constexpr int PACE = 656;
constexpr int LEAD_NS = 1255;
constexpr int GATE_X = 25;
constexpr int POLL_NS = 300;
constexpr int ALPHA16 = 4;
constexpr int GU_NS = 4695;
constexpr int W2_NS = 5865;
constexpr int GB_LEAD = 355;
constexpr int NQ = 8;
constexpr int PROBES = 6;
constexpr int PROBE_NS = 1000;
constexpr int EARLY_NS = 800;
constexpr int NW = 4;
constexpr int HEAD_WARP = 8;
constexpr int N_WMOD = 0, N_WQ = 2, N_K = 6, N_V = N_K + NT, N_WO = N_V + NT, N_FFN = N_WO + 4;
constexpr int N_GATE = N_V + GATE_X;
constexpr int THREADS = 320;
constexpr int N_MOD_CTA = 80;
#define SPIN_LIMIT_S "4194304"
constexpr unsigned SPIN_LIMIT = 1u << 22;

constexpr int SM_RING = 0;
constexpr int SM_P = STAGES * TILE_BYTES;
constexpr int SM_PART = SM_P + WIN * 2;
constexpr int SM_OP = SM_PART + 8192;
constexpr int SM_Q = SM_OP + 2048;
constexpr int SM_RED = SM_Q + 256;
constexpr int SM_ML = SM_RED + 128;
constexpr int SM_PROG = SM_ML + 16;
constexpr int SM_SIDE = SM_PROG + 16;
constexpr int SM_BAR = SM_SIDE + 16;
constexpr int BAR_FULL = SM_BAR, BAR_EMPTY = SM_BAR + 8 * STAGES, BAR_XQ = SM_BAR + 16 * STAGES,
              BAR_XML = BAR_XQ + 8, BAR_XP = BAR_XQ + 16, BAR_XO = BAR_XQ + 24, BAR_FFN = BAR_XQ + 32;
constexpr int BAR_W2 = BAR_FFN + 8 * NQ;
constexpr int SMEM_BYTES = BAR_W2 + 8 * NW;
static_assert(SMEM_BYTES <= 232448, "shared memory");
__host__ __device__ constexpr uint32_t slot_addr(int n) { return SM_RING + (n % STAGES) * TILE_BYTES; }
__host__ __device__ constexpr uint32_t full_bar(int n) { return BAR_FULL + 8 * (n % STAGES); }
__host__ __device__ constexpr uint32_t empty_bar(int n) { return BAR_EMPTY + 8 * (n % STAGES); }
__host__ __device__ constexpr uint32_t tile_phase(int n) { return (n / STAGES) & 1; }
static_assert((N_FFN + 4) % STAGES + 2 <= STAGES && N_FFN % STAGES + 4 <= STAGES, "w1/w3 tiles and w2 tiles occupy consecutive slots");
static_assert(GATE_X >= MEET_AT && N_GATE - STAGES < N_V + MEET_AT && N_FFN + 5 - 2 * STAGES < N_V + MEET_AT && N_FFN + 5 - STAGES < N_WO,
              "barrier parities the helper warp waits on are unambiguous after the rendezvous; the wo tiles are not replaced");
__host__ __device__ constexpr int fill_tile(int j) { return j < K_FIRST ? N_K + j : j < K_FIRST + N_K ? j - K_FIRST : j; }

struct Ptrs {
    const __nv_bfloat16 *kwin, *x, *c;
    __nv_bfloat16* out;
};
struct Params {
    CUtensorMap m_wmod, m_wq, m_v, m_wo, m_w1, m_w3, m_w2, m_gb;
};

__device__ unsigned g_epoch;
__device__ __align__(128) uint2 g_mod[2][5 * D_ / 2];
__device__ __align__(256) unsigned char g_s[131072];
__device__ __forceinline__ unsigned long long s_line(int blk, int i) {
    return (((unsigned long long)g_s + 65535) & ~65535ull) + blk * 4096 + (i >> 1) * 1024 + (i & 1) * 256;
}
__device__ __forceinline__ int e1_blk(int r, int w) { return 2 * w + (r ^ (w & 1)); }
constexpr int S_OUT = 512, S_PROG = 128;
__device__ __align__(128) unsigned g_clear;

typedef unsigned long long u64;
__device__ __forceinline__ unsigned time_ns() {
    unsigned r;
    asm volatile("mov.u32 %0, %%globaltimer_lo;" : "=r"(r));
    return r;
}
__device__ __forceinline__ bool elect_one() {
    uint32_t r;
    asm volatile("{\n.reg .pred p;\nelect.sync _|p, 0xffffffff;\nselp.u32 %0, 1, 0, p;\n}" : "=r"(r));
    return r != 0;
}
#define PIN64(v) asm volatile("" : "+l"(v))

__device__ __forceinline__ void mbar_init(uint32_t bar, uint32_t cnt) {
    asm volatile("mbarrier.init.shared::cta.b64 [%0], %1;" :: "r"(bar), "r"(cnt) : "memory");
}
__device__ __forceinline__ void mbar_expect_tx(uint32_t bar, uint32_t bytes) {
    asm volatile("mbarrier.arrive.expect_tx.shared::cta.b64 _, [%0], %1;" :: "r"(bar), "r"(bytes) : "memory");
}
__device__ __forceinline__ void mbar_arrive(uint32_t bar) {
    asm volatile("mbarrier.arrive.shared::cta.b64 _, [%0];" :: "r"(bar) : "memory");
}
__device__ __forceinline__ void mbar_arrive_n(uint32_t bar, uint32_t n) {
    asm volatile("mbarrier.arrive.shared::cta.b64 _, [%0], %1;" :: "r"(bar), "r"(n) : "memory");
}
__device__ __forceinline__ void mbar_wait(uint32_t bar, uint32_t parity) {
    asm volatile("{\n.reg .pred p;\n.reg .u32 n;\nmov.u32 n, 0;\nW0:\n"
                 "mbarrier.try_wait.parity.shared::cta.b64 p, [%0], %1;\n@p bra W1;\n"
                 "add.u32 n, n, 1;\nsetp.lt.u32 p, n, " SPIN_LIMIT_S ";\n@p bra W0;\nW1:\n}"
                 :: "r"(bar), "r"(parity) : "memory");
}
__device__ __forceinline__ void mbar_wait_cluster(uint32_t bar, uint32_t parity) {
    asm volatile("{\n.reg .pred p;\n.reg .u32 n;\nmov.u32 n, 0;\nW0:\n"
                 "mbarrier.try_wait.parity.acquire.cluster.shared::cta.b64 p, [%0], %1;\n@p bra W1;\n"
                 "add.u32 n, n, 1;\nsetp.lt.u32 p, n, " SPIN_LIMIT_S ";\n@p bra W0;\nW1:\n}"
                 :: "r"(bar), "r"(parity) : "memory");
}
__device__ __forceinline__ void bulk_load(uint32_t dst, const void* src, uint32_t bytes, uint32_t bar, uint64_t pol) {
    asm volatile("cp.async.bulk.shared::cluster.global.mbarrier::complete_tx::bytes.L2::cache_hint [%0], [%1], %2, [%3], %4;"
                 :: "r"(dst), "l"(src), "r"(bytes), "r"(bar), "l"(pol) : "memory");
}
__device__ __forceinline__ void tma2d(uint32_t dst, const CUtensorMap* m, int c0, int c1, uint32_t bar) {
    asm volatile("cp.async.bulk.tensor.2d.shared::cluster.global.mbarrier::complete_tx::bytes [%0], [%1, {%3, %4}], [%2];"
                 :: "r"(dst), "l"(m), "r"(bar), "r"(c0), "r"(c1) : "memory");
}
__device__ __forceinline__ void tma2d_hint(uint32_t dst, const CUtensorMap* m, int c0, int c1, uint32_t bar, uint64_t pol) {
    asm volatile("cp.async.bulk.tensor.2d.shared::cluster.global.mbarrier::complete_tx::bytes.L2::cache_hint [%0], [%1, {%3, %4}], [%2], %5;"
                 :: "r"(dst), "l"(m), "r"(bar), "r"(c0), "r"(c1), "l"(pol) : "memory");
}
__device__ __forceinline__ void tma3d(uint32_t dst, const CUtensorMap* m, int c0, int c1, int c2, uint32_t bar) {
    asm volatile("cp.async.bulk.tensor.3d.shared::cluster.global.mbarrier::complete_tx::bytes [%0], [%1, {%3, %4, %5}], [%2];"
                 :: "r"(dst), "l"(m), "r"(bar), "r"(c0), "r"(c1), "r"(c2) : "memory");
}
__device__ __forceinline__ void tma4d(uint32_t dst, const CUtensorMap* m, int c0, int c3, uint32_t bar) {
    asm volatile("cp.async.bulk.tensor.4d.shared::cluster.global.mbarrier::complete_tx::bytes [%0], [%1, {%3, %5, %5, %4}], [%2];"
                 :: "r"(dst), "l"(m), "r"(bar), "r"(c0), "r"(c3), "r"(0) : "memory");
}
__device__ __forceinline__ void tma5d(uint32_t dst, const CUtensorMap* m, int c3, int c4, uint32_t bar) {
    asm volatile("cp.async.bulk.tensor.5d.shared::cluster.global.mbarrier::complete_tx::bytes [%0], [%1, {%5, %5, %5, %3, %4}], [%2];"
                 :: "r"(dst), "l"(m), "r"(bar), "r"(c3), "r"(c4), "r"(0) : "memory");
}
__device__ __forceinline__ uint32_t mapa(uint32_t addr, uint32_t rank) {
    uint32_t r;
    asm("mapa.shared::cluster.u32 %0, %1, %2;" : "=r"(r) : "r"(addr), "r"(rank));
    return r;
}
__device__ __forceinline__ void st_async_b32(uint32_t addr, uint32_t v, uint32_t bar) {
    asm volatile("st.async.weak.shared::cluster.mbarrier::complete_tx::bytes.b32 [%0], %1, [%2];" :: "r"(addr), "r"(v), "r"(bar) : "memory");
}
__device__ __forceinline__ void st_async_v2(uint32_t addr, float a, float b, uint32_t bar) {
    asm volatile("st.async.weak.shared::cluster.mbarrier::complete_tx::bytes.v2.f32 [%0], {%1, %2}, [%3];" :: "r"(addr), "f"(a), "f"(b), "r"(bar) : "memory");
}
__device__ __forceinline__ void st_async_v4(uint32_t addr, uint32_t a, uint32_t b, uint32_t c, uint32_t d, uint32_t bar) {
    asm volatile("st.async.weak.shared::cluster.mbarrier::complete_tx::bytes.v4.b32 [%0], {%1, %2, %3, %4}, [%5];"
                 :: "r"(addr), "r"(a), "r"(b), "r"(c), "r"(d), "r"(bar) : "memory");
}
template <int ID> __device__ __forceinline__ void bar_sync() { asm volatile("bar.sync %0, 288;" :: "n"(ID) : "memory"); }
template <int ID> __device__ __forceinline__ void bar_arrive() { asm volatile("bar.arrive %0, 288;" :: "n"(ID) : "memory"); }
__device__ __forceinline__ void cbar() { asm volatile("bar.sync 1, 256;" ::: "memory"); }

__device__ __forceinline__ uint4 ldg128(const void* p) {
    uint4 v;
    asm volatile("ld.global.nc.v4.u32 {%0,%1,%2,%3}, [%4];" : "=r"(v.x), "=r"(v.y), "=r"(v.z), "=r"(v.w) : "l"(p));
    return v;
}
__device__ __forceinline__ uint32_t ldg16(const void* p) {
    uint16_t v;
    asm volatile("ld.global.nc.u16 %0, [%1];" : "=h"(v) : "l"(p));
    return v;
}
__device__ __forceinline__ uint4 ld_strong128(unsigned long long p) {
    uint4 v;
    asm volatile("ld.relaxed.gpu.global.v4.b32 {%0,%1,%2,%3}, [%4];" : "=r"(v.x), "=r"(v.y), "=r"(v.z), "=r"(v.w) : "l"(p) : "memory");
    return v;
}
__device__ __forceinline__ uint2 ld_strong64(unsigned long long p) {
    uint2 v;
    asm volatile("ld.relaxed.gpu.global.v2.b32 {%0,%1}, [%2];" : "=r"(v.x), "=r"(v.y) : "l"(p) : "memory");
    return v;
}
__device__ __forceinline__ uint32_t ldg32(const void* p) {
    uint32_t v;
    asm volatile("ld.global.nc.u32 %0, [%1];" : "=r"(v) : "l"(p));
    return v;
}
struct Pkt2 { u64 a, b; };
__device__ __forceinline__ uint32_t lo32(u64 v) { return (uint32_t)v; }
__device__ __forceinline__ uint32_t hi32(u64 v) { return (uint32_t)(v >> 32); }
__device__ __forceinline__ Pkt2 ld_pkt2(const void* p) {
    Pkt2 r;
    asm volatile("ld.relaxed.gpu.global.v2.b64 {%0,%1}, [%2];" : "=l"(r.a), "=l"(r.b) : "l"(p) : "memory");
    return r;
}
__device__ __forceinline__ bool pkt_ok(const Pkt2& r, uint32_t tag) { return hi32(r.a) == tag && hi32(r.b) == tag; }
__device__ __forceinline__ void st_pkt(u64 p, uint32_t data, uint32_t tag) {
    asm volatile("{\n.reg .b64 v;\nmov.b64 v, {%1, %2};\nst.relaxed.gpu.global.b64 [%0], v;\n}" :: "l"(p), "r"(data), "r"(tag) : "memory");
}
__device__ __forceinline__ uint4 lds128(uint32_t a) {
    uint4 v;
    asm volatile("ld.shared.v4.u32 {%0,%1,%2,%3}, [%4];" : "=r"(v.x), "=r"(v.y), "=r"(v.z), "=r"(v.w) : "r"(a) : "memory");
    return v;
}
__device__ __forceinline__ float4 lds128f(uint32_t a) {
    float4 v;
    asm volatile("ld.shared.v4.f32 {%0,%1,%2,%3}, [%4];" : "=f"(v.x), "=f"(v.y), "=f"(v.z), "=f"(v.w) : "r"(a) : "memory");
    return v;
}
__device__ __forceinline__ uint2 lds64(uint32_t a) {
    uint2 v;
    asm volatile("ld.shared.v2.u32 {%0,%1}, [%2];" : "=r"(v.x), "=r"(v.y) : "r"(a) : "memory");
    return v;
}
__device__ __forceinline__ float2 lds64f(uint32_t a) {
    float2 v;
    asm volatile("ld.shared.v2.f32 {%0,%1}, [%2];" : "=f"(v.x), "=f"(v.y) : "r"(a) : "memory");
    return v;
}
__device__ __forceinline__ float lds32f(uint32_t a) {
    float v;
    asm volatile("ld.shared.f32 %0, [%1];" : "=f"(v) : "r"(a) : "memory");
    return v;
}
__device__ __forceinline__ void sts64f(uint32_t a, float x, float y) {
    asm volatile("st.shared.v2.f32 [%0], {%1,%2};" :: "r"(a), "f"(x), "f"(y) : "memory");
}
__device__ __forceinline__ void sts128f(uint32_t a, float x, float y, float z, float w) {
    asm volatile("st.shared.v4.f32 [%0], {%1,%2,%3,%4};" :: "r"(a), "f"(x), "f"(y), "f"(z), "f"(w) : "memory");
}
__device__ __forceinline__ void sts32f(uint32_t a, float x) {
    asm volatile("st.shared.f32 [%0], %1;" :: "r"(a), "f"(x) : "memory");
}
__device__ __forceinline__ void sts128(uint32_t a, uint32_t x, uint32_t y, uint32_t z, uint32_t w) {
    asm volatile("st.shared.v4.u32 [%0], {%1,%2,%3,%4};" :: "r"(a), "r"(x), "r"(y), "r"(z), "r"(w) : "memory");
}
__device__ __forceinline__ void settle(uint32_t tag, uint32_t a, uint32_t x, uint32_t y, uint32_t z, uint32_t w) {
    asm volatile("{\n.reg .pred p;\nsetp.eq.u32 p, %0, 0;\n@p st.shared.v4.u32 [%1], {%2,%3,%4,%5};\n}" :: "r"(tag), "r"(a), "r"(x), "r"(y), "r"(z), "r"(w) : "memory");
}
__device__ __forceinline__ void settle(uint32_t tag, uint32_t a, const float4& v) {
    settle(tag, a, __float_as_uint(v.x), __float_as_uint(v.y), __float_as_uint(v.z), __float_as_uint(v.w));
}
__device__ __forceinline__ void sts16(uint32_t a, uint32_t x) {
    asm volatile("st.shared.u16 [%0], %1;" :: "r"(a), "h"((uint16_t)x) : "memory");
}
__device__ __forceinline__ void ldsm4t(uint32_t a, uint32_t (&r)[4]) {
    asm volatile("ldmatrix.sync.aligned.m8n8.x4.trans.shared.b16 {%0,%1,%2,%3}, [%4];"
                 : "=r"(r[0]), "=r"(r[1]), "=r"(r[2]), "=r"(r[3]) : "r"(a) : "memory");
}
__device__ __forceinline__ void mma(float (&c)[4], uint32_t a0, uint32_t a1, uint32_t a2, uint32_t a3, uint32_t b0, uint32_t b1) {
    asm volatile("mma.sync.aligned.m16n8k16.row.col.f32.bf16.bf16.f32 {%0,%1,%2,%3}, {%4,%5,%6,%7}, {%8,%9}, {%0,%1,%2,%3};"
                 : "+f"(c[0]), "+f"(c[1]), "+f"(c[2]), "+f"(c[3]) : "r"(a0), "r"(a1), "r"(a2), "r"(a3), "r"(b0), "r"(b1));
}
__device__ __forceinline__ void mma4(float (&c)[4], const uint32_t (&a)[4], uint32_t b0, uint32_t b1) { mma(c, a[0], a[1], a[2], a[3], b0, b1); }
__device__ __forceinline__ float sel(uint32_t c, float a, float b) {
    float r;
    asm("{\n.reg .pred p;\nsetp.ne.u32 p, %3, 0;\nselp.f32 %0, %1, %2, p;\n}" : "=f"(r) : "f"(a), "f"(b), "r"(c));
    return r;
}
__device__ __forceinline__ float bf_lo(uint32_t v) { return __uint_as_float(v << 16); }
__device__ __forceinline__ float bf_hi(uint32_t v) { return __uint_as_float(v & 0xffff0000u); }
__device__ __forceinline__ uint32_t pack2(float lo, float hi) {
    uint32_t r;
    asm("cvt.rn.bf16x2.f32 %0, %1, %2;" : "=r"(r) : "f"(hi), "f"(lo));
    return r;
}
__device__ __forceinline__ float rbf(float x) { return __uint_as_float(pack2(0.f, x)); }
__device__ __forceinline__ uint32_t hadd2(uint32_t a, uint32_t b) { uint32_t r; asm("add.rn.bf16x2 %0, %1, %2;" : "=r"(r) : "r"(a), "r"(b)); return r; }
__device__ __forceinline__ uint32_t hsub2(uint32_t a, uint32_t b) { uint32_t r; asm("sub.rn.bf16x2 %0, %1, %2;" : "=r"(r) : "r"(a), "r"(b)); return r; }
__device__ __forceinline__ uint32_t hmul2(uint32_t a, uint32_t b) { uint32_t r; asm("mul.rn.bf16x2 %0, %1, %2;" : "=r"(r) : "r"(a), "r"(b)); return r; }
__device__ __forceinline__ uint32_t hfma2(uint32_t a, uint32_t b, uint32_t c) { uint32_t r; asm("fma.rn.bf16x2 %0, %1, %2, %3;" : "=r"(r) : "r"(a), "r"(b), "r"(c)); return r; }
__device__ __forceinline__ uint32_t selu(uint32_t c, uint32_t a, uint32_t b) { return __float_as_uint(sel(c, __uint_as_float(a), __uint_as_float(b))); }
constexpr uint32_t ONE2 = 0x3f803f80u;
__device__ __forceinline__ float sigmoid_f(float x) {
    float e, r;
    asm("ex2.approx.ftz.f32 %0, %1;" : "=f"(e) : "f"(x * -1.4426950408889634f));
    asm("rcp.approx.ftz.f32 %0, %1;" : "=f"(r) : "f"(1.0f + e));
    return r;
}
__device__ __forceinline__ float silu_f(float x) { return x * sigmoid_f(x); }
__device__ __forceinline__ float rcp_sd(float m2) {
    float s, r;
    asm("sqrt.approx.ftz.f32 %0, %1;" : "=f"(s) : "f"(rbf(rbf(m2 * (1.0f / D_)) + 1e-5f)));
    asm("rcp.approx.ftz.f32 %0, %1;" : "=f"(r) : "f"(rbf(s)));
    return r;
}
__device__ __forceinline__ uint32_t ln_mod2(uint32_t x, uint32_t mean2, float rsd, uint32_t c1, uint32_t sh) {
    const uint32_t d = hsub2(x, mean2);
    return hadd2(hmul2(pack2(bf_lo(d) * rsd, bf_hi(d) * rsd), c1), sh);
}
__device__ __forceinline__ int pair_pos(int j) { return 2 * (j & 3) + (j >> 2); }

__global__ void __cluster_dims__(2, 1, 1) __launch_bounds__(THREADS, 1)
fused_decode_kernel(const __grid_constant__ Ptrs q_, const __grid_constant__ Params p) {
    extern __shared__ __align__(1024) unsigned char smem[];
    unsigned t_top;
    asm volatile("mov.u32 %0, %%globaltimer_lo;" : "=r"(t_top));
    const int tid = threadIdx.x;
    uint32_t z0;
    asm("and.b32 %0, %1, 1024;" : "=r"(z0) : "r"(tid));
    const char* kw = *(const char* const*)((const char*)&q_.kwin + z0);
    const uint32_t sb = (uint32_t)__cvta_generic_to_shared(smem);
    auto place = [](int cl) { return cl < 4 ? 8 * cl + 39 : cl - 4 + max((cl * 37 - 36 * 37) >> 8, 0); };
    uint32_t z2;
    asm("and.b32 %0, %1, 2048;" : "=r"(z2) : "r"(tid));
    const int cv = blockIdx.x + z2, pw = place(cv >> 1);
    static_assert(SK * DH * 2 == 1 << 22 && TILE_BYTES == 1 << 14, "koff");
    const char* kp;
    auto set_kp = [&](uint32_t off) {
        asm volatile("{\n.reg .u32 lo, hi;\nmov.b64 {lo, hi}, %1;\nadd.cc.u32 lo, lo, %2;\naddc.u32 hi, hi, 0;\nmov.b64 %0, {lo, hi};\n}"
                     : "=l"(kp) : "l"(kw), "r"(off));
    };
    uint64_t pol;
    asm("createpolicy.fractional.L2::evict_first.b64 %0, 1.0;" : "=l"(pol));
    auto fill_k = [&](int n) {
        mbar_expect_tx(sb + full_bar(n), TILE_BYTES);
        bulk_load(sb + slot_addr(n), kp + (n - N_K) * 2 * TILE_BYTES, TILE_BYTES, sb + full_bar(n), pol);
    };
    static_assert(K_FIRST >= 1, "head block starts with K tile 0");
    const bool el = elect_one();
    if ((tid >> 5) + (sb >> 28) == HEAD_WARP && el) {
        mbar_init(sb + full_bar(N_K), 1);
        set_kp(((pw & 7) << 22) | ((pw & 8) << 24) | ((pw & 48) << 21) | ((cv & 1) << 14));
        bulk_load(sb + slot_addr(N_K), kp, TILE_BYTES, sb + full_bar(N_K), pol);
        mbar_expect_tx(sb + full_bar(N_K), TILE_BYTES);
#pragma unroll
        for (int j = 1; j < K_FIRST; j++) { mbar_init(sb + full_bar(N_K + j), 1); fill_k(N_K + j); }
    }
    __syncwarp();
    const int cta = blockIdx.x, rank = cta & 1, pv = place(cta >> 1);
    const int b = (pv >> 3) & 1, h = (pv & 7) | ((pv >> 1) & 24), bh = 32 * b + h;
    const int mc = 2 * pv + rank;
    auto first_fill = [&](int j) {
        const int n = fill_tile(j);
        if (n >= N_K) {
            fill_k(n);
        } else if (n >= N_WQ) {
            mbar_expect_tx(sb + full_bar(n), TILE_BYTES);
            tma2d(sb + slot_addr(n), &p.m_wq, h * DH + 64 * rank, 128 * (n - N_WQ), sb + full_bar(n));
        } else if (mc < N_MOD_CTA) {
            mbar_expect_tx(sb + full_bar(n), TILE_BYTES);
            tma2d(sb + slot_addr(n), &p.m_wmod, 32 * mc, 256 * n, sb + full_bar(n));
        } else {
            mbar_arrive(sb + full_bar(n));
        }
    };
    if ((tid >> 5) == HEAD_WARP && el) {
#pragma unroll
        for (int j = K_FIRST; j < FIRST_N; j++) mbar_init(sb + full_bar(fill_tile(j)), 1);
#pragma unroll
        for (int j = K_FIRST; j < FIRST_N; j++) first_fill(j);
        asm volatile("fence.mbarrier_init.release.cluster;" ::: "memory");
    }
    __syncwarp();
    const int role = cta / 3;
    const bool is_gu = cta == 3 * role, is_gb = cta == 3 * role + 1 && role < 32;
    if (tid >= 288) {
        const unsigned t_start = t_top;
        asm volatile("barrier.cluster.arrive.relaxed.aligned;" ::: "memory");
        unsigned tag;
        asm volatile("ld.relaxed.gpu.global.u32 %0, [%1];" : "=r"(tag) : "l"(&g_epoch) : "memory");
        tag += 1;
        if (cta == NCTA - 1) {
#pragma unroll 2
            for (int i = tid - 288; i < 128 * 8; i += 32) {
                uint4* q = reinterpret_cast<uint4*>(s_line(i >> 6, (i >> 3) & 7)) + (i & 7);
                const uint32_t v = (i & 48) == 48 ? ~0u : 0u;
                q[0] = make_uint4(v, v, v, v);
                q[8] = q[32] = q[40] = make_uint4(0u, 0u, 0u, 0u);
            }
            __syncwarp();
            asm volatile("fence.acq_rel.gpu;" ::: "memory");
            if (tid == 288) asm volatile("st.relaxed.gpu.global.u32 [%0], %1;" :: "l"(&g_clear), "r"(tag) : "memory");
        }
        asm volatile("barrier.cluster.wait.acquire.aligned;" ::: "memory");
        mbar_wait_cluster(sb + BAR_XQ, 0);
#pragma unroll 1
        for (uint32_t n = 0; n < SPIN_LIMIT; n++) {
            unsigned c;
            asm volatile("ld.relaxed.gpu.global.u32 %0, [%1];" : "=r"(c) : "l"(&g_clear) : "memory");
            if (c == tag) break;
        }
        asm volatile("fence.acq_rel.gpu;" ::: "memory");
        asm volatile("st.volatile.shared.u32 [%0], %1;" :: "r"(sb + SM_SIDE), "r"(0) : "memory");
        asm volatile("bar.sync 2, 288;" ::: "memory");
        if (elect_one()) {
            asm volatile("prefetch.tensormap [%0];" :: "l"(is_gu ? &p.m_w1 : &p.m_gb) : "memory");
            asm volatile("prefetch.tensormap [%0];" :: "l"(&p.m_w3) : "memory");
            asm volatile("prefetch.tensormap [%0];" :: "l"(&p.m_w2) : "memory");
            const int issue = ((4 * N_GATE - 11) * PACE >> 2) - LEAD_NS;
            unsigned now, c = 0, best[2] = {~0u, ~0u}, np = is_gu ? 0 : PROBES;
            auto probe = [&]() {
                const int k = np >> 1, i = (role >> 3) + 2 * k;
                const u64 a = (s_line(e1_blk(0, role & 7), i < 6 ? i : i - 6) + (k ? 512 * k - 384 : 0)) ^ ((np & 1) << 12);
                unsigned v, c0, c1 = 0;
                asm volatile("mov.u32 %0, %%clock;" : "=r"(c0));
                asm volatile("ld.relaxed.gpu.global.u32 %0, [%1];" : "=r"(v) : "l"(a) : "memory");
                asm volatile("{\n.reg .pred p;\nsetp.ne.u32 p, %1, 0xffffffff;\n@p mov.u32 %0, %%clock;\n}" : "+r"(c1) : "r"(v));
                if (np & 1) best[1] = min(best[1], c1 - c0); else best[0] = min(best[0], c1 - c0);
                np++;
                if (!(np & 1)) asm volatile("st.volatile.shared.u32 [%0], %1;" :: "r"(sb + SM_SIDE), "r"(best[0] <= best[1] ? 0 : 4096) : "memory");
            };
#pragma unroll 1
            while (np < PROBES) {
                now = time_ns();
                if ((int)(now - t_start) >= issue + EARLY_NS) break;
                probe();
            }
            mbar_wait(sb + full_bar(N_GATE), tile_phase(N_GATE));
            now = time_ns();
            const unsigned ref = t_start & ~0x3ffffu, mine = (1u << 24) + min((now - ref) >> 2, 100000u);
            const int own = now - t_start;
            const u64 prog = s_line(0, 7) + S_PROG;
            asm volatile("red.relaxed.gpu.global.add.u32 [%0], %1;" :: "l"(prog), "r"(mine) : "memory");
            if (is_gu || is_gb) {
#pragma unroll
                for (int i = 0; i < 6; i++) mbar_wait(sb + empty_bar(N_FFN + i), tile_phase(N_FFN + i) ^ 1);
#pragma unroll
                for (int i = 0; i < NQ; i++) mbar_expect_tx(sb + BAR_FFN + 8 * i, is_gu ? 65536 / NQ : 8192);
#pragma unroll
                for (int i = 0; i < NW; i++) mbar_expect_tx(sb + BAR_W2 + 8 * i, 32768 / NW);
                unsigned due = 0, next = now;
                constexpr unsigned full = (unsigned)NCTA << 24;
                asm volatile("st.volatile.shared.u32 [%0], %1;" :: "r"(sb + SM_PROG), "r"(mine) : "memory");
#pragma unroll 1
                for (uint32_t n = 0; n < 4096; n++) {
                    unsigned v;
                    asm volatile("ld.volatile.shared.u32 %0, [%1];" : "=r"(v) : "r"(sb + SM_PROG) : "memory");
                    if (v > c) {
                        c = v;
                        int arr = (int)__fdividef((float)(c & 0xffffffu) * 4.0f, (float)(c >> 24)) - (int)(t_start - ref);
                        if (abs(arr - own) > 2000) arr = own;
                        due = arr - ((arr - issue) * ALPHA16 >> 4) + (is_gb ? W2_NS - GB_LEAD : GU_NS);
                    }
                    now = time_ns();
                    if (now - t_start + PROBE_NS >= due) np = PROBES;
                    if ((c >= full && np == PROBES) || now - t_start >= due) break;
                    if ((int)(now - next) >= 0 && c < full) {
                        asm volatile("cp.async.cg.shared.global [%0], [%1], 16;" :: "r"(sb + SM_PROG), "l"(prog) : "memory");
                        next = now + POLL_NS;
                    }
                    if (np < PROBES) probe();
                }
#pragma unroll 1
                for (uint32_t n = 0; n < 1024 && now - t_start < due; n++) now = time_ns();
                if (is_gu) {
#pragma unroll
                    for (int i = 0; i < 2 * NQ; i++) {
                        const int q = i >> 1, r0 = q * (512 / NQ);
                        tma4d(sb + slot_addr(N_FFN) + (r0 >> 8) * 2 * TILE_BYTES + (i & 1) * TILE_BYTES + (r0 & 255) * 64, (i & 1) ? &p.m_w3 : &p.m_w1, 32 * role, r0 / 16, sb + BAR_FFN + 8 * q);
                    }
#pragma unroll 1
                    for (uint32_t n = 0; n < 1024 && now - t_start < due + (W2_NS - GU_NS); n++) now = time_ns();
#pragma unroll
                    for (int i = 0; i < NW; i++) {
                        const int j = (i >> 1) + (i & 1) * (NW / 2);
                        tma5d(sb + slot_addr(N_FFN + 4) + j * (32768 / NW), &p.m_w2, 2 * role, j * (8 / NW), sb + BAR_W2 + 8 * j);
                    }
                } else {
                    tma2d(sb + slot_addr(N_FFN), &p.m_gb, 5 * D_ + 16 * role, 0, sb + BAR_FFN);
                    tma2d(sb + slot_addr(N_FFN) + 8192, &p.m_gb, 5 * D_ + 16 * role, 256, sb + BAR_FFN + 8);
                }
                asm volatile("cp.async.wait_all;" ::: "memory");
            }
        }
        __syncwarp();
        if (is_gu) {
            const int lane = tid & 31;
            auto sum8 = [&](uint32_t a, int stride) {
                float4 u[8];
#pragma unroll
                for (int i = 0; i < 8; i++) u[i] = lds128f(a + i * stride);
                return make_float4(((u[0].x + u[1].x) + (u[2].x + u[3].x)) + ((u[4].x + u[5].x) + (u[6].x + u[7].x)),
                                   ((u[0].y + u[1].y) + (u[2].y + u[3].y)) + ((u[4].y + u[5].y) + (u[6].y + u[7].y)),
                                   ((u[0].z + u[1].z) + (u[2].z + u[3].z)) + ((u[4].z + u[5].z) + (u[6].z + u[7].z)),
                                   ((u[0].w + u[1].w) + (u[2].w + u[3].w)) + ((u[4].w + u[5].w) + (u[6].w + u[7].w)));
            };
            uint32_t h_st = sb + SM_Q + (((lane & 1) * 4 + ((lane >> 2) & 3)) * 4 + (lane & 2) + (lane >> 4)) * 4;
            bar_sync<3>();
            const float4 C = sum8(sb + SM_P + lane * 16, 1024), S = sum8(sb + SM_P + 512 + lane * 16, 1024);
            const uint32_t st_ld = sb + SM_RED + (lane & 1) * 64;
            settle(tag, sb + SM_OP, C); settle(tag, sb + SM_OP, S); settle(tag, sb + SM_OP, h_st, st_ld, 0, 0);
            bar_sync<4>();
            const float4 r0 = lds128f(st_ld), r1 = lds128f(st_ld + 16), r2 = lds128f(st_ld + 32), r3 = lds128f(st_ld + 48);
            const float4 Y = sum8(sb + SM_PART + lane * 16, 512);
            const float e1 = r0.z - r0.x, e2 = r1.x - r0.x, e3 = r1.z - r0.x, e4 = r2.x - r0.x, e5 = r2.z - r0.x, e6 = r3.x - r0.x, e7 = r3.z - r0.x;
            const float se = ((e1 + e2) + (e3 + e4)) + ((e5 + e6) + e7);
            const float ee = (fmaf(e1, e1, e2 * e2) + fmaf(e3, e3, e4 * e4)) + fmaf(e5, e5, fmaf(e6, e6, e7 * e7));
            const float sq = ((r0.y + r0.w) + (r1.y + r1.w)) + ((r2.y + r2.w) + (r3.y + r3.w));
            float rsd;
            asm("rsqrt.approx.ftz.f32 %0, %1;" : "=f"(rsd) : "f"(fmaf(fmaf(se * (-1.0f / D_), se, fmaf(ee, 1.0f / 64, sq)), 1.0f / D_, 1e-5f)));
            const float mu = -rbf(fmaf(r0.x, 8.0f, se) * (1.0f / D_));
            const float g0 = fmaf(rsd, fmaf(mu, C.x, Y.x), S.x), g1 = fmaf(rsd, fmaf(mu, C.z, Y.z), S.z);
            const float u0 = fmaf(rsd, fmaf(mu, C.y, Y.y), S.y), u1 = fmaf(rsd, fmaf(mu, C.w, Y.w), S.w);
            const uint32_t hv = pack2(silu_f(g0) * u0, silu_f(g1) * u1);
            sts32f(h_st, __uint_as_float(hv));
            bar_arrive<5>();
            if (role == 0 && lane == 0) g_epoch = tag;
        }
        return;
    }
    if (tid >= 256) {
        set_kp(bh * (SK * DH * 2) + rank * TILE_BYTES);
        const unsigned t_start = t_top;
        auto pace = [&](int q4) {
            const int due = (q4 * PACE >> 2) - LEAD_NS;
            unsigned now, n = 0;
            do { now = time_ns(); } while ((int)(now - t_start) < due && ++n < 256);
        };
        if (tid == 256) {
#pragma unroll
            for (int j = FIRST_N; j < STAGES; j++) mbar_init(sb + full_bar(fill_tile(j)), 1);
#pragma unroll
            for (int s = 0; s < STAGES; s++) mbar_init(sb + BAR_EMPTY + 8 * s, 8);
            mbar_init(sb + BAR_XQ, 1); mbar_init(sb + BAR_XML, 1); mbar_init(sb + BAR_XP, 1); mbar_init(sb + BAR_XO, 1);
#pragma unroll
            for (int i = 0; i < NQ + NW; i++) mbar_init(sb + BAR_FFN + 8 * i, 1);
            mbar_expect_tx(sb + BAR_XQ, 256); mbar_expect_tx(sb + BAR_XML, 8); mbar_expect_tx(sb + BAR_XP, WIN); mbar_expect_tx(sb + BAR_XO, 1024);
            asm volatile("fence.mbarrier_init.release.cluster;" ::: "memory");
            asm volatile("fence.proxy.async.shared::cta;" ::: "memory");
        }
        __syncwarp();
        asm volatile("barrier.cluster.arrive.relaxed.aligned;" ::: "memory");
        if (elect_one()) {
#pragma unroll
            for (int j = FIRST_N; j < STAGES; j++) {
                pace(j <= K_FIRST ? 4 * j : j <= K_FIRST + 2 ? 4 * K_FIRST + 5 * (j - K_FIRST) / 2 :
                     j <= K_FIRST + 6 ? 4 * K_FIRST + 5 + 2 * (j - K_FIRST - 2) : 4 * j - 11);
                first_fill(j);
            }
        }
        __syncwarp();
        asm volatile("barrier.cluster.wait.acquire.aligned;" ::: "memory");
        if (elect_one()) {
            asm volatile("prefetch.tensormap [%0];" :: "l"(&p.m_v) : "memory");
            asm volatile("prefetch.tensormap [%0];" :: "l"(&p.m_wo) : "memory");
            int s = 0, ph = 0;
#pragma unroll 1
            for (int n = STAGES; n < N_FFN; n++) {
                const uint32_t dst = sb + SM_RING + s * TILE_BYTES, bar = sb + BAR_FULL + 8 * s;
                mbar_wait(sb + BAR_EMPTY + 8 * s, ph);
                mbar_expect_tx(bar, TILE_BYTES);
                pace(n < N_WO ? 4 * n - 11 : 2 * (N_WO + n) - 11);
                if (n < N_V) bulk_load(dst, kp + (n - N_K) * 2 * TILE_BYTES, TILE_BYTES, bar, pol);
                else if (n < N_WO) tma2d_hint(dst, &p.m_v, 64 * rank, bh * SK + (SK - WIN) + 128 * (n - N_V), bar, pol);
                else tma3d(dst, &p.m_wo, 0, h * DH + 32 * (n - N_WO), 4 * rank, bar);
                if (++s == STAGES) { s = 0; ph ^= 1; }
            }
        }
        return;
    }

    const unsigned t_c = t_top;
    const int lane = tid & 31, w = tid >> 5, g = lane >> 2, t = lane & 3;
    const int hgrp = 4 * w + (g & 3);
    const int vb = g >> 2;
    const uint32_t cv0 = ldg32(q_.c + vb * D_ + 16 * hgrp + 2 * t), cv1 = ldg32(q_.c + vb * D_ + 16 * hgrp + 8 + 2 * t);
    unsigned tag;
    asm volatile("ld.relaxed.gpu.global.u32 %0, [%1];" : "=r"(tag) : "l"(&g_epoch) : "memory");
    const uint4 xa = ldg128(q_.x + b * D_ + 16 * lane), xb = ldg128(q_.x + b * D_ + 16 * lane + 8);
    const uint32_t xh0 = ldg32(q_.x + b * D_ + 16 * hgrp + 2 * t), xh1 = ldg32(q_.x + b * D_ + 16 * hgrp + 8 + 2 * t);
    asm volatile("barrier.cluster.arrive.relaxed.aligned;" ::: "memory");
#pragma unroll 1
    for (uint32_t n = t_c; n < 2; n++) asm volatile("nanosleep.u32 1;" ::: "memory");
    const int grp = w >> 2, sub = w & 3;
    const int lrow = (lane & 7) + 8 * (lane >> 4);
    const int lch = (lane >> 3) & 1;
    const int ob = lane >> 4;
    const uint32_t t1 = t & 1, t2 = t & 2;
    const int gsrc = 16 * (g & 1) + t;
    const uint32_t sw128 = lrow * 128 + ((lch ^ (lrow & 7)) << 4);
    uint32_t A[16][4];

    const uint32_t sc0 = pack2(silu_f(bf_lo(cv0)), silu_f(bf_hi(cv0))), sc1 = pack2(silu_f(bf_lo(cv1)), silu_f(bf_hi(cv1)));
    tag += 1;
    asm volatile("barrier.cluster.wait.acquire.aligned;" ::: "memory");
    mbar_wait(sb + BAR_FULL + 8 * (N_WMOD + grp), 0);
    if (mc < N_MOD_CTA) {
        const uint32_t tb = sb + SM_RING + (N_WMOD + grp) * TILE_BYTES + (64 * sub + lrow) * 64;
#pragma unroll
        for (int i = 0; i < 8; i++)
            ldsm4t(tb + (i >> 1) * 1024 + (((2 * (i & 1) + lch) ^ ((lrow >> 1) & 3)) << 4), A[i]);
        float acc[2][4] = {{0.f, 0.f, 0.f, 0.f}, {0.f, 0.f, 0.f, 0.f}};
#pragma unroll
        for (int s = 0; s < 4; s++) {
            const uint32_t b0 = __shfl_sync(~0u, sc0, 4 * s + gsrc), b1 = __shfl_sync(~0u, sc1, 4 * s + gsrc);
            mma4(acc[0], A[2 * s], b0, b1);
            mma4(acc[1], A[2 * s + 1], b0, b1);
        }
        sts32f(sb + SM_P + (w * 64 + 8 * t + g) * 4, sel(t2, sel(t1, acc[1][2], acc[1][0]), sel(t1, acc[0][2], acc[0][0])));
        sts32f(sb + SM_P + (w * 64 + 32 + 8 * t + g) * 4, sel(t2, sel(t1, acc[1][3], acc[1][1]), sel(t1, acc[0][3], acc[0][1])));
        cbar();
        if (w == 0) {
            const bool adj = mc < 32;
            const uint32_t a0 = sb + SM_P + (adj ? 2 * lane : ob * 32 + (lane & 1) * 16 + ((lane >> 1) & 7)) * 4, a1 = a0 + (adj ? 4 : 32);
            float2 sum = make_float2(0.f, 0.f);
#pragma unroll
            for (int i = 0; i < 8; i++) { sum.x += lds32f(a0 + i * 256); sum.y += lds32f(a1 + i * 256); }
            st_pkt((u64)&g_mod[ob][16 * mc + (adj ? (lane & 8) + pair_pos(lane & 7) : lane & 15)], pack2(sum.x, sum.y), tag);
        }
    }
    __syncwarp();
    if (lane == 0) mbar_arrive_n(sb + BAR_EMPTY + 8 * (N_WMOD + grp), 2);

    {
        const uint2* mp = &g_mod[b][vb * 256 + 8 * hgrp + 2 * t];
        const uint32_t ms = sb + SM_PART + tid * 16;
        auto fetch_mod = [&](uint32_t k) {
            asm volatile("cp.async.cg.shared.global [%0], [%1], 16;\ncp.async.commit_group;" :: "r"(ms + k), "l"(mp) : "memory");
        };
        fetch_mod(0);
        float xs[16] = {bf_lo(xa.x), bf_hi(xa.x), bf_lo(xa.y), bf_hi(xa.y), bf_lo(xa.z), bf_hi(xa.z), bf_lo(xa.w), bf_hi(xa.w),
                        bf_lo(xb.x), bf_hi(xb.x), bf_lo(xb.y), bf_hi(xb.y), bf_lo(xb.z), bf_hi(xb.z), bf_lo(xb.w), bf_hi(xb.w)};
        float s = 0.f;
#pragma unroll
        for (int i = 0; i < 16; i++) s += xs[i];
#pragma unroll
        for (int m = 1; m < 32; m <<= 1) s += __shfl_xor_sync(~0u, s, m);
        const float mean = s * (1.0f / D_);
        float q = 0.f;
#pragma unroll
        for (int i = 0; i < 16; i++) q += (xs[i] - mean) * (xs[i] - mean);
#pragma unroll
        for (int m = 1; m < 32; m <<= 1) q += __shfl_xor_sync(~0u, q, m);
        const uint32_t mean2 = pack2(mean, mean);
        const float rsd = rcp_sd(q);

        mbar_wait(sb + BAR_FULL + 8 * (N_WQ + (w >> 1)), 0);
        const uint32_t tb = sb + SM_RING + (N_WQ + (w >> 1)) * TILE_BYTES + (w & 1) * 8192;
#pragma unroll
        for (int i = 0; i < 16; i++) ldsm4t(tb + (i >> 2) * 2048 + (sw128 ^ ((i & 3) * 32)), A[i]);
        __syncwarp();
        if (lane == 0) mbar_arrive_n(sb + BAR_EMPTY + 8 * (N_WQ + (w >> 1)), 4);

        Pkt2 m;
        for (uint32_t n = 0, k = 0; n < SPIN_LIMIT; n++) {
            fetch_mod(k ^ 4096);
            asm volatile("cp.async.wait_group 1;" ::: "memory");
            const uint4 u = lds128(ms + k);
            m.a = u.x | (u64)u.y << 32; m.b = u.z | (u64)u.w << 32;
            if (__all_sync(~0u, pkt_ok(m, tag))) break;
            k ^= 4096;
        }
        const uint32_t ca0 = __shfl_xor_sync(~0u, lo32(m.a), 16), ca1 = __shfl_xor_sync(~0u, lo32(m.b), 16);
        const uint32_t v0 = ln_mod2(xh0, mean2, rsd, hadd2(ONE2, ca0), lo32(m.a));
        const uint32_t v1 = ln_mod2(xh1, mean2, rsd, hadd2(ONE2, ca1), lo32(m.b));
        float acc[4][4];
#pragma unroll
        for (int i = 0; i < 4; i++) { acc[i][0] = acc[i][1] = acc[i][2] = acc[i][3] = 0.f; }
#pragma unroll
        for (int s4 = 0; s4 < 4; s4++) {
            const uint32_t b0 = __shfl_sync(~0u, v0, 4 * s4 + t), b1 = __shfl_sync(~0u, v1, 4 * s4 + t);
#pragma unroll
            for (int i = 0; i < 4; i++) mma4(acc[i], A[4 * s4 + i], b0, b1);
        }
        sts32f(sb + SM_OP + (w * 64 + 16 * t + g) * 4, sel(t2, sel(t1, acc[3][0], acc[2][0]), sel(t1, acc[1][0], acc[0][0])));
        sts32f(sb + SM_OP + (w * 64 + 16 * t + 8 + g) * 4, sel(t2, sel(t1, acc[3][2], acc[2][2]), sel(t1, acc[1][2], acc[0][2])));
        cbar();
        if (w == 0) {
            float2 sum = make_float2(0.f, 0.f);
#pragma unroll
            for (int i = 0; i < 8; i++) { const float2 u = lds64f(sb + SM_OP + (i * 64 + 2 * lane) * 4); sum.x += u.x; sum.y += u.y; }
            const uint32_t v = pack2(sum.x, sum.y), a = sb + SM_Q + rank * 128 + lane * 4;
            st_async_b32(mapa(a, rank ^ 1), v, mapa(sb + BAR_XQ, rank ^ 1));
            st_async_b32(mapa(a, rank), v, mapa(sb + BAR_XQ, rank));
        }
        mbar_wait_cluster(sb + BAR_XQ, 0);
    }

    Pkt2 mga, msb, mcb;
    uint32_t tx0, tx1;
    const uint2* tmp = &g_mod[ob][32 * w + 2 * (lane & 15)];
    {
        uint4 Q[4];
        uint32_t koff[4];
#pragma unroll
        for (int i = 0; i < 4; i++) {
            const int ch = t + 4 * (i ^ (g & 1));
            Q[i] = lds128(sb + SM_Q + ch * 16);
            koff[i] = (sub * 16 + g) * 256 + ch * 16;
        }
        float mx = -INFINITY;
        int stage = N_K + grp, phase = 0;
#pragma unroll 1
        for (int it = 0; it < NT / 2; it++) {
            const uint32_t tb = sb + SM_RING + stage * TILE_BYTES;
            mbar_wait(sb + BAR_FULL + 8 * stage, phase);
            uint4 Ka[4], Kb[4];
#pragma unroll
            for (int i = 0; i < 4; i++) { Ka[i] = lds128(tb + koff[i]); Kb[i] = lds128(tb + koff[i] + 2048); }
            float c0[4] = {0.f, 0.f, 0.f, 0.f}, c1[4] = {0.f, 0.f, 0.f, 0.f};
#pragma unroll
            for (int i = 0; i < 4; i++) {
                mma(c0, Ka[i].x, Kb[i].x, Ka[i].y, Kb[i].y, Q[i].x, Q[i].y);
                mma(c1, Ka[i].z, Kb[i].z, Ka[i].w, Kb[i].w, Q[i].z, Q[i].w);
            }
            __syncwarp();
            if (lane == 0) mbar_arrive_n(sb + BAR_EMPTY + 8 * stage, 2);
            const float lo = (g & 1) ? c0[1] + c1[1] : c0[0] + c1[0];
            const float hi = (g & 1) ? c0[3] + c1[3] : c0[2] + c1[2];
            const float sc = rbf(rbf(t1 ? hi : lo) * 0.08838834764831845f);
            mx = fmaxf(mx, sc);
            if (t < 2) sts16(sb + SM_P + ((2 * it + grp) * 128 + rank * 64 + sub * 16 + 4 * (g >> 1) + 2 * t + (g & 1)) * 2, __float_as_uint(sc) >> 16);
            stage += 2;
            if (stage >= STAGES) { stage -= STAGES; phase ^= 1; }
        }

        mga = ld_pkt2(tmp + 2 * 256); msb = ld_pkt2(tmp + 3 * 256); mcb = ld_pkt2(tmp + 4 * 256);
        const __nv_bfloat16* xp = q_.x + ob * D_ + 64 * w + 4 * (lane & 8) + (lane & 7);
        tx0 = ldg16(xp) | ldg16(xp + 8) << 16;
        tx1 = ldg16(xp + 16) | ldg16(xp + 24) << 16;

        asm volatile("cp.async.wait_all;" ::: "memory");

#pragma unroll
        for (int m = 1; m < 32; m <<= 1) mx = fmaxf(mx, __shfl_xor_sync(~0u, mx, m));
        if (lane == 0) sts32f(sb + SM_RED + w * 4, mx);
        cbar();
        {
            const float4 u = lds128f(sb + SM_RED), v = lds128f(sb + SM_RED + 16);
            mx = fmaxf(fmaxf(fmaxf(u.x, u.y), fmaxf(u.z, u.w)), fmaxf(fmaxf(v.x, v.y), fmaxf(v.z, v.w)));
        }
        const uint32_t pa = sb + SM_P + (tid >> 3) * 256 + rank * 128 + (tid & 7) * 16;
        const uint4 s0 = lds128(pa);
        const float sc[8] = {bf_lo(s0.x), bf_hi(s0.x), bf_lo(s0.y), bf_hi(s0.y), bf_lo(s0.z), bf_hi(s0.z), bf_lo(s0.w), bf_hi(s0.w)};
        float l = 0.f;
#pragma unroll
        for (int i = 0; i < 8; i++) l += __expf(sc[i] - mx);
#pragma unroll
        for (int m = 1; m < 32; m <<= 1) l += __shfl_xor_sync(~0u, l, m);
        if (lane == 0) sts32f(sb + SM_RED + 32 + w * 4, l);
        cbar();
        {
            const float4 u = lds128f(sb + SM_RED + 32), v = lds128f(sb + SM_RED + 48);
            l = ((u.x + u.y) + (u.z + u.w)) + ((v.x + v.y) + (v.z + v.w));
        }
        if (tid == 0) st_async_v2(mapa(sb + SM_ML, rank ^ 1), mx, l, mapa(sb + BAR_XML, rank ^ 1));
        mbar_wait_cluster(sb + BAR_XML, 0);
        const float2 o = lds64f(sb + SM_ML);
        const float m = fmaxf(mx, o.x);
        const float inv = __fdividef(1.0f, l * __expf(mx - m) + o.y * __expf(o.x - m));
        const uint32_t p0 = pack2(__expf(sc[0] - m) * inv, __expf(sc[1] - m) * inv), p1 = pack2(__expf(sc[2] - m) * inv, __expf(sc[3] - m) * inv);
        const uint32_t p2 = pack2(__expf(sc[4] - m) * inv, __expf(sc[5] - m) * inv), p3 = pack2(__expf(sc[6] - m) * inv, __expf(sc[7] - m) * inv);
        st_async_v4(mapa(pa, rank ^ 1), p0, p1, p2, p3, mapa(sb + BAR_XP, rank ^ 1));
        sts128(pa, p0, p1, p2, p3);
        cbar();
        mbar_wait_cluster(sb + BAR_XP, 0);
    }

#pragma unroll 1
    for (uint32_t n = 0; n < SPIN_LIMIT && !__all_sync(~0u, pkt_ok(mga, tag) && pkt_ok(msb, tag) && pkt_ok(mcb, tag)); n++) {
        mga = ld_pkt2(tmp + 2 * 256); msb = ld_pkt2(tmp + 3 * 256); mcb = ld_pkt2(tmp + 4 * 256);
    }
    const uint32_t ga0 = lo32(mga.a), ga1 = lo32(mga.b), sb0 = lo32(msb.a), sb1 = lo32(msb.b);
    const uint32_t cb0 = hadd2(ONE2, lo32(mcb.a)), cb1 = hadd2(ONE2, lo32(mcb.b));
    const int wb = 4 * rank + sub;
    u64 red_p = s_line(e1_blk(1, wb), 2 * b) + lane * 4, red2_p = s_line(e1_blk(1, wb), 4 + b) + lane * 4;

    PIN64(red_p); PIN64(red2_p);
    float oa[4][4];
#pragma unroll
    for (int i = 0; i < 4; i++) { oa[i][0] = oa[i][1] = oa[i][2] = oa[i][3] = 0.f; }
    {
        int stage = N_V % STAGES, phase = tile_phase(N_V);
        auto v_tiles = [&](int v0, int v1) {
#pragma unroll 1
            for (int v = v0; v < v1; v++) {
                const uint32_t tb = sb + SM_RING + stage * TILE_BYTES + grp * 8192 + (sw128 ^ (sub * 32));
                uint2 P[4];
#pragma unroll
                for (int i = 0; i < 4; i++) P[i] = lds64(sb + SM_P + v * 256 + grp * 128 + i * 32 + t * 8);
                mbar_wait(sb + BAR_FULL + 8 * stage, phase);
                uint32_t a[4][4];
#pragma unroll
                for (int i = 0; i < 4; i++) ldsm4t(tb + i * 2048, a[i]);
#pragma unroll
                for (int i = 0; i < 4; i++) mma4(oa[i], a[i], P[i].x, P[i].y);
                __syncwarp();
                if (lane == 0) mbar_arrive(sb + BAR_EMPTY + 8 * stage);
                if (++stage == STAGES) { stage = 0; phase ^= 1; }
            }
        };
        v_tiles(0, MEET_AT);
        asm volatile("bar.sync 2, 288;" ::: "memory");
        v_tiles(MEET_AT, NT);
    }

    if (t < 2) {
        const uint32_t a = sb + SM_OP + rank * 512 + w * 64 + (g >> 1) * 16 + (g & 1) * 4 + t * 8;
        const uint32_t v = __float_as_uint(sel(t1, (oa[0][2] + oa[1][2]) + (oa[2][2] + oa[3][2]), (oa[0][0] + oa[1][0]) + (oa[2][0] + oa[3][0])));
        st_async_b32(mapa(a, rank ^ 1), v, mapa(sb + BAR_XO, rank ^ 1));
        st_async_b32(mapa(a, rank), v, mapa(sb + BAR_XO, rank));
    }
    __syncwarp();
    mbar_wait_cluster(sb + BAR_XO, 0);

    {
        float acc[4][4];
        const uint32_t o_ld = sb + SM_OP + grp * 512 + (lane & 15) * 16 + vb * 8, x_st = sb + SM_PART + 4096 + sub * 1024 + lane * 16;
        const float2 u = lds64f(o_ld), v = lds64f(o_ld + 256);
        const uint32_t o2 = pack2(u.x + v.x, u.y + v.y);
        uint32_t bo[8];
#pragma unroll
        for (int i = 0; i < 8; i++) bo[i] = __shfl_sync(~0u, o2, 16 * (i & 1) + 4 * (i >> 1) + t);
        float4 x0 = make_float4(0.f, 0.f, 0.f, 0.f), x1 = x0;
#pragma unroll
        for (int i = 0; i < 4; i++) { acc[i][0] = acc[i][1] = acc[i][2] = acc[i][3] = 0.f; }
        static_assert(N_WO % STAGES + 4 <= STAGES, "wo tiles occupy consecutive slots");
        const uint32_t wa = sb + slot_addr(N_WO) + grp * 2 * TILE_BYTES + sub * 4096, wbar = sb + full_bar(N_WO) + grp * 16;
#pragma unroll
        for (int j = 0; j < 2; j++) {
            if (j == 1 && grp) { asm volatile("bar.sync 8, 256;" ::: "memory"); x0 = lds128f(x_st); x1 = lds128f(x_st + 512); }
            mbar_wait(wbar + 8 * j, tile_phase(N_WO));
            if (j == 1) { }
#pragma unroll
            for (int i = 0; i < 8; i++) ldsm4t(wa + j * TILE_BYTES + (i >> 2) * 2048 + (sw128 ^ ((i & 3) * 32)), A[8 * j + i]);
#pragma unroll
            for (int i = 0; i < 8; i++) mma4(acc[i & 3], A[8 * j + i], bo[4 * j + 2 * (i >> 2)], bo[4 * j + 2 * (i >> 2) + 1]);
        }
        if (!grp) {
            sts128f(x_st, acc[0][0], acc[1][0], acc[2][0], acc[3][0]); sts128f(x_st + 512, acc[0][2], acc[1][2], acc[2][2], acc[3][2]);
            asm volatile("bar.arrive 8, 256;" ::: "memory");
        } else {
            acc[0][0] += x0.x; acc[1][0] += x0.y; acc[2][0] += x0.z; acc[3][0] += x0.w; acc[0][2] += x1.x; acc[1][2] += x1.y; acc[2][2] += x1.z; acc[3][2] += x1.w;
            const float r0 = sel(t2, sel(t1, 1.0f, acc[1][0]), sel(t1, acc[0][2], acc[0][0]));
            const float r1 = sel(t2, sel(t1, 1.0f, acc[3][0]), sel(t1, acc[2][2], acc[2][0]));
            const float r2 = sel(t2, 1.0f, sel(t1, acc[3][2], acc[1][2]));
            asm volatile("red.relaxed.gpu.global.add.f32 [%0], %2;\nred.relaxed.gpu.global.add.f32 [%0 + 256], %3;\nred.relaxed.gpu.global.add.f32 [%1], %4;"
                         :: "l"(red_p), "l"(red2_p), "f"(r0), "f"(r1), "f"(r2) : "memory");
            asm volatile("red.relaxed.gpu.global.add.f32 [%0], %2;\nred.relaxed.gpu.global.add.f32 [%0 + 256], %3;\nred.relaxed.gpu.global.add.f32 [%1], %4;"
                         :: "l"(red_p ^ 4096), "l"(red2_p ^ 4096), "f"(r0), "f"(r1), "f"(r2) : "memory");
        }
    }

    constexpr uint32_t CNT = 0x42000000u;
    if (is_gu) {
        uint32_t side;
        asm volatile("ld.volatile.shared.u32 %0, [%1];" : "=r"(side) : "r"(sb + SM_SIDE) : "memory");
        u64 acc_p = (s_line(e1_blk(0, w), lane >> 3) + (lane & 7) * 16) ^ side, acc2_p = (s_line(e1_blk(0, w), 4 + ob) + (lane & 7) * 16) ^ side;
        const int eb = e1_blk(w >> 2, w & 3);
        const bool near = __all_sync(~0u, (w >> 2) * 4096 == side);
        u64 out_p = s_line(eb, lane >> 3) + S_OUT + (lane & 7) * 16, out2_p = s_line(eb, 4 + ob) + S_OUT + (lane & 15) * 8;
        u64 gb_p = (s_line(e1_blk(0, w), 6 + ob) + (lane & 15) * 8) ^ side, y_p = (u64)(q_.out + t1 * D_ + 64 * w + 4 * t2 + g);
        PIN64(acc_p); PIN64(acc2_p); PIN64(out_p); PIN64(out2_p); PIN64(gb_p); PIN64(y_p);
        auto keep = [&](uint32_t x) { return __shfl_sync(~0u, x, lane); };
        const int src = keep(8 * (g & 2) + t), src1 = keep(src + 4), src2 = keep(src + 8), src3 = keep(src + 12);
        const uint32_t p_st = keep(sb + SM_PART + w * 512 + lane * 16), r_st = keep(sb + SM_RED + (vb * 8 + w) * 8);
        tx0 = keep(tx0); tx1 = keep(tx1);
        uint32_t w2a[4];
#pragma unroll
        for (int i = 0; i < 4; i++) w2a[i] = keep(sb + slot_addr(N_FFN + 4) + w * 4096 + (sw128 ^ (i * 32)));
        const uint32_t hva = keep(sb + SM_Q + ((g & 2) * 2 + t) * 16), w2b = keep(sb + BAR_W2 + 8 * (w * NW >> 3)), t2k = keep(t2);
        const uint32_t g1 = g & 1;
        uint32_t cp[8], cn[8];
        float acc[4][4];
#pragma unroll
        for (int i = 0; i < 8; i++) {
            cp[i] = __shfl_sync(~0u, (i & 1) ? cb1 : cb0, 4 * (i >> 1) + src);
            cn[i] = selu(g1, __shfl_sync(~0u, (i & 1) ? sb1 : sb0, 4 * (i >> 1) + src), cp[i]);
        }
        const int frow = (lane & 7) + (lane & 16);
        const uint32_t fa = sb + slot_addr(N_FFN) + grp * 2 * TILE_BYTES + (64 * sub + frow) * 64 + ((lch ^ ((frow >> 1) & 3)) << 4);
        mbar_wait(sb + BAR_FFN + 8 * (w * NQ >> 3), 0);
        uint4 u = ld_strong128(acc_p), v = ld_strong128(acc2_p);
#pragma unroll
        for (int i = 0; i < 16; i++) ldsm4t((fa ^ ((i & 1) * 32)) + (i >> 3) * 2048 + ((i >> 2) & 1) * 512 + ((i >> 1) & 1) * TILE_BYTES, A[i]);
#pragma unroll
        for (int i = 0; i < 4; i++) { acc[i][0] = acc[i][1] = acc[i][2] = acc[i][3] = 0.f; }
#pragma unroll
        for (int i = 0; i < 16; i++)
            mma4(acc[i & 3], A[i], cn[2 * (i >> 2)], cn[2 * (i >> 2) + 1]);
        sts128f(sb + SM_P + w * 1024 + lane * 16, sel(t2, acc[1][0], acc[0][0]), sel(t2, acc[3][0], acc[2][0]), sel(t2, acc[1][2], acc[0][2]), sel(t2, acc[3][2], acc[2][2]));
        sts128f(sb + SM_P + w * 1024 + 512 + lane * 16, sel(t2, acc[1][1], acc[0][1]), sel(t2, acc[3][1], acc[2][1]), sel(t2, acc[1][3], acc[0][3]), sel(t2, acc[3][3], acc[2][3]));
        bar_arrive<3>();
#pragma unroll
        for (int i = 0; i < 8; i++) cn[i] = selu(g1, cp[i] ^ 0x80008000u, 0u);
        settle(tag, sb + SM_OP, cn[0], cn[1], cn[2], cn[3]); settle(tag, sb + SM_OP, cn[4], cn[5], cn[6], cn[7]);
        for (uint32_t n = 0; !__all_sync(~0u, u.w == CNT && v.w == CNT) && n < SPIN_LIMIT; n++) { u = ld_strong128(acc_p); v = ld_strong128(acc2_p); }
        const uint32_t x0 = hadd2(tx0, hmul2(ga0, pack2(__uint_as_float(u.x), __uint_as_float(u.y))));
        const uint32_t x1 = hadd2(tx1, hmul2(ga1, pack2(__uint_as_float(u.z), __uint_as_float(selu(lane & 8, v.y, v.x)))));
        float c[4] = {0.f, 0.f, 0.f, 0.f};
        mma(c, x0, ONE2, x1, ONE2, x0, x1);
#pragma unroll
        for (int i = 0; i < 4; i++) { acc[i][0] = acc[i][1] = acc[i][2] = acc[i][3] = 0.f; }
        float q, s;
#pragma unroll
        for (int s4 = 0; s4 < 4; s4++) {
            const int from = s4 == 0 ? src : s4 == 1 ? src1 : s4 == 2 ? src2 : src3;
            uint32_t b0 = __shfl_sync(~0u, x0, from), b1 = __shfl_sync(~0u, x1, from);
            b0 = hfma2(b0, cp[2 * s4], hmul2(b0, cn[2 * s4]));
            b1 = hfma2(b1, cp[2 * s4 + 1], hmul2(b1, cn[2 * s4 + 1]));
#pragma unroll
            for (int i = 0; i < 4; i++) mma4(acc[i], A[4 * s4 + i], b0, b1);
            if (s4 == 0) { q = sel(g1, c[1], c[0]); s = c[2] + c[3]; q += __shfl_xor_sync(~0u, q, 4); s += __shfl_xor_sync(~0u, s, 9); }
            if (s4 == 1) q += __shfl_xor_sync(~0u, q, 9);
            if (s4 == 2) { if (lane == 0 || lane == 18) sts64f(r_st, s, fmaxf(fmaf(s * (-1.0f / 64), s, q), 0.f)); }
        }
        sts128f(p_st, sel(t2, acc[1][0] + acc[1][1], acc[0][0] + acc[0][1]), sel(t2, acc[3][0] + acc[3][1], acc[2][0] + acc[2][1]),
                sel(t2, acc[1][2] + acc[1][3], acc[0][2] + acc[0][3]), sel(t2, acc[3][2] + acc[3][3], acc[2][2] + acc[2][3]));
        bar_arrive<4>();
        auto w2_frags = [&]() {
            mbar_wait(w2b, 0);
#pragma unroll
            for (int i = 0; i < 8; i++) ldsm4t(w2a[i & 3] + (i >> 2) * 2048, A[i]);
        };
        if (!near) w2_frags();
#pragma unroll
        for (int i = 0; i < 4; i++) { acc[i][0] = acc[i][1] = acc[i][2] = acc[i][3] = 0.f; }
        bar_sync<5>();
        const uint4 hv = lds128(hva);
        if (near) w2_frags();
#pragma unroll
        for (int i = 0; i < 4; i++) mma4(acc[i], A[i], hv.x, hv.y);
#pragma unroll
        for (int i = 0; i < 4; i++) mma4(acc[i], A[4 + i], hv.z, hv.w);
        float r[4], o[6];
#pragma unroll
        for (int i = 0; i < 4; i++) r[i] = sel(t2k, acc[i][2], acc[i][0]);
        asm volatile("atom.relaxed.gpu.global.add.v4.f32 {%0, %1, %2, %3}, [%4], {%5, %6, %7, %8};"
                     : "=f"(o[0]), "=f"(o[1]), "=f"(o[2]), "=f"(o[4]) : "l"(out_p), "f"(r[0]), "f"(r[1]), "f"(r[2]), "f"(1.0f) : "memory");
        asm volatile("atom.relaxed.gpu.global.add.v2.f32 {%0, %1}, [%2], {%3, %4};"
                     : "=f"(o[3]), "=f"(o[5]) : "l"(out2_p), "f"(r[3]), "f"(1.0f) : "memory");
        uint2 gb = ld_strong64(gb_p);
        uint32_t xo[2];
#pragma unroll
        for (int j = 0; j < 2; j++) {
            const uint32_t e0 = __shfl_sync(~0u, x0, 16 * t1 + 8 * j + g), e1 = __shfl_sync(~0u, x1, 16 * t1 + 8 * j + g);
            xo[j] = __byte_perm(e0, e1, t2 ? 0x7632 : 0x5410);
        }
        const uint32_t f0 = pack2(o[0] + r[0], o[1] + r[1]), f1 = pack2(o[2] + r[2], o[3] + r[3]);
#pragma unroll 1
        for (uint32_t n = 0; n < SPIN_LIMIT; n++) {
            const uint32_t y0 = hadd2(xo[0], hmul2(gb.x, f0)), y1 = hadd2(xo[1], hmul2(gb.y, f1));
            uint32_t late;
            asm volatile("{\n.reg .pred p, q, m;\n.reg .b16 a, b, c, d;\n"
                         "mov.b32 {a, b}, %6;\nmov.b32 {c, d}, %7;\nsetp.ne.b16 m, a, 0xffff;\nsetp.ne.and.b16 m, b, 0xffff, m;\nsetp.ne.and.b16 m, c, 0xffff, m;\nsetp.ne.and.b16 m, d, 0xffff, m;\n"
                         "setp.eq.and.f32 p, %4, 0f42280000, m;\nsetp.eq.and.f32 q, %5, 0f42280000, m;\n"
                         "mov.b32 {a, b}, %2;\nmov.b32 {c, d}, %3;\n"
                         "@p st.global.u16 [%1], a;\n@p st.global.u16 [%1 + 32], b;\n@p st.global.u16 [%1 + 64], c;\n@q st.global.u16 [%1 + 96], d;\n"
                         "vote.sync.all.pred m, m, 0xffffffff;\nselp.u32 %0, 0, 1, m;\n}"
                         : "=r"(late) : "l"(y_p), "r"(y0), "r"(y1), "f"(o[4]), "f"(o[5]), "r"(gb.x), "r"(gb.y) : "memory");
            if (!late) break;
            gb = ld_strong64(gb_p);
        }
    } else if (is_gb) {
        const uint32_t fa = sb + slot_addr(N_FFN) + grp * 8192 + (64 * sub + lrow) * 32 + ((lch ^ ((lrow >> 2) & 1)) << 4);
        const int dl = (lane & 7) * 4 + ((lane >> 3) & 1) * 2 + ob;
        u64 gb_p = s_line(2 * (role >> 2), 6 + (dl >> 4)) + (dl & 15) * 8 + (role & 3) * 2;
        PIN64(gb_p);
        uint32_t bs[8];
#pragma unroll
        for (int i = 0; i < 8; i++) bs[i] = __shfl_sync(~0u, (i & 1) ? sc1 : sc0, 4 * (i >> 1) + 16 * ((g >> 1) & 1) + t);
        const uint32_t c_st = sb + SM_PART + (w * 32 + t1 * 16 + (t >> 1) * 8 + g) * 4;
        settle(tag, sb + SM_OP, bs[0], bs[1], bs[2], bs[3]); settle(tag, sb + SM_OP, bs[4], bs[5], bs[6], bs[7]); settle(tag, sb + SM_OP, c_st, fa, 0, 0);
        mbar_wait(sb + BAR_FFN + 8 * grp, 0);
        float c[4][4];
#pragma unroll
        for (int s4 = 0; s4 < 4; s4++) ldsm4t(fa + s4 * 512, A[s4]);
#pragma unroll
        for (int s4 = 0; s4 < 4; s4++) { c[s4][0] = c[s4][1] = c[s4][2] = c[s4][3] = 0.f; mma4(c[s4], A[s4], bs[2 * s4], bs[2 * s4 + 1]); }
        sts32f(c_st, sel(t2, (c[0][2] + c[1][2]) + (c[2][2] + c[3][2]), (c[0][0] + c[1][0]) + (c[2][0] + c[3][0])));
        cbar();
        if (w == 0) {
            float u[8];
#pragma unroll
            for (int i = 0; i < 8; i++) u[i] = lds32f(sb + SM_PART + i * 128 + lane * 4);
            const uint16_t v = (uint16_t)pack2(((u[0] + u[1]) + (u[2] + u[3])) + ((u[4] + u[5]) + (u[6] + u[7])), 0.f);
            asm volatile("st.relaxed.gpu.global.u16 [%0], %1;\nst.relaxed.gpu.global.u16 [%0 + 4096], %1;" :: "l"(gb_p), "h"(v) : "memory");
        }
    }
}

typedef CUresult (*EncodeFn)(CUtensorMap*, CUtensorMapDataType, cuuint32_t, void*, const cuuint64_t*, const cuuint64_t*,
                             const cuuint32_t*, const cuuint32_t*, CUtensorMapInterleave, CUtensorMapSwizzle,
                             CUtensorMapL2promotion, CUtensorMapFloatOOBfill);

void make_map(EncodeFn enc, CUtensorMap* m, void* ptr, int cols, int rows, int box_cols, int box_rows, CUtensorMapSwizzle sw) {
    cuuint64_t gd[2] = {(cuuint64_t)cols, (cuuint64_t)rows}, gs[1] = {(cuuint64_t)cols * 2};
    cuuint32_t bd[2] = {(cuuint32_t)box_cols, (cuuint32_t)box_rows}, es[2] = {1, 1};
    enc(m, CU_TENSOR_MAP_DATA_TYPE_BFLOAT16, 2, ptr, gd, gs, bd, es, CU_TENSOR_MAP_INTERLEAVE_NONE, sw,
        CU_TENSOR_MAP_L2_PROMOTION_NONE, CU_TENSOR_MAP_FLOAT_OOB_FILL_NONE);
}

}

extern "C" void kernel_launch(void* const* d_in, const int* in_sizes, int n_in, void* d_out, int out_size) {
    (void)in_sizes; (void)n_in; (void)out_size;
    static EncodeFn enc = nullptr;
    if (!enc) {
        void* fn = nullptr;
        cudaDriverEntryPointQueryResult qr;
        cudaGetDriverEntryPoint("cuTensorMapEncodeTiled", &fn, cudaEnableDefault, &qr);
        enc = (EncodeFn)fn;
        cudaFuncSetAttribute(fused_decode_kernel, cudaFuncAttributeMaxDynamicSharedMemorySize, SMEM_BYTES);
    }
    Params p;
    Ptrs q;
    make_map(enc, &p.m_wmod, d_in[10], MODW, D_, 32, 256, CU_TENSOR_MAP_SWIZZLE_64B);
    make_map(enc, &p.m_wq, d_in[3], QD, D_, 64, 128, CU_TENSOR_MAP_SWIZZLE_128B);
    make_map(enc, &p.m_v, d_in[2], DH, 64 * SK, 64, 128, CU_TENSOR_MAP_SWIZZLE_128B);
    {
        cuuint64_t gd[3] = {64, QD, 8}, gs[2] = {D_ * 2, 128};
        cuuint32_t bd[3] = {64, 32, 4}, es[3] = {1, 1, 1};
        enc(&p.m_wo, CU_TENSOR_MAP_DATA_TYPE_BFLOAT16, 3, d_in[4], gd, gs, bd, es, CU_TENSOR_MAP_INTERLEAVE_NONE,
            CU_TENSOR_MAP_SWIZZLE_128B, CU_TENSOR_MAP_L2_PROMOTION_NONE, CU_TENSOR_MAP_FLOAT_OOB_FILL_NONE);
    }
    for (int i = 0; i < 2; i++) {
        cuuint64_t gd[4] = {FF, 2, 8, D_ / 16}, gs[3] = {8 * FF * 2, FF * 2, 16 * FF * 2};
        cuuint32_t bd[4] = {32, 2, 8, 32 / NQ}, es[4] = {1, 1, 1, 1};
        enc(i ? &p.m_w3 : &p.m_w1, CU_TENSOR_MAP_DATA_TYPE_BFLOAT16, 4, d_in[6 + i], gd, gs, bd, es, CU_TENSOR_MAP_INTERLEAVE_NONE,
            CU_TENSOR_MAP_SWIZZLE_64B, CU_TENSOR_MAP_L2_PROMOTION_NONE, CU_TENSOR_MAP_FLOAT_OOB_FILL_NONE);
    }
    {
        cuuint64_t gd[5] = {64, 2, 8, FF / 16, 8}, gs[4] = {8 * D_ * 2, D_ * 2, 16 * D_ * 2, 128};
        cuuint32_t bd[5] = {64, 2, 8, 2, 8 / NW}, es[5] = {1, 1, 1, 1, 1};
        enc(&p.m_w2, CU_TENSOR_MAP_DATA_TYPE_BFLOAT16, 5, d_in[8], gd, gs, bd, es, CU_TENSOR_MAP_INTERLEAVE_NONE,
            CU_TENSOR_MAP_SWIZZLE_128B, CU_TENSOR_MAP_L2_PROMOTION_NONE, CU_TENSOR_MAP_FLOAT_OOB_FILL_NONE);
    }
    make_map(enc, &p.m_gb, d_in[10], MODW, D_, 16, 256, CU_TENSOR_MAP_SWIZZLE_32B);
    q.x = (const __nv_bfloat16*)d_in[0];
    q.kwin = (const __nv_bfloat16*)d_in[1] + (size_t)(SK - WIN) * DH;
    q.c = (const __nv_bfloat16*)d_in[9];
    q.out = (__nv_bfloat16*)d_out;
    fused_decode_kernel<<<NCTA, THREADS, SMEM_BYTES, cudaStreamPerThread>>>(q, p);
}
```
